```python
import torch

def _softmax(x, axis=-1):
    return torch.softmax(x, dim=axis)
def _gelu(x):
    return torch.nn.functional.gelu(x, approximate="tanh")
def _silu(x):
    return torch.nn.functional.silu(x)
def _sigmoid(x):
    return torch.sigmoid(x)
def _layernorm(x, axis=-1, eps=1e-5):
    m = x.mean(dim=axis, keepdim=True)
    v = x.var(dim=axis, keepdim=True, unbiased=False)
    return (x - m) / torch.sqrt(v + eps)
def _scatter_add(tgt, idx, src, axis=0):
    return tgt.clone().index_add_(axis, idx, src)
def _segment_sum(src, seg, n):
    out = torch.zeros((n,) + src.shape[1:], dtype=src.dtype)
    return out.index_add_(0, seg, src)
def _pad(x, pw):
    flat = tuple(v for pair in reversed(pw) for v in pair)
    return torch.nn.functional.pad(x, flat)

kernel_name = 'parallel_sum__sliding_block_cached__glu_gated_reglu__decode'

def setup_inputs():

    _w = (lambda a: (lambda t: t.to(torch.bfloat16) if t.is_floating_point() else t)(torch.as_tensor(a)))
    def _A_setup():
        B, Sq, D = 2, 1, 448
        Hq, Hkv, Sk, Dh = 16, 8, 32768, 256
        assert Hq % Hkv == 0, (Hq, Hkv)
        return {
            "x": _w((lambda *s: torch.randn(*s, dtype=torch.bfloat16) * 0.05)(B, Sq, D)),
            "k_cache": _w((lambda *s: torch.randn(*s, dtype=torch.bfloat16) * 1.6)(B, Hkv, Sk, Dh)),
            "v_cache": _w((lambda *s: torch.randn(*s, dtype=torch.bfloat16) * 0.8)(B, Hkv, Sk, Dh)),
            "wq": _w((lambda *s: torch.randn(*s, dtype=torch.bfloat16) * 1.6)(D, Hq * Dh) * (D ** -0.5)),
            "wo": _w((lambda *s: torch.randn(*s, dtype=torch.bfloat16) * 0.8)(Hq * Dh, D) * ((Hq * Dh) ** -0.5)),
        }
    _A_in = _A_setup()

    def _B_setup():
        B, S, D, F = 2, 1, 448, 1792
        return {
            "x": _w((lambda *s: torch.randn(*s, dtype=torch.bfloat16) * 0.05)(B, S, D)),
            "W_gate": _w((lambda *s: torch.randn(*s, dtype=torch.bfloat16) * 0.4)(D, F) * (2.0 / D) ** 0.5),
            "W_up": _w((lambda *s: torch.randn(*s, dtype=torch.bfloat16) * 0.4)(D, F) * (2.0 / D) ** 0.5),
            "W_down": _w((lambda *s: torch.randn(*s, dtype=torch.bfloat16) * 0.4)(F, D) * (1.0 / F) ** 0.5),
        }
    _B_in = _B_setup()

    return {
        "A_x": _A_in["x"],
        "A_k_cache": _A_in["k_cache"],
        "A_v_cache": _A_in["v_cache"],
        "A_wq": _A_in["wq"],
        "A_wo": _A_in["wo"],
        "B_x": _B_in["x"],
        "B_W_gate": _B_in["W_gate"],
        "B_W_up": _B_in["W_up"],
        "B_W_down": _B_in["W_down"],
    }

def reference(A_x, A_k_cache, A_v_cache, A_wq, A_wo, B_x, B_W_gate, B_W_up, B_W_down):
    def _A_ref(x, k_cache, v_cache, wq, wo):
        B, Sq, D = x.shape
        Hq, Dh = 16, 256
        Hkv, Sk = k_cache.shape[1], k_cache.shape[2]
        W = min(4096, max(256, Sk // 4))
        rep = Hq // Hkv
        q = (lambda x, *d: x.permute(*d))((x @ wq).reshape(B, Sq, Hq, Dh), 0, 2, 1, 3)
        k = (lambda x, n, axis: torch.repeat_interleave(x, n, dim=axis))(k_cache[:, :, Sk - W:, :], rep, axis=1)
        v = (lambda x, n, axis: torch.repeat_interleave(x, n, dim=axis))(v_cache[:, :, Sk - W:, :], rep, axis=1)
        scores = torch.einsum("bhqd,bhkd->bhqk", q, k) * (Dh ** -0.5)
        p = _softmax(scores, axis=-1)
        o = torch.einsum("bhqk,bhkd->bhqd", p, v)
        return (lambda x, *d: x.permute(*d))(o, 0, 2, 1, 3).reshape(B, Sq, Hq * Dh) @ wo

    def _B_ref(x, W_gate, W_up, W_down):
        gate = torch.einsum("bsd,df->bsf", x, W_gate)
        up = torch.einsum("bsd,df->bsf", x, W_up)
        gate = gate * (lambda x, dt: x.to(dt))(gate > 0, gate.dtype)
        h = gate * up
        return torch.einsum("bsf,fd->bsd", h, W_down)

    x = A_x
    xn = _layernorm(x, axis=-1)
    return x + _A_ref(xn, A_k_cache, A_v_cache, A_wq, A_wo) + _B_ref(xn, B_W_gate, B_W_up, B_W_down)
```

```cpp
#include <cuda_runtime.h>
#include <cuda_bf16.h>
#include <stdint.h>

namespace {

constexpr int D_MODEL = 448;
constexpr int SK      = 32768;
constexpr int WIN     = 4096;
constexpr int DH      = 256;
constexpr int QCOLS   = 4096;
constexpr int FF      = 1792;
constexpr int NCTA    = 128;
constexpr int NFFN    = 112;
constexpr int NTHREADS = 352;

constexpr int NS       = 6;
constexpr int GRP      = 4096 + 16;
constexpr int SLOT     = 8 * GRP;
constexpr int GRP_WO   = 4 * 896 + 16;
constexpr int GRP_DN   = 2 * 896 + 16;
constexpr int NSTAGE   = 18;
constexpr int SROW     = 144;
constexpr int XROW     = 912;

constexpr int SM_RING  = 0;
constexpr int SM_STRIP = SM_RING + (NS - 2) * SLOT;
constexpr int SM_S    = SM_RING + NS * SLOT;
constexpr int SM_P    = SM_S + 2 * 520 * 4;
constexpr int SM_Q    = SM_P + 2 * 260 * 4;
constexpr int SM_XN   = SM_Q + 2 * 264 * 2;
constexpr int SM_STAT = SM_XN + 2 * XROW;
constexpr int SM_H    = SM_STAT + 2 * 8 * 2 * 4;
constexpr int SM_OB   = SM_H + 2 * 16 * 2;
constexpr int SM_BAR  = SM_OB + 2 * 16 * 4;
constexpr int SM_TAG  = SM_BAR + (2 * NS + 3) * 8;
constexpr int SM_TOTAL = SM_TAG + 8;
static_assert(448 * SROW <= 2 * SLOT, "strip overlay");
static_assert(SM_Q % 16 == 0 && SM_XN % 16 == 0 && SM_OB % 16 == 0 && SM_P % 16 == 0 && SM_BAR % 8 == 0, "align");

constexpr int SPIN_LIMIT = 1 << 22;

struct Scratch {
    uint4    part[NCTA * 2 * 8 * 8];
    uint4    outp[NFFN * NCTA * 2];
    uint4    q[8 * 2 * 128];
    uint2    ml[8 * 2 * 2 * 8];
    unsigned epoch[NCTA * 8];
};
__device__ Scratch g_scratch;

#define TL(i)

__device__ __forceinline__ void mbar_init(uint32_t bar, uint32_t cnt) {
    asm volatile("mbarrier.init.shared::cta.b64 [%0], %1;" :: "r"(bar), "r"(cnt) : "memory");
}
__device__ __forceinline__ void mbar_expect_tx(uint32_t bar, uint32_t bytes) {
    asm volatile("mbarrier.arrive.expect_tx.shared::cta.b64 _, [%0], %1;" :: "r"(bar), "r"(bytes) : "memory");
}
__device__ __forceinline__ void mbar_arrive(uint32_t bar, uint32_t cnt) {
    asm volatile("mbarrier.arrive.shared::cta.b64 _, [%0], %1;" :: "r"(bar), "r"(cnt) : "memory");
}
__device__ __forceinline__ void mbar_wait(uint32_t bar, uint32_t parity) {
    asm volatile("{\n"
                 ".reg .pred p, q;\n"
                 ".reg .u32 it;\n"
                 "mov.u32 it, 0;\n"
                 "WAIT_LOOP:\n"
                 "mbarrier.try_wait.parity.shared::cta.b64 p, [%0], %1;\n"
                 "@p bra WAIT_DONE;\n"
                 "add.u32 it, it, 1;\n"
                 "setp.lt.u32 q, it, %2;\n"
                 "@q bra WAIT_LOOP;\n"
                 "trap;\n"
                 "WAIT_DONE:\n"
                 "}" :: "r"(bar), "r"(parity), "n"(SPIN_LIMIT) : "memory");
}
__device__ __forceinline__ void bulk_g2s(uint32_t dst, const void* src, uint32_t bytes, uint32_t bar) {
    asm volatile("cp.async.bulk.shared::cluster.global.mbarrier::complete_tx::bytes [%0], [%1], %2, [%3];"
                 :: "r"(dst), "l"(src), "r"(bytes), "r"(bar) : "memory");
}
__device__ __forceinline__ void cp_async16(uint32_t dst, const void* src) {
    asm volatile("cp.async.cg.shared.global [%0], [%1], 16;" :: "r"(dst), "l"(src) : "memory");
}
__device__ __forceinline__ void cp_async_arrive(uint32_t bar) {
    asm volatile("cp.async.mbarrier.arrive.noinc.shared::cta.b64 [%0];" :: "r"(bar) : "memory");
}
__device__ __forceinline__ void bar_sync(int id, int n)   { asm volatile("bar.sync %0, %1;" :: "r"(id), "r"(n) : "memory"); }
__device__ __forceinline__ void bar_arrive(int id, int n) { asm volatile("bar.arrive %0, %1;" :: "r"(id), "r"(n) : "memory"); }

__device__ __forceinline__ uint32_t ld_poll1(const void* p) {
    uint32_t v;
    asm volatile("ld.relaxed.gpu.global.u32 %0, [%1];" : "=r"(v) : "l"(p) : "memory");
    return v;
}
__device__ __forceinline__ uint2 ld_poll2(const void* p) {
    uint2 v;
    asm volatile("ld.relaxed.gpu.global.v2.u32 {%0,%1}, [%2];" : "=r"(v.x), "=r"(v.y) : "l"(p) : "memory");
    return v;
}
__device__ __forceinline__ uint4 ld_poll4(const void* p) {
    uint4 v;
    asm volatile("ld.relaxed.gpu.global.v4.u32 {%0,%1,%2,%3}, [%4];" : "=r"(v.x), "=r"(v.y), "=r"(v.z), "=r"(v.w) : "l"(p) : "memory");
    return v;
}
__device__ __forceinline__ void ld_poll4_if(uint4& v, const void* p, uint32_t bad) {
    asm volatile("{\n.reg .pred p;\n.reg .b32 t;\nand.b32 t, %5, 1;\nsetp.ne.u32 p, t, 0;\n"
                 "@p ld.relaxed.gpu.global.v4.u32 {%0,%1,%2,%3}, [%4];\n}"
                 : "+r"(v.x), "+r"(v.y), "+r"(v.z), "+r"(v.w) : "l"(p), "r"(bad) : "memory");
}
__device__ __forceinline__ void st_pub4(void* p, uint4 v) {
    asm volatile("st.relaxed.gpu.global.v4.u32 [%0], {%1,%2,%3,%4};" :: "l"(p), "r"(v.x), "r"(v.y), "r"(v.z), "r"(v.w) : "memory");
}
__device__ __forceinline__ void st_pub2(void* p, uint32_t a, uint32_t b) {
    asm volatile("st.relaxed.gpu.global.v2.u32 [%0], {%1,%2};" :: "l"(p), "r"(a), "r"(b) : "memory");
}
__device__ __forceinline__ void st_pub1(void* p, uint32_t a) {
    asm volatile("st.relaxed.gpu.global.u32 [%0], %1;" :: "l"(p), "r"(a) : "memory");
}
__device__ __forceinline__ uint32_t tagf(float v, uint32_t tag) { return (__float_as_uint(v) & ~1u) | tag; }
__device__ __forceinline__ uint32_t bad2(uint32_t a, uint32_t b, uint32_t tag) {
    uint32_t r;
    asm("lop3.b32 %0, %1, %2, %3, 0x7E;" : "=r"(r) : "r"(a), "r"(b), "r"(tag));
    return r;
}
__device__ __forceinline__ uint32_t bad4(const uint4& v, uint32_t tag) { return bad2(v.x, v.y, tag) | bad2(v.z, v.w, tag); }
__device__ __forceinline__ bool warp_bad(uint32_t bad) { return __any_sync(0xffffffffu, bad & 1u); }

__device__ __forceinline__ void ldsm4(uint32_t addr, uint32_t (&a)[4]) {
    asm volatile("ldmatrix.sync.aligned.m8n8.x4.shared.b16 {%0,%1,%2,%3}, [%4];" : "=r"(a[0]), "=r"(a[1]), "=r"(a[2]), "=r"(a[3]) : "r"(addr) : "memory");
}
__device__ __forceinline__ void ldsm4t(uint32_t addr, uint32_t (&a)[4]) {
    asm volatile("ldmatrix.sync.aligned.m8n8.x4.trans.shared.b16 {%0,%1,%2,%3}, [%4];" : "=r"(a[0]), "=r"(a[1]), "=r"(a[2]), "=r"(a[3]) : "r"(addr) : "memory");
}
__device__ __forceinline__ void mma16816(float (&c)[4], const uint32_t (&a)[4], uint32_t b0, uint32_t b1) {
    asm volatile("mma.sync.aligned.m16n8k16.row.col.f32.bf16.bf16.f32 {%0,%1,%2,%3}, {%4,%5,%6,%7}, {%8,%9}, {%0,%1,%2,%3};"
                 : "+f"(c[0]), "+f"(c[1]), "+f"(c[2]), "+f"(c[3]) : "r"(a[0]), "r"(a[1]), "r"(a[2]), "r"(a[3]), "r"(b0), "r"(b1));
}
__device__ __forceinline__ float bf_lo(uint32_t u) { return __uint_as_float(u << 16); }
__device__ __forceinline__ float bf_hi(uint32_t u) { return __uint_as_float(u & 0xffff0000u); }
__device__ __forceinline__ float rbf(float v) { return __bfloat162float(__float2bfloat16_rn(v)); }
__device__ __forceinline__ uint32_t pack_bf(float lo, float hi) {
    uint32_t r;
    asm("cvt.rn.bf16x2.f32 %0, %1, %2;" : "=r"(r) : "f"(hi), "f"(lo));
    return r;
}
__device__ __forceinline__ float sel4(const float (&c)[4], int t) {
    float a = (t & 1) ? c[1] : c[0];
    float b = (t & 1) ? c[3] : c[2];
    return (t & 2) ? b : a;
}
__device__ __forceinline__ float ex2(float x) { float y; asm("ex2.approx.ftz.f32 %0, %1;" : "=f"(y) : "f"(x)); return y; }
__device__ __forceinline__ float sqrt_approx(float x) { float y; asm("sqrt.approx.f32 %0, %1;" : "=f"(y) : "f"(x)); return y; }

__device__ __forceinline__ float strip_tile(uint32_t sb, int tile, int lane) {
    float c0[4] = {0.f, 0.f, 0.f, 0.f}, c1[4] = {0.f, 0.f, 0.f, 0.f};
    uint32_t aa = sb + SM_STRIP + ((lane & 7) + (lane >> 4) * 8) * SROW + tile * 32 + ((lane >> 3) & 1) * 16;
    uint32_t ba = sb + SM_XN + (lane & 1) * XROW + (lane >> 3) * 16;
#pragma unroll 7
    for (int ks = 0; ks < 14; ks++) {
        uint32_t a0[4], a1[4], b[4];
        ldsm4(ba, b);
        ldsm4t(aa, a0);
        ldsm4t(aa + 16 * SROW, a1);
        mma16816(c0, a0, b[0], b[1]);
        mma16816(c1, a1, b[2], b[3]);
        aa += 32 * SROW; ba += 64;
    }
    return sel4(c0, lane & 3) + sel4(c1, lane & 3);
}

enum { BAR_INIT = 1, BAR_OB = 2, BAR_LATE = 3, BAR_CONS = 4, BAR_GO = 5, BAR_INIT2 = 6 };

#define WINDOW 2
#define LATE_ST 3
#define GO_LATE 1

__global__ void __launch_bounds__(NTHREADS, 1)
fused_decode_kernel(const __nv_bfloat16* __restrict__ x, const __nv_bfloat16* __restrict__ kc, const __nv_bfloat16* __restrict__ vc,
                    const __nv_bfloat16* __restrict__ wq, const __nv_bfloat16* __restrict__ wo,
                    const __nv_bfloat16* __restrict__ wg, const __nv_bfloat16* __restrict__ wu, const __nv_bfloat16* __restrict__ wd,
                    __nv_bfloat16* __restrict__ out, Scratch* __restrict__ scr) {
    extern __shared__ __align__(128) unsigned char smem[];
    const uint32_t sb = (uint32_t)__cvta_generic_to_shared(smem);
    const int tid = threadIdx.x, warp = tid >> 5, lane = tid & 31;
    const int cta = blockIdx.x;
    const int hkv = cta >> 4, j = cta & 15, bat = j >> 3, sp = j & 7;
    const uint32_t full0 = sb + SM_BAR, empty0 = full0 + NS * 8;
    const uint32_t bar_wq = empty0 + NS * 8, bar_ff = bar_wq + 8, bar_strip = bar_wq + 16;

    if (warp == 8) {
        TL(0);
        if (lane == 0) {
#pragma unroll
            for (int i = 0; i < NS; i++) { mbar_init(full0 + i * 8, 1); mbar_init(empty0 + i * 8, 8); }
            mbar_init(bar_wq, 257); mbar_init(bar_ff, 256); mbar_init(bar_strip, 3);
            asm volatile("fence.mbarrier_init.release.cluster;" ::: "memory");
        }
        __syncwarp();
        bar_arrive(BAR_INIT2, 64);
        bar_sync(BAR_INIT, 288);
        bar_sync(BAR_GO, 288);
        if (lane == 0) {
            const size_t kvoff = ((size_t)(bat * 8 + hkv) * SK + (SK - WIN) + sp * 512) * DH * 2;
            const char* src = reinterpret_cast<const char*>(kc) + kvoff;
            uint32_t bytes = 4096;
            int slot = 0, par = 1;
            const int nst = cta < NFFN ? NSTAGE : NSTAGE - 1;
#pragma unroll 1
            for (int st = 0; st < nst; st++) {
                if (st == 8)  src = reinterpret_cast<const char*>(vc) + kvoff;
                if (st == 16) { src = reinterpret_cast<const char*>(wo) + (size_t)cta * (32 * 896); bytes = 4 * 896; }
                if (st == 17) { src = reinterpret_cast<const char*>(wd) + (size_t)cta * (16 * 896); bytes = 2 * 896; }
                if (st >= NS) mbar_wait(empty0 + slot * 8, par);
                else if (st == NS - 2) { mbar_wait(bar_strip, 0); asm volatile("fence.proxy.async.shared::cta;" ::: "memory"); }
                else if (st >= WINDOW && st < NS - 2) mbar_wait(full0 + (st - WINDOW) * 8, 0);
                mbar_expect_tx(full0 + slot * 8, bytes * 8);
                uint32_t dst = sb + SM_RING + slot * SLOT;
#pragma unroll
                for (int i = 0; i < 8; i++) {
                    bulk_g2s(dst, src, bytes, full0 + slot * 8);
                    dst += bytes + 16; src += bytes;
                }
                if (++slot == NS) { slot = 0; par ^= 1; }
            }
        }
        TL(1);
    } else if (warp == 10) {
        bar_sync(BAR_LATE, 96);
        const uint32_t tag = *reinterpret_cast<volatile uint32_t*>(smem + SM_TAG);
        const int s = lane >> 2, c = lane & 3;
        const uint4* pp = scr->part + (size_t)cta * 128 + s * 8 + c;
        uint4 v[4];
#pragma unroll
        for (int i = 0; i < 4; i++) v[i] = ld_poll4(pp + (i >> 1) * 64 + (i & 1) * 4);
        float wgt[2];
        {
            const uint2* mlp = scr->ml + (hkv * 2 + (j >> 3)) * 16 + s;
            uint2 a, b;
            int it = 0;
            do {
                a = ld_poll2(mlp); b = ld_poll2(mlp + 8);
                if (++it > SPIN_LIMIT) __trap();
            } while (warp_bad(bad2(a.x, a.y, tag) | bad2(b.x, b.y, tag)));
            float m[2] = {__uint_as_float(a.x), __uint_as_float(b.x)};
            float l[2] = {__uint_as_float(a.y), __uint_as_float(b.y)};
#pragma unroll
            for (int bb = 0; bb < 2; bb++) {
                float M = m[bb];
                M = fmaxf(M, __shfl_xor_sync(0xffffffffu, M, 4));
                M = fmaxf(M, __shfl_xor_sync(0xffffffffu, M, 8));
                M = fmaxf(M, __shfl_xor_sync(0xffffffffu, M, 16));
                const float e = ex2(m[bb] - M);
                float L = e * l[bb];
                L += __shfl_xor_sync(0xffffffffu, L, 4);
                L += __shfl_xor_sync(0xffffffffu, L, 8);
                L += __shfl_xor_sync(0xffffffffu, L, 16);
                wgt[bb] = __fdividef(e, L);
            }
        }
        uint32_t* obp = reinterpret_cast<uint32_t*>(smem + SM_OB) + (lane >> 4) * 16 + (c + 4 * ((lane >> 3) & 1)) * 2 + ((lane >> 2) & 1);
        mbar_wait(full0 + (15 % NS) * 8, (15 / NS) & 1);
        TL(2);
        for (int it = 0;; it++) {
            uint32_t bad[4];
#pragma unroll
            for (int i = 0; i < 4; i++) bad[i] = bad4(v[i], tag);
            if (!warp_bad(bad[0] | bad[1] | bad[2] | bad[3])) break;
#pragma unroll
            for (int i = 0; i < 4; i++) ld_poll4_if(v[i], pp + (i >> 1) * 64 + (i & 1) * 4, bad[i]);
            if (it > SPIN_LIMIT) __trap();
        }
        TL(3);
        float r8[8], r4[4], r2[2];
        const bool h16 = lane & 16, h8 = lane & 8, h4 = lane & 4;
        {
            const float wk = h16 ? wgt[1] : wgt[0], ws = h16 ? wgt[0] : wgt[1];
            const uint32_t f0[8] = {v[0].x, v[0].y, v[0].z, v[0].w, v[1].x, v[1].y, v[1].z, v[1].w};
            const uint32_t f1[8] = {v[2].x, v[2].y, v[2].z, v[2].w, v[3].x, v[3].y, v[3].z, v[3].w};
#pragma unroll
            for (int e = 0; e < 8; e++) {
                const float keep = __uint_as_float(h16 ? f1[e] : f0[e]), send = __uint_as_float(h16 ? f0[e] : f1[e]);
                r8[e] = fmaf(keep, wk, __shfl_xor_sync(0xffffffffu, send * ws, 16));
            }
        }
#pragma unroll
        for (int e = 0; e < 4; e++) {
            const float keep = h8 ? r8[4 + e] : r8[e], send = h8 ? r8[e] : r8[4 + e];
            r4[e] = keep + __shfl_xor_sync(0xffffffffu, send, 8);
        }
#pragma unroll
        for (int e = 0; e < 2; e++) {
            const float keep = h4 ? r4[2 + e] : r4[e], send = h4 ? r4[e] : r4[2 + e];
            r2[e] = keep + __shfl_xor_sync(0xffffffffu, send, 4);
        }
        *obp = pack_bf(r2[0], r2[1]);
        bar_arrive(BAR_OB, 288);
        TL(14);
    } else if (warp == 9) {
        uint32_t tag;
        {
            uint32_t xs[2][7];
#pragma unroll
            for (int b = 0; b < 2; b++)
#pragma unroll
                for (int i = 0; i < 7; i++) xs[b][i] = __ldg(reinterpret_cast<const uint32_t*>(x) + b * (D_MODEL / 2) + i * 32 + lane);
            const uint32_t epoch = ld_poll1(&scr->epoch[cta * 8]);
#pragma unroll
            for (int b = 0; b < 2; b++) {
                float sum = 0.f;
#pragma unroll
                for (int i = 0; i < 7; i++) sum += bf_lo(xs[b][i]) + bf_hi(xs[b][i]);
#pragma unroll
                for (int o = 16; o > 0; o >>= 1) sum += __shfl_xor_sync(0xffffffffu, sum, o);
                const float mean = sum * (1.0f / D_MODEL);
                float sq = 0.f;
#pragma unroll
                for (int i = 0; i < 7; i++) {
                    const float d0 = bf_lo(xs[b][i]) - mean, d1 = bf_hi(xs[b][i]) - mean;
                    sq = fmaf(d0, d0, fmaf(d1, d1, sq));
                }
#pragma unroll
                for (int o = 16; o > 0; o >>= 1) sq += __shfl_xor_sync(0xffffffffu, sq, o);
                const float mb = rbf(mean);
                const float sd = rbf(sqrt_approx(rbf(rbf(sq * (1.0f / D_MODEL)) + 1e-5f)));
#pragma unroll
                for (int i = 0; i < 7; i++)
                    reinterpret_cast<uint32_t*>(smem + SM_XN + b * XROW)[i * 32 + lane] =
                        pack_bf(__fdividef(rbf(bf_lo(xs[b][i]) - mb), sd), __fdividef(rbf(bf_hi(xs[b][i]) - mb), sd));
            }
            tag = (epoch + 1) & 1;
            if (lane == 0) *reinterpret_cast<volatile uint32_t*>(smem + SM_TAG) = tag;
            bar_sync(BAR_INIT2, 64);
            if (lane == 0) { mbar_arrive(bar_wq, 1); scr->epoch[cta * 8] = epoch + 1; }
        }
        if (cta < NFFN) {
            mbar_wait(bar_ff, 0);
            float ga = rbf(strip_tile(sb, 2, lane));
            const float up = rbf(strip_tile(sb, 3, lane));
            ga *= (ga > 0.f ? 1.f : 0.f);
            const int cc = (lane >> 2) + 8 * ((lane >> 1) & 1);
            reinterpret_cast<__nv_bfloat16*>(smem + SM_H)[(lane & 1) * 16 + (cc >> 1) + 8 * (cc & 1)] = __float2bfloat16_rn(ga * up);
        }
        __syncwarp();
        if (lane == 0) mbar_arrive(bar_strip, 1);
        TL(13);
        if (cta < NFFN) {
            const int i16 = cta & 15;
            const int mt = ((lane >> 1) & 1) * 2 + ((lane >> 2) & 1);
            const int oidx = (lane & 1) * D_MODEL + (cta >> 4) * 64 + mt * 16 + (i16 >> 1) + (i16 & 1) * 8;
            const float xv = __bfloat162float(x[oidx]);
            __nv_bfloat16* optr = out + oidx;
            const uint4* op = scr->outp + (size_t)cta * 256 + lane;
            bar_sync(BAR_LATE, 96);
            uint4 v[8];
#pragma unroll
            for (int i = 0; i < 8; i++) v[i] = ld_poll4(op + i * 32);
            bar_sync(BAR_OB, 288);
            for (int it = 0;; it++) {
                uint32_t bad[8];
#pragma unroll
                for (int i = 0; i < 8; i++) bad[i] = bad4(v[i], tag);
                if (!warp_bad(bad[0] | bad[1] | bad[2] | bad[3] | bad[4] | bad[5] | bad[6] | bad[7])) break;
#pragma unroll
                for (int i = 0; i < 8; i++) ld_poll4_if(v[i], op + i * 32, bad[i]);
                if (it > SPIN_LIMIT) __trap();
            }
            TL(4);
            float a[4];
            a[0] = ((__uint_as_float(v[0].x) + __uint_as_float(v[1].x)) + (__uint_as_float(v[2].x) + __uint_as_float(v[3].x))) +
                   ((__uint_as_float(v[4].x) + __uint_as_float(v[5].x)) + (__uint_as_float(v[6].x) + __uint_as_float(v[7].x)));
            a[1] = ((__uint_as_float(v[0].y) + __uint_as_float(v[1].y)) + (__uint_as_float(v[2].y) + __uint_as_float(v[3].y))) +
                   ((__uint_as_float(v[4].y) + __uint_as_float(v[5].y)) + (__uint_as_float(v[6].y) + __uint_as_float(v[7].y)));
            a[2] = ((__uint_as_float(v[0].z) + __uint_as_float(v[1].z)) + (__uint_as_float(v[2].z) + __uint_as_float(v[3].z))) +
                   ((__uint_as_float(v[4].z) + __uint_as_float(v[5].z)) + (__uint_as_float(v[6].z) + __uint_as_float(v[7].z)));
            a[3] = ((__uint_as_float(v[0].w) + __uint_as_float(v[1].w)) + (__uint_as_float(v[2].w) + __uint_as_float(v[3].w))) +
                   ((__uint_as_float(v[4].w) + __uint_as_float(v[5].w)) + (__uint_as_float(v[6].w) + __uint_as_float(v[7].w)));
            const bool h2 = lane & 2, h4 = lane & 4;
            float r2[2];
#pragma unroll
            for (int e = 0; e < 2; e++) {
                const float keep = h2 ? a[2 + e] : a[e], send = h2 ? a[e] : a[2 + e];
                r2[e] = keep + __shfl_xor_sync(0xffffffffu, send, 2);
            }
            float r = (h4 ? r2[1] : r2[0]) + __shfl_xor_sync(0xffffffffu, h4 ? r2[0] : r2[1], 4);
            r += __shfl_xor_sync(0xffffffffu, r, 8);
            r += __shfl_xor_sync(0xffffffffu, r, 16);
            if (lane < 8) *optr = __float2bfloat16_rn(xv + r);
            TL(5);
        } else {
            bar_sync(BAR_LATE, 96);
            bar_sync(BAR_OB, 288);
        }
    } else {
        const int g = lane >> 2, t = lane & 3;
        {
            const int row0 = tid >> 2;
            const uint32_t dst = sb + SM_STRIP + row0 * SROW + t * 16;
            const __nv_bfloat16* p = wq + (size_t)row0 * QCOLS + cta * 32 + t * 8;
#pragma unroll
            for (int i = 0; i < 7; i++) {
                cp_async16(dst + i * 64 * SROW, p + (size_t)i * 64 * QCOLS);
            }
            bar_sync(BAR_INIT, 288);
            cp_async_arrive(bar_wq);
            if (cta < NFFN) {
                p = ((t & 2) ? wu : wg) + (size_t)row0 * FF + cta * 16 + (t & 1) * 8;
#pragma unroll
                for (int i = 0; i < 7; i++) {
                    cp_async16(dst + 64 + i * 64 * SROW, p + (size_t)i * 64 * FF);
                }
                cp_async_arrive(bar_ff);
            }
            bar_arrive(BAR_GO, 288);
        }
        mbar_wait(bar_wq, 0);
        const uint32_t tag = *reinterpret_cast<volatile uint32_t*>(smem + SM_TAG);
        if (warp < 2) {
            if (warp == 0) TL(15);
            const float qv = strip_tile(sb, warp, lane);
            st_pub1(reinterpret_cast<uint32_t*>(scr->q) + (hkv * 2 + (t & 1)) * 512 + j * 32 + warp * 16 + g + 8 * (t >> 1),
                    (pack_bf(0.f, qv) & 0xffff0000u) | tag);
            __syncwarp();
            if (lane == 0) mbar_arrive(bar_strip, 1);
            if (warp == 0) TL(6);
        } else if (warp >= 4) {
            const int i = tid - 128;
            const uint4* qp = scr->q + (hkv * 2 + bat) * 128 + i;
            uint4 v;
            int it = 0;
            do {
                v = ld_poll4(qp);
                if (++it > SPIN_LIMIT) __trap();
            } while (warp_bad(bad4(v, tag)));
            *reinterpret_cast<uint2*>(smem + SM_Q + (i >> 6) * 528 + (i & 63) * 8) =
                make_uint2(__byte_perm(v.x, v.y, 0x7632), __byte_perm(v.z, v.w, 0x7632));
        }
        bar_sync(BAR_CONS, 256);
        if (warp == 0) TL(7);
        {
            uint32_t qf[8][4];
#pragma unroll
            for (int k2 = 0; k2 < 8; k2++) ldsm4(sb + SM_Q + (lane & 1) * 528 + k2 * 64 + (lane >> 3) * 16, qf[k2]);
            const int mt = warp & 3;
            const uint32_t aoff = (lane & 7) * GRP + (2 * mt + ((lane >> 3) & 1)) * 512 + (lane >> 4) * 16;
            float* sc = reinterpret_cast<float*>(smem + SM_S) + (t & 1) * 520 + (g >> 1) * 16 + (2 * mt + (t >> 1)) * 2 + (g & 1);
#pragma unroll 1
            for (int st = warp >> 2; st < 8; st += 2) {
                const int slot = st >= NS ? st - NS : st;
                mbar_wait(full0 + slot * 8, st >= NS);
                const uint32_t base = sb + SM_RING + slot * SLOT + aoff;
                float c0[4] = {0.f, 0.f, 0.f, 0.f}, c1[4] = {0.f, 0.f, 0.f, 0.f};
#pragma unroll
                for (int k2 = 0; k2 < 8; k2++) {
                    uint32_t a0[4], a1[4];
                    ldsm4(base + k2 * 64, a0);
                    ldsm4(base + k2 * 64 + 32, a1);
                    mma16816(c0, a0, qf[k2][0], qf[k2][1]);
                    mma16816(c1, a1, qf[k2][2], qf[k2][3]);
                }
                __syncwarp();
                if (lane == 0) mbar_arrive(empty0 + slot * 8, 2);
                sc[st * 64] = rbf(sel4(c0, t) + sel4(c1, t));
            }
        }
        bar_sync(BAR_CONS, 256);
        if (warp == 0) TL(8);
        {
            constexpr float C = 0.0625f * 1.4426950408889634f;
            const float* sc = reinterpret_cast<const float*>(smem + SM_S);
            float* stat = reinterpret_cast<float*>(smem + SM_STAT);
            const float2 s0 = *reinterpret_cast<const float2*>(sc + 2 * tid);
            const float2 s1 = *reinterpret_cast<const float2*>(sc + 520 + 2 * tid);
            float m0 = fmaxf(s0.x, s0.y), m1 = fmaxf(s1.x, s1.y);
#pragma unroll
            for (int o = 16; o > 0; o >>= 1) {
                m0 = fmaxf(m0, __shfl_xor_sync(0xffffffffu, m0, o));
                m1 = fmaxf(m1, __shfl_xor_sync(0xffffffffu, m1, o));
            }
            if (lane == 0) *reinterpret_cast<float2*>(stat + warp * 2) = make_float2(m0, m1);
            bar_sync(BAR_CONS, 256);
#pragma unroll
            for (int w = 0; w < 8; w++) {
                const float2 mm = *reinterpret_cast<const float2*>(stat + w * 2);
                m0 = fmaxf(m0, mm.x); m1 = fmaxf(m1, mm.y);
            }
            const float p00 = ex2((s0.x - m0) * C), p01 = ex2((s0.y - m0) * C);
            const float p10 = ex2((s1.x - m1) * C), p11 = ex2((s1.y - m1) * C);
            uint32_t* ps = reinterpret_cast<uint32_t*>(smem + SM_P);
            ps[tid] = pack_bf(p00, p01);
            ps[260 + tid] = pack_bf(p10, p11);
            float l0 = p00 + p01, l1 = p10 + p11;
#pragma unroll
            for (int o = 16; o > 0; o >>= 1) {
                l0 += __shfl_xor_sync(0xffffffffu, l0, o);
                l1 += __shfl_xor_sync(0xffffffffu, l1, o);
            }
            if (lane == 0) *reinterpret_cast<float2*>(stat + 16 + warp * 2) = make_float2(l0, l1);
            bar_sync(BAR_CONS, 256);
            if (tid < 2) {
                float l = 0.f;
#pragma unroll
                for (int w = 0; w < 8; w++) l += stat[16 + w * 2 + tid];
                st_pub2(scr->ml + ((hkv * 2 + tid) * 2 + bat) * 8 + sp, tagf((tid ? m1 : m0) * C, tag), tagf(l, tag));
            }
        }
        if (warp == 0) TL(9);
        {
            float o0[4] = {0.f, 0.f, 0.f, 0.f}, o1[4] = {0.f, 0.f, 0.f, 0.f};
            float o2[4] = {0.f, 0.f, 0.f, 0.f}, o3[4] = {0.f, 0.f, 0.f, 0.f};
            const uint32_t aoff = (lane & 7) * GRP + (lane >> 4) * 512 + (warp * 32 + ((lane >> 3) & 1) * 8) * 2;
            const uint4* ps = reinterpret_cast<const uint4*>(smem + SM_P + (g & 1) * 260 * 4) + t * 2;
            uint32_t* dst = reinterpret_cast<uint32_t*>(scr->part) + ((size_t)(hkv * 16 + (t & 1) * 8 + warp) * 16 + j) * 32 + (g + 8 * (t >> 1)) * 2;
            int slot = 8 % NS, par = (8 / NS) & 1;
#pragma unroll 1
            for (int st = 0; st < 8; st++) {
                const uint4 pa = ps[st * 8], pb = ps[st * 8 + 1];
                mbar_wait(full0 + slot * 8, par);
                const uint32_t base = sb + SM_RING + slot * SLOT + aoff;
                uint32_t a[8][4];
#pragma unroll
                for (int i = 0; i < 8; i++) ldsm4t(base + (i >> 1) * 1024 + (i & 1) * 32, a[i]);
                mma16816(o0, a[0], pa.x, pa.y);
                mma16816(o1, a[1], pa.x, pa.y);
                mma16816(o2, a[2], pa.z, pa.w);
                mma16816(o3, a[3], pa.z, pa.w);
                mma16816(o0, a[4], pb.x, pb.y);
                mma16816(o1, a[5], pb.x, pb.y);
                mma16816(o2, a[6], pb.z, pb.w);
                mma16816(o3, a[7], pb.z, pb.w);
                __syncwarp();
                if (lane == 0) mbar_arrive(empty0 + slot * 8, 1);
                if (++slot == NS) { slot = 0; par ^= 1; }
                if (st == LATE_ST && warp == 7) bar_arrive(BAR_LATE, 96);
            }
            const float v0 = sel4(o0, t) + sel4(o2, t), v1 = sel4(o1, t) + sel4(o3, t);
            st_pub2(dst, tagf(v0, tag), tagf(v1, tag));
        }
        if (warp == 0) TL(10);
        if (warp < 7) {
            float c[4][4];
#pragma unroll
            for (int m = 0; m < 4; m++)
#pragma unroll
                for (int e = 0; e < 4; e++) c[m][e] = 0.f;
            const uint32_t coff = (warp * 64 + ((lane >> 3) & 1) * 8) * 2;
            uint4* dst = scr->outp + ((size_t)(warp * 16 + (lane >> 1)) * NCTA + cta) * 2 + (lane & 1);
            uint32_t a[8][4];
            {
                mbar_wait(full0 + (16 % NS) * 8, (16 / NS) & 1);
                const int grp = ((lane & 1) << 2) | ((lane & 7) >> 1);
                const uint32_t base = sb + SM_RING + (16 % NS) * SLOT + grp * GRP_WO + (lane >> 4) * 896 + coff;
#pragma unroll
                for (int i = 0; i < 8; i++) ldsm4t(base + (i >> 2) * 1792 + (i & 3) * 32, a[i]);
            }
            if (cta < NFFN) {
                const uint32_t* hs = reinterpret_cast<const uint32_t*>(smem + SM_H) + (g & 1) * 8;
                const uint32_t h0 = hs[t], h1 = hs[4 + t];
                mbar_wait(full0 + (17 % NS) * 8, (17 / NS) & 1);
                const uint32_t base = sb + SM_RING + (17 % NS) * SLOT + (lane & 7) * GRP_DN + (lane >> 4) * 896 + coff;
#pragma unroll
                for (int m = 0; m < 4; m++) {
                    uint32_t d[4];
                    ldsm4t(base + m * 32, d);
                    mma16816(c[m], d, h0, h1);
                }
            }
            if (warp == 0) TL(11);
            bar_sync(BAR_OB, 288);
            const uint4 ob = *reinterpret_cast<const uint4*>(smem + SM_OB + (g & 1) * 64 + t * 16);
#pragma unroll
            for (int m = 0; m < 4; m++) mma16816(c[m], a[m], ob.x, ob.y);
#pragma unroll
            for (int m = 0; m < 4; m++) mma16816(c[m], a[4 + m], ob.z, ob.w);
            uint4 r;
            r.x = tagf(sel4(c[0], t), tag); r.y = tagf(sel4(c[1], t), tag);
            r.z = tagf(sel4(c[2], t), tag); r.w = tagf(sel4(c[3], t), tag);
            st_pub4(dst, r);
            if (warp == 0) TL(12);
        }
    }
}

}

extern "C" void kernel_launch(void* const* d_in, const int* in_sizes, int n_in, void* d_out, int out_size) {
    (void)in_sizes; (void)n_in; (void)out_size;
    static Scratch* scr = nullptr;
    if (!scr) {
        cudaFuncSetAttribute(fused_decode_kernel, cudaFuncAttributeMaxDynamicSharedMemorySize, SM_TOTAL);
        cudaGetSymbolAddress(reinterpret_cast<void**>(&scr), g_scratch);
    }
    fused_decode_kernel<<<NCTA, NTHREADS, SM_TOTAL>>>(
        (const __nv_bfloat16*)d_in[0], (const __nv_bfloat16*)d_in[1], (const __nv_bfloat16*)d_in[2],
        (const __nv_bfloat16*)d_in[3], (const __nv_bfloat16*)d_in[4],
        (const __nv_bfloat16*)d_in[6], (const __nv_bfloat16*)d_in[7], (const __nv_bfloat16*)d_in[8],
        (__nv_bfloat16*)d_out, scr);
}
```

```cpp
#include <cuda_runtime.h>
#include <cuda_bf16.h>
#include <stdint.h>

namespace {

#define PACE_DT 640
#define PACE_LEAD 300
#define FFN_ST 8
#define E2_T 24400
#define E3_T 25350
#define LPM 4
#define PRE_ST 12

#define TN_PARAM
#define TN_ARG
#define TN_E2 E2_T
#define TN_E3 E3_T

constexpr int D_MODEL = 448;
constexpr int SK      = 32768;
constexpr int WIN     = 4096;
constexpr int DH      = 256;
constexpr int QCOLS   = 4096;
constexpr int FF      = 1792;
constexpr int NCTA    = 128;
constexpr int NFFN    = 112;
constexpr int NPW     = 4;
constexpr int NPT     = NPW * 32;
constexpr int NTHREADS = 256 + NPT;
constexpr int NRED    = 224 / LPM;
constexpr int RSTEP   = LPM / 2;

constexpr int NS     = 11;
constexpr int SLOT   = 16384;
constexpr int XROW   = 912;
constexpr int S_K  = 0;
constexpr int S_V  = 16;
constexpr int S_DN = 32;
constexpr int S_WO = 33;
constexpr int NSTAGE = 35;
#define GU_FIRST 8
constexpr int S_GU = GU_FIRST;
constexpr int NBAR   = 40;
constexpr int B_X = NSTAGE, B_Q = NBAR + NSTAGE;

constexpr int SM_RING = 0;
constexpr int SM_STRIP = SM_RING + NS * SLOT;
constexpr int SM_S    = SM_STRIP + 448 * 64;
constexpr int SM_P    = SM_S + 2 * 520 * 4;
constexpr int SM_Q    = SM_P + 2 * 272 * 4;
constexpr int SM_XN   = SM_Q + 2 * 264 * 2;
constexpr int SM_X    = SM_XN + 2 * XROW;
constexpr int SM_RED  = SM_X + 1792 + 16;
constexpr int SM_STAT = SM_RED + 7 * 64 * 4;
constexpr int SM_OB   = SM_STAT + 2 * 8 * 2 * 4;
constexpr int SM_BAR  = SM_OB + 2 * 16 * 4;
constexpr int SM_TOTAL = SM_BAR + 2 * NBAR * 8;
static_assert(SM_Q % 16 == 0 && SM_XN % 16 == 0 && SM_X % 16 == 0 && SM_OB % 16 == 0 && SM_P % 16 == 0 && SM_BAR % 8 == 0, "align");
static_assert(S_GU + 13 <= S_V + FFN_ST, "the gate/up strip lands with stage S_GU + 13");

constexpr int SPIN_LIMIT = 1 << 22;

struct Scratch {
    uint4    part[NCTA * 2 * 8 * 8];
    uint4    outp[NRED * NCTA * LPM];
    uint4    q[8 * 2 * 128];
    uint2    ml[8 * 2 * 2 * 8];
    unsigned epoch[NCTA * 8];
};
__device__ Scratch g_scratch;

#define TL(i)

__device__ __forceinline__ void mbar_init(uint32_t bar, uint32_t cnt) {
    asm volatile("mbarrier.init.shared::cta.b64 [%0], %1;" :: "r"(bar), "r"(cnt) : "memory");
}
__device__ __forceinline__ void mbar_arrive(uint32_t bar, uint32_t cnt) {
    asm volatile("mbarrier.arrive.shared::cta.b64 _, [%0], %1;" :: "r"(bar), "r"(cnt) : "memory");
}
__device__ __forceinline__ bool mbar_try(uint32_t bar) {
    uint32_t ok;
    asm volatile("{\n.reg .pred p;\nmbarrier.try_wait.parity.shared::cta.b64 p, [%1], 0;\nselp.u32 %0, 1, 0, p;\n}"
                 : "=r"(ok) : "r"(bar) : "memory");
    return ok;
}
__device__ __forceinline__ bool mbar_test(uint32_t bar) {
    uint32_t ok;
    asm volatile("{\n.reg .pred p;\nmbarrier.test_wait.parity.shared::cta.b64 p, [%1], 0;\nselp.u32 %0, 1, 0, p;\n}"
                 : "=r"(ok) : "r"(bar) : "memory");
    return ok;
}
__device__ __forceinline__ uint32_t time_ns() { uint32_t t; asm volatile("mov.u32 %0, %globaltimer_lo;" : "=r"(t)); return t; }
__device__ __forceinline__ void mbar_wait(uint32_t bar) {
    asm volatile("{\n.reg .pred p;\nWAIT_LOOP:\nmbarrier.try_wait.parity.shared::cta.b64 p, [%0], 0;\n@!p bra WAIT_LOOP;\n}" :: "r"(bar) : "memory");
}
__device__ __forceinline__ void cp_async16(uint32_t dst, const void* src) {
    asm volatile("cp.async.cg.shared.global [%0], [%1], 16;" :: "r"(dst), "l"(src) : "memory");
}
__device__ __forceinline__ void cp_async_arrive(uint32_t bar) {
    asm volatile("cp.async.mbarrier.arrive.noinc.shared::cta.b64 [%0];" :: "r"(bar) : "memory");
}
__device__ __forceinline__ void bar_sync(int id, int n)   { asm volatile("bar.sync %0, %1;" :: "r"(id), "r"(n) : "memory"); }
__device__ __forceinline__ void bar_arrive(int id, int n) { asm volatile("bar.arrive %0, %1;" :: "r"(id), "r"(n) : "memory"); }

__device__ __forceinline__ uint2 ld_poll2(const void* p) {
    uint2 v;
    asm volatile("ld.relaxed.gpu.global.v2.u32 {%0,%1}, [%2];" : "=r"(v.x), "=r"(v.y) : "l"(p) : "memory");
    return v;
}
__device__ __forceinline__ uint4 ld_poll4(const void* p) {
    uint4 v;
    asm volatile("ld.relaxed.gpu.global.v4.u32 {%0,%1,%2,%3}, [%4];" : "=r"(v.x), "=r"(v.y), "=r"(v.z), "=r"(v.w) : "l"(p) : "memory");
    return v;
}
__device__ __forceinline__ void ld_poll4_if(uint4& v, const void* p, uint32_t bad) {
    asm volatile("{\n.reg .pred p;\n.reg .b32 t;\nand.b32 t, %5, 1;\nsetp.ne.u32 p, t, 0;\n"
                 "@p ld.relaxed.gpu.global.v4.u32 {%0,%1,%2,%3}, [%4];\n}"
                 : "+r"(v.x), "+r"(v.y), "+r"(v.z), "+r"(v.w) : "l"(p), "r"(bad) : "memory");
}
__device__ __forceinline__ void st_pub4(void* p, uint4 v) {
    asm volatile("st.relaxed.gpu.global.v4.u32 [%0], {%1,%2,%3,%4};" :: "l"(p), "r"(v.x), "r"(v.y), "r"(v.z), "r"(v.w) : "memory");
}
__device__ __forceinline__ void st_pub2(void* p, uint32_t a, uint32_t b) {
    asm volatile("st.relaxed.gpu.global.v2.u32 [%0], {%1,%2};" :: "l"(p), "r"(a), "r"(b) : "memory");
}
__device__ __forceinline__ void st_pub1(void* p, uint32_t a) {
    asm volatile("st.relaxed.gpu.global.u32 [%0], %1;" :: "l"(p), "r"(a) : "memory");
}
__device__ __forceinline__ uint32_t tagf(float v, uint32_t tag) { return (__float_as_uint(v) & ~1u) | tag; }
__device__ __forceinline__ uint32_t bad2(uint32_t a, uint32_t b, uint32_t tag) {
    uint32_t r;
    asm("lop3.b32 %0, %1, %2, %3, 0x7E;" : "=r"(r) : "r"(a), "r"(b), "r"(tag));
    return r;
}
__device__ __forceinline__ uint32_t bad4(const uint4& v, uint32_t tag) { return bad2(v.x, v.y, tag) | bad2(v.z, v.w, tag); }
__device__ __forceinline__ bool warp_bad(uint32_t bad) { return __any_sync(0xffffffffu, bad & 1u); }

__device__ __forceinline__ void ldsm4(uint32_t addr, uint32_t (&a)[4]) {
    asm volatile("ldmatrix.sync.aligned.m8n8.x4.shared.b16 {%0,%1,%2,%3}, [%4];" : "=r"(a[0]), "=r"(a[1]), "=r"(a[2]), "=r"(a[3]) : "r"(addr) : "memory");
}
__device__ __forceinline__ void ldsm4t(uint32_t addr, uint32_t (&a)[4]) {
    asm volatile("ldmatrix.sync.aligned.m8n8.x4.trans.shared.b16 {%0,%1,%2,%3}, [%4];" : "=r"(a[0]), "=r"(a[1]), "=r"(a[2]), "=r"(a[3]) : "r"(addr) : "memory");
}
__device__ __forceinline__ void mma16816(float (&c)[4], const uint32_t (&a)[4], uint32_t b0, uint32_t b1) {
    asm volatile("mma.sync.aligned.m16n8k16.row.col.f32.bf16.bf16.f32 {%0,%1,%2,%3}, {%4,%5,%6,%7}, {%8,%9}, {%0,%1,%2,%3};"
                 : "+f"(c[0]), "+f"(c[1]), "+f"(c[2]), "+f"(c[3]) : "r"(a[0]), "r"(a[1]), "r"(a[2]), "r"(a[3]), "r"(b0), "r"(b1));
}
__device__ __forceinline__ float bf_lo(uint32_t u) { return __uint_as_float(u << 16); }
__device__ __forceinline__ float bf_hi(uint32_t u) { return __uint_as_float(u & 0xffff0000u); }
__device__ __forceinline__ float rbf(float v) { return __bfloat162float(__float2bfloat16_rn(v)); }
__device__ __forceinline__ uint32_t pack_bf(float lo, float hi) {
    uint32_t r;
    asm("cvt.rn.bf16x2.f32 %0, %1, %2;" : "=r"(r) : "f"(hi), "f"(lo));
    return r;
}
__device__ __forceinline__ float sel4(const float (&c)[4], int t) {
    float a = (t & 1) ? c[1] : c[0];
    float b = (t & 1) ? c[3] : c[2];
    return (t & 2) ? b : a;
}
__device__ __forceinline__ float ex2(float x) { float y; asm("ex2.approx.ftz.f32 %0, %1;" : "=f"(y) : "f"(x)); return y; }
__device__ __forceinline__ float sqrt_approx(float x) { float y; asm("sqrt.approx.f32 %0, %1;" : "=f"(y) : "f"(x)); return y; }

__device__ __forceinline__ constexpr uint32_t slot_of(int s) { return SM_RING + (s % NS) * SLOT; }

__device__ __forceinline__ void layernorm(unsigned char* smem, int lane) {
    uint32_t xs[2][7];
#pragma unroll
    for (int b = 0; b < 2; b++)
#pragma unroll
        for (int i = 0; i < 7; i++) xs[b][i] = reinterpret_cast<const uint32_t*>(smem + SM_X)[b * (D_MODEL / 2) + i * 32 + lane];
#pragma unroll
    for (int b = 0; b < 2; b++) {
        float sum = 0.f;
#pragma unroll
        for (int i = 0; i < 7; i++) sum += bf_lo(xs[b][i]) + bf_hi(xs[b][i]);
#pragma unroll
        for (int o = 16; o > 0; o >>= 1) sum += __shfl_xor_sync(0xffffffffu, sum, o);
        const float mean = sum * (1.0f / D_MODEL);
        float sq = 0.f;
#pragma unroll
        for (int i = 0; i < 7; i++) {
            const float d0 = bf_lo(xs[b][i]) - mean, d1 = bf_hi(xs[b][i]) - mean;
            sq = fmaf(d0, d0, fmaf(d1, d1, sq));
        }
#pragma unroll
        for (int o = 16; o > 0; o >>= 1) sq += __shfl_xor_sync(0xffffffffu, sq, o);
        const float mb = rbf(mean);
        const float sd = rbf(sqrt_approx(rbf(rbf(sq * (1.0f / D_MODEL)) + 1e-5f)));
#pragma unroll
        for (int i = 0; i < 7; i++)
            reinterpret_cast<uint32_t*>(smem + SM_XN + b * XROW)[i * 32 + lane] =
                pack_bf(__fdividef(rbf(bf_lo(xs[b][i]) - mb), sd), __fdividef(rbf(bf_hi(xs[b][i]) - mb), sd));
    }
}

__device__ __forceinline__ void strip_partial(uint32_t sb, uint32_t strip, unsigned char* smem, int warp, int lane) {
    float c[2][2][4];
#pragma unroll
    for (int n = 0; n < 2; n++)
#pragma unroll
        for (int e = 0; e < 4; e++) c[n][0][e] = c[n][1][e] = 0.f;
    const uint32_t ba = sb + SM_XN + (lane & 1) * XROW + (lane >> 3) * 16 + warp * 128;
    const uint32_t aa = sb + strip + (warp * 64 + (lane & 7) + (lane >> 4) * 8) * 64 + (((lane >> 3) & 1) ^ ((lane & 7) >> 1)) * 16;
#pragma unroll
    for (int k2 = 0; k2 < 2; k2++) {
        uint32_t b[4];
        ldsm4(ba + k2 * 64, b);
#pragma unroll
        for (int n = 0; n < 2; n++) {
            uint32_t a0[4], a1[4];
            ldsm4t((aa ^ (n * 32)) + k2 * 2048, a0);
            ldsm4t((aa ^ (n * 32)) + k2 * 2048 + 1024, a1);
            mma16816(c[n][0], a0, b[0], b[1]);
            mma16816(c[n][1], a1, b[2], b[3]);
        }
    }
    float* red = reinterpret_cast<float*>(smem + SM_RED) + warp * 64 + lane;
#pragma unroll
    for (int n = 0; n < 2; n++) red[n * 32] = sel4(c[n][0], lane & 3) + sel4(c[n][1], lane & 3);
}
__device__ __forceinline__ float strip_sum(const unsigned char* smem, int idx) {
    const float* red = reinterpret_cast<const float*>(smem + SM_RED) + idx;
    return ((red[0] + red[64]) + (red[128] + red[192])) + ((red[256] + red[320]) + red[384]);
}

struct Prod {
    uint32_t sb, kvdst, sdst, rdst[7], t0;
    const char *k, *v, *wo, *wd;
    const __nv_bfloat16* gu;
    bool ffn;
};
__host__ __device__ constexpr int bytes_before(int s) {
    return 28672 + (s <= S_DN ? s * 16384 : S_DN * 16384 + 12544 + (s - S_WO) * 14336) + (s <= S_GU ? 0 : s < S_GU + 14 ? s - S_GU : 14) * 1792;
}
__host__ __device__ constexpr int issue_time(int s) { return (int)((long long)bytes_before(s) * PACE_DT / 16384) - PACE_LEAD; }

template <int S>
__device__ __forceinline__ void issue_stage(const Prod& p) {
    const uint32_t dst = p.sb + slot_of(S);
    if constexpr (S < S_DN) {
        const char* src = S < S_V ? p.k + (S - S_K) * 16384 : p.v + (S - S_V) * 16384;
#pragma unroll
        for (int i = 0; i < 8; i++) cp_async16(dst + (p.kvdst ^ ((i & 1) * 64)) + i * 2048, src + i * 2048);
        if constexpr (S >= S_GU && S < S_GU + 14) {
            if (p.ffn) cp_async16(p.sdst + (S - S_GU) * 2048, p.gu + (size_t)(S - S_GU) * 32 * FF);
        }
    } else {
        if (S != S_DN || p.ffn) {
            const char* src = S != S_DN ? p.wo + (S - S_WO) * 14336 : p.wd;
#pragma unroll
            for (int i = 0; i < 7; i++) cp_async16(dst + p.rdst[i], src + i * 2048);
        }
    }
    cp_async_arrive(p.sb + SM_BAR + S * 8);
}
template <int S>
__device__ __forceinline__ void produce(const Prod& p) {
    if constexpr (S < NSTAGE) {
        if constexpr (S == S_GU) mbar_wait(p.sb + SM_BAR + B_Q * 8);
        if constexpr (S >= NS) mbar_wait(p.sb + SM_BAR + (NBAR + S - NS) * 8);
        while (time_ns() - p.t0 < (uint32_t)issue_time(S)) {}
        issue_stage<S>(p);
        produce<S + 1>(p);
    }
}

enum { BAR_OB = 1, BAR_CONS = 2, BAR_LN = 3, BAR_FF = 4, BAR_FIN = 5 };

__global__ void __launch_bounds__(NTHREADS, 1)
fused_decode_kernel(const __nv_bfloat16* __restrict__ wq, const __nv_bfloat16* __restrict__ kc, const __nv_bfloat16* __restrict__ x,
                    Scratch* __restrict__ scr, const __nv_bfloat16* __restrict__ vc, const __nv_bfloat16* __restrict__ wo,
                    const __nv_bfloat16* __restrict__ wg, const __nv_bfloat16* __restrict__ wu, const __nv_bfloat16* __restrict__ wd,
                    __nv_bfloat16* __restrict__ out TN_PARAM) {
    extern __shared__ __align__(128) unsigned char smem[];
    const uint32_t sb = (uint32_t)__cvta_generic_to_shared(smem);
    const int tid = threadIdx.x, warp = tid >> 5, lane = tid & 31;
    const int cta = blockIdx.x;
    const int hkv = cta >> 4, j = cta & 15, bat = j >> 3, sp = j & 7;
    const uint32_t full0 = sb + SM_BAR, done0 = full0 + NBAR * 8;

    if (warp < 8) {
        const int g = lane >> 2, t = lane & 3;
        const uint32_t t0 = time_ns();
        if (warp < 7) {
            const __nv_bfloat16* src = wq + (size_t)(warp * 64 + g) * QCOLS + cta * 32 + t * 8;
            const uint32_t dst = sb + SM_STRIP + (warp * 64 + g) * 64 + (t ^ (g >> 1)) * 16;
#pragma unroll
            for (int i = 0; i < 8; i++) cp_async16(dst + i * 512, src + (size_t)i * 8 * QCOLS);
            if (warp == 0) TL(0);
        } else if (lane == 0) {
            mbar_init(full0 + B_X * 8, 1);
            asm volatile("fence.mbarrier_init.release.cluster;" ::: "memory");
            asm volatile("mbarrier.arrive.expect_tx.shared::cta.b64 _, [%0], %1;" :: "r"(full0 + B_X * 8), "r"(1792 + 16) : "memory");
            asm volatile("cp.async.bulk.shared::cluster.global.mbarrier::complete_tx::bytes [%0], [%1], %2, [%3];"
                         :: "r"(sb + SM_X), "l"(x), "r"(1792), "r"(full0 + B_X * 8) : "memory");
            asm volatile("cp.async.bulk.shared::cluster.global.mbarrier::complete_tx::bytes [%0], [%1], %2, [%3];"
                         :: "r"(sb + SM_X + 1792), "l"(&scr->epoch[cta * 8]), "r"(16), "r"(full0 + B_X * 8) : "memory");
        }
        __syncthreads();
        mbar_wait(full0 + B_X * 8);
        const uint32_t epoch = *reinterpret_cast<const uint32_t*>(smem + SM_X + 1792);
        const uint32_t tag = (epoch + 1) & 1;
        uint32_t* qdst = reinterpret_cast<uint32_t*>(scr->q) + (hkv * 2 + (t & 1)) * 512 + j * 32 + warp * 16 + g + 8 * (t >> 1);
        if (warp < 2) st_pub1(qdst, tag ^ 1);
        if (warp == 7) {
            layernorm(smem, lane);
            bar_arrive(BAR_LN, 256);
            TL(13);
        } else {
            asm volatile("cp.async.wait_all;" ::: "memory");
            bar_sync(BAR_LN, 256);
            strip_partial(sb, SM_STRIP, smem, warp, lane);
        }
        bar_sync(BAR_CONS, 256);
        if (warp < 2) {
            st_pub1(qdst, (pack_bf(0.f, strip_sum(smem, tid)) & 0xffff0000u) | tag);
            if (warp == 0) TL(6);
        } else if (warp >= 4) {
            const int i = tid - 128;
            const uint4* qp = scr->q + (hkv * 2 + bat) * 128 + i;
            uint4 v;
            int it = 0;
            do {
                v = ld_poll4(qp);
                if (++it > SPIN_LIMIT) __trap();
            } while (warp_bad(bad4(v, tag)));
            *reinterpret_cast<uint2*>(smem + SM_Q + (i >> 6) * 528 + (i & 63) * 8) =
                make_uint2(__byte_perm(v.x, v.y, 0x7632), __byte_perm(v.z, v.w, 0x7632));
        }
        bar_sync(BAR_CONS, 256);
        if (tid == 96) { mbar_arrive(full0 + B_Q * 8, 8); scr->epoch[cta * 8] = epoch + 1; }
        if (warp == 0) TL(7);
        {
            uint32_t qf[8][4];
#pragma unroll
            for (int k2 = 0; k2 < 8; k2++) ldsm4(sb + SM_Q + (lane & 1) * 528 + k2 * 64 + (lane >> 3) * 16, qf[k2]);
            const int mt = warp & 1;
            const uint32_t aoff = (16 * mt + (lane & 15)) * 512 + ((lane >> 4) ^ (lane & 7)) * 16;
            float* sc = reinterpret_cast<float*>(smem + SM_S) + (t & 1) * 520 + (g >> 1) * 8 + (2 * mt + (t >> 1)) * 2 + (g & 1);
#pragma unroll 1
            for (int k = warp >> 1; k < 16; k += 4) {
                const int s = S_K + k;
                mbar_wait(full0 + s * 8);
                const uint32_t base = sb + SM_RING + (s >= NS ? s - NS : s) * SLOT + aoff;
                float c0[4] = {0.f, 0.f, 0.f, 0.f}, c1[4] = {0.f, 0.f, 0.f, 0.f};
#pragma unroll
                for (int k2 = 0; k2 < 8; k2++) {
                    uint32_t a0[4], a1[4];
                    ldsm4((base ^ ((k2 & 1) * 64)) + (k2 >> 1) * 128, a0);
                    ldsm4((base ^ ((k2 & 1) * 64 + 32)) + (k2 >> 1) * 128, a1);
                    mma16816(c0, a0, qf[k2][0], qf[k2][1]);
                    mma16816(c1, a1, qf[k2][2], qf[k2][3]);
                }
                __syncwarp();
                if (lane == 0) mbar_arrive(done0 + s * 8, 4);
                sc[k * 32] = rbf(sel4(c0, t) + sel4(c1, t));
            }
        }
        bar_sync(BAR_CONS, 256);
        if (warp == 0) TL(8);
        {
            constexpr float C = 0.0625f * 1.4426950408889634f;
            const float* sc = reinterpret_cast<const float*>(smem + SM_S);
            float* stat = reinterpret_cast<float*>(smem + SM_STAT);
            const float2 s0 = *reinterpret_cast<const float2*>(sc + 2 * tid);
            const float2 s1 = *reinterpret_cast<const float2*>(sc + 520 + 2 * tid);
            float m0 = fmaxf(s0.x, s0.y), m1 = fmaxf(s1.x, s1.y);
#pragma unroll
            for (int o = 16; o > 0; o >>= 1) {
                m0 = fmaxf(m0, __shfl_xor_sync(0xffffffffu, m0, o));
                m1 = fmaxf(m1, __shfl_xor_sync(0xffffffffu, m1, o));
            }
            if (lane == 0) *reinterpret_cast<float2*>(stat + warp * 2) = make_float2(m0, m1);
            bar_sync(BAR_CONS, 256);
#pragma unroll
            for (int w = 0; w < 8; w++) {
                const float2 mm = *reinterpret_cast<const float2*>(stat + w * 2);
                m0 = fmaxf(m0, mm.x); m1 = fmaxf(m1, mm.y);
            }
            const float p00 = ex2((s0.x - m0) * C), p01 = ex2((s0.y - m0) * C);
            const float p10 = ex2((s1.x - m1) * C), p11 = ex2((s1.y - m1) * C);
            uint32_t* ps = reinterpret_cast<uint32_t*>(smem + SM_P);
            ps[tid] = pack_bf(p00, p01);
            ps[272 + tid] = pack_bf(p10, p11);
            float l0 = p00 + p01, l1 = p10 + p11;
#pragma unroll
            for (int o = 16; o > 0; o >>= 1) {
                l0 += __shfl_xor_sync(0xffffffffu, l0, o);
                l1 += __shfl_xor_sync(0xffffffffu, l1, o);
            }
            if (lane == 0) *reinterpret_cast<float2*>(stat + 16 + warp * 2) = make_float2(l0, l1);
            bar_sync(BAR_CONS, 256);
            if (tid < 2) {
                float l = 0.f;
#pragma unroll
                for (int w = 0; w < 8; w++) l += stat[16 + w * 2 + tid];
                st_pub2(scr->ml + ((hkv * 2 + tid) * 2 + bat) * 8 + sp, tagf((tid ? m1 : m0) * C, tag), tagf(l, tag));
            }
        }
        if (warp == 0) TL(9);
        uint4* odst = scr->outp + ((size_t)(tid / LPM) * NCTA + cta) * LPM + lane % LPM;
        uint32_t h0 = 0, h1 = 0;
        {
            float o0[4] = {0.f, 0.f, 0.f, 0.f}, o1[4] = {0.f, 0.f, 0.f, 0.f};
            float o2[4] = {0.f, 0.f, 0.f, 0.f}, o3[4] = {0.f, 0.f, 0.f, 0.f};
            const uint32_t aoff = ((lane & 7) + (lane >> 4) * 8) * 512 + ((warp * 4 + ((lane >> 3) & 1) * 2) ^ (lane & 7)) * 16;
            const uint4* ps = reinterpret_cast<const uint4*>(smem + SM_P + (g & 1) * 272 * 4) + t;
            uint32_t* dst = reinterpret_cast<uint32_t*>(scr->part) + ((size_t)(hkv * 16 + (t & 1) * 8 + warp) * 16 + j) * 32 +
                            (4 * (g & 3) + (t & 2) + (g >> 2)) * 2;
#pragma unroll
            for (int k = 0; k < 16; k++) {
                const uint4 pa = ps[k * 4];
                mbar_wait(full0 + (S_V + k) * 8);
                uint32_t a[4][4];
#pragma unroll
                for (int i = 0; i < 4; i++) ldsm4t(sb + (aoff ^ ((i & 1) * 16)) + slot_of(S_V + k) + (i >> 1) * 8192, a[i]);
                mma16816(o0, a[0], pa.x, pa.y);
                mma16816(o1, a[1], pa.x, pa.y);
                mma16816(o2, a[2], pa.z, pa.w);
                mma16816(o3, a[3], pa.z, pa.w);
                if (S_V + k + NS < NSTAGE) {
                    __syncwarp();
                    if (lane == 0) mbar_arrive(done0 + (S_V + k) * 8, 1);
                }
                if (k == FFN_ST && warp < 7 && cta < NFFN) {
                    strip_partial(sb, SM_STRIP, smem, warp, lane);
                    bar_sync(BAR_FF, 224);
                    float ga = rbf(strip_sum(smem, lane));
                    ga *= (ga > 0.f ? 1.f : 0.f);
                    const float hv = ga * rbf(strip_sum(smem, 32 + lane));
                    const uint32_t w = pack_bf(hv, __shfl_xor_sync(0xffffffffu, hv, 2));
                    h0 = __shfl_sync(0xffffffffu, w, 4 * t + (g & 1));
                    h1 = __shfl_sync(0xffffffffu, w, 4 * t + 16 + (g & 1));
                }
                if (k == FFN_ST && warp == 7) {
                    const uint2* mlp = scr->ml + (hkv * 2 + (j >> 3)) * 16 + g;
                    uint2 a, b;
                    int it = 0;
                    do {
                        a = ld_poll2(mlp); b = ld_poll2(mlp + 8);
                        if (++it > SPIN_LIMIT) __trap();
                    } while (warp_bad(bad2(a.x, a.y, tag) | bad2(b.x, b.y, tag)));
                    float m[2] = {__uint_as_float(a.x), __uint_as_float(b.x)};
                    float l[2] = {__uint_as_float(a.y), __uint_as_float(b.y)};
#pragma unroll
                    for (int bb = 0; bb < 2; bb++) {
                        float M = m[bb];
                        M = fmaxf(M, __shfl_xor_sync(0xffffffffu, M, 4));
                        M = fmaxf(M, __shfl_xor_sync(0xffffffffu, M, 8));
                        M = fmaxf(M, __shfl_xor_sync(0xffffffffu, M, 16));
                        const float e = ex2(m[bb] - M);
                        float L = e * l[bb];
                        L += __shfl_xor_sync(0xffffffffu, L, 4);
                        L += __shfl_xor_sync(0xffffffffu, L, 8);
                        L += __shfl_xor_sync(0xffffffffu, L, 16);
                        (bb ? h1 : h0) = __float_as_uint(__fdividef(e, L));
                    }
                }
                if (k == PRE_ST) {
                    st_pub2(dst, tag ^ 1, tag ^ 1);
                    if (warp < 7) st_pub4(odst, make_uint4(tag ^ 1, tag ^ 1, tag ^ 1, tag ^ 1));
                }
            }
            const float v0 = sel4(o0, t) + sel4(o2, t), v1 = sel4(o1, t) + sel4(o3, t);
            st_pub2(dst, tagf(v0, tag), tagf(v1, tag));
        }
        if (warp == 0) TL(10);
        if (warp < 7) {
            float c[4][4];
#pragma unroll
            for (int m = 0; m < 4; m++)
#pragma unroll
                for (int e = 0; e < 4; e++) c[m][e] = 0.f;
            const int r7 = ((lane & 7) >> 1) + 4 * (lane >> 4);
            const uint32_t aoff = sb + (r7 + 8 * (lane & 1)) * 896 + ((warp * 8 + ((lane >> 3) & 1)) ^ r7 ^ ((lane & 1) << 2)) * 16;
            uint32_t a[4][4];
            if (cta < NFFN) {
                mbar_wait(full0 + S_DN * 8);
#pragma unroll
                for (int m = 0; m < 4; m++) ldsm4t((aoff ^ (m * 32)) + slot_of(S_DN), a[m]);
#pragma unroll
                for (int m = 0; m < 4; m++) mma16816(c[m], a[m], h0, h1);
            }
            mbar_wait(full0 + S_WO * 8);
#pragma unroll
            for (int m = 0; m < 4; m++) ldsm4t((aoff ^ (m * 32)) + slot_of(S_WO), a[m]);
            bar_sync(BAR_OB, 256);
            const uint4 ob = *reinterpret_cast<const uint4*>(smem + SM_OB + (g & 1) * 64 + t * 16);
            mbar_wait(full0 + (S_WO + 1) * 8);
            uint32_t a2[4][4];
#pragma unroll
            for (int m = 0; m < 4; m++) ldsm4t((aoff ^ (m * 32)) + slot_of(S_WO + 1), a2[m]);
#pragma unroll
            for (int m = 0; m < 4; m++) mma16816(c[m], a[m], ob.x, ob.y);
#pragma unroll
            for (int m = 0; m < 4; m++) mma16816(c[m], a2[m], ob.z, ob.w);
            uint4 r;
            r.x = tagf(sel4(c[0], t), tag); r.y = tagf(sel4(c[1], t), tag);
            r.z = tagf(sel4(c[2], t), tag); r.w = tagf(sel4(c[3], t), tag);
            st_pub4(odst, r);
            if (warp == 0) TL(12);
        } else {
            const uint4* pp = scr->part + (size_t)cta * 128 + g * 8 + t;
            uint32_t* obp = reinterpret_cast<uint32_t*>(smem + SM_OB) + (lane >> 4) * 16 + (t + 4 * ((lane >> 3) & 1)) * 2 + ((lane >> 2) & 1);
            while (time_ns() - t0 < TN_E2) {}
            TL(2);
            uint4 v[4];
            uint32_t bad[4] = {1, 1, 1, 1};
            for (int it = 0;; it++) {
#pragma unroll
                for (int i = 0; i < 4; i++) ld_poll4_if(v[i], pp + (i >> 1) * 64 + (i & 1) * 4, bad[i]);
#pragma unroll
                for (int i = 0; i < 4; i++) bad[i] = bad4(v[i], tag);
                if (!warp_bad(bad[0] | bad[1] | bad[2] | bad[3])) break;
                if (it > SPIN_LIMIT) __trap();
            }
            TL(3);
            float r8[8], r4[4], r2[2];
            const bool h16 = lane & 16, h8 = lane & 8, h4 = lane & 4;
            {
                const float wk = __uint_as_float(h16 ? h1 : h0), ws = __uint_as_float(h16 ? h0 : h1);
                const uint32_t f0[8] = {v[0].x, v[0].y, v[0].z, v[0].w, v[1].x, v[1].y, v[1].z, v[1].w};
                const uint32_t f1[8] = {v[2].x, v[2].y, v[2].z, v[2].w, v[3].x, v[3].y, v[3].z, v[3].w};
#pragma unroll
                for (int e = 0; e < 8; e++) {
                    const float keep = __uint_as_float(h16 ? f1[e] : f0[e]), send = __uint_as_float(h16 ? f0[e] : f1[e]);
                    r8[e] = fmaf(keep, wk, __shfl_xor_sync(0xffffffffu, send * ws, 16));
                }
            }
#pragma unroll
            for (int e = 0; e < 4; e++) {
                const float keep = h8 ? r8[4 + e] : r8[e], send = h8 ? r8[e] : r8[4 + e];
                r4[e] = keep + __shfl_xor_sync(0xffffffffu, send, 8);
            }
#pragma unroll
            for (int e = 0; e < 2; e++) {
                const float keep = h4 ? r4[2 + e] : r4[e], send = h4 ? r4[e] : r4[2 + e];
                r2[e] = keep + __shfl_xor_sync(0xffffffffu, send, 4);
            }
            *obp = pack_bf(r2[0], r2[1]);
            bar_arrive(BAR_OB, 256);
            TL(14);
        }
    } else if (warp < 8 + NPW) {
        const int pt = tid - 256, pw = warp - 8;
        Prod p;
        p.t0 = time_ns();
        if (lane == 0) {
            const int w = __shfl_sync(1u, pw, 0);
#pragma unroll
            for (int i = 0; i < 10; i++) {
                if (w * 10 + i != B_X) mbar_init(full0 + (w * 10 + i) * 8, NPT);
                mbar_init(done0 + (w * 10 + i) * 8, 8);
            }
        }
        const size_t kvoff = ((size_t)(bat * 8 + hkv) * SK + (SK - WIN) + sp * 512) * DH * 2 + pt * 16;
        p.sb = sb;
        p.kvdst = (pt ^ pw) * 16;
        p.sdst = sb + SM_STRIP + (pt >> 2) * 64 + ((pt & 3) ^ ((pt >> 3) & 3)) * 16;
#pragma unroll
        for (int i = 0; i < 7; i++) {
            const int id = i * NPT + pt, row = id / 56;
            p.rdst[i] = (id ^ (row & 7) ^ ((row >> 3) << 2)) * 16;
        }
        p.k = reinterpret_cast<const char*>(kc) + kvoff;
        p.v = reinterpret_cast<const char*>(vc) + kvoff;
        p.wo = reinterpret_cast<const char*>(wo) + (size_t)cta * 28672 + pt * 16;
        p.wd = reinterpret_cast<const char*>(wd) + (size_t)cta * 14336 + pt * 16;
        p.gu = ((pt & 2) ? wu : wg) + cta * 16 + (pt & 1) * 8 + (size_t)(pt >> 2) * FF;
        p.ffn = cta < NFFN;
        asm volatile("" :: "l"(p.gu), "l"(p.wd));
        __syncthreads();
        produce<0>(p);
        if (pw == 0) TL(1);
        asm volatile("cp.async.wait_all;" ::: "memory");
        if (cta % RSTEP == 0 && cta < NRED * RSTEP) {
            constexpr int NL = LPM;
            const int rid = cta / RSTEP;
            const uint32_t tag = (*reinterpret_cast<const uint32_t*>(smem + SM_X + 1792) + 1) & 1;
            const uint4* op = scr->outp + (size_t)rid * (NCTA * LPM) + pw * (NL * 32) + lane;
            const int sl = rid * LPM + lane % LPM;
            const int oidx = (sl & 1) * D_MODEL + (sl >> 5) * 64 + (lane >> 3) * 16 + ((sl >> 2) & 7) + (sl & 2) * 4;
            const float xv = __bfloat162float(reinterpret_cast<const __nv_bfloat16*>(smem + SM_X)[oidx]);
            float* red = reinterpret_cast<float*>(smem + SM_S) + lane;
            uint4 v[NL];
            uint32_t bad[NL];
#pragma unroll
            for (int i = 0; i < NL; i++) bad[i] = 1;
            while (time_ns() - p.t0 < TN_E3) {}
            for (int it = 0;; it++) {
                uint32_t any = 0;
#pragma unroll
                for (int i = 0; i < NL; i++) ld_poll4_if(v[i], op + i * 32, bad[i]);
#pragma unroll
                for (int i = 0; i < NL; i++) { bad[i] = bad4(v[i], tag); any |= bad[i]; }
                if (!warp_bad(any)) break;
                if (it > SPIN_LIMIT) __trap();
            }
            if (pw == 0) TL(4);
            float a[NL][4];
#pragma unroll
            for (int i = 0; i < NL; i++) {
                a[i][0] = __uint_as_float(v[i].x); a[i][1] = __uint_as_float(v[i].y);
                a[i][2] = __uint_as_float(v[i].z); a[i][3] = __uint_as_float(v[i].w);
            }
#pragma unroll
            for (int o = NL / 2; o > 0; o >>= 1)
#pragma unroll
                for (int i = 0; i < o; i++)
#pragma unroll
                    for (int e = 0; e < 4; e++) a[i][e] += a[i + o][e];
            const bool h16 = lane & 16, h8 = lane & 8;
            float r2[2];
#pragma unroll
            for (int e = 0; e < 2; e++)
                r2[e] = (h16 ? a[0][2 + e] : a[0][e]) + __shfl_xor_sync(0xffffffffu, h16 ? a[0][e] : a[0][2 + e], 16);
            float r = (h8 ? r2[1] : r2[0]) + __shfl_xor_sync(0xffffffffu, h8 ? r2[0] : r2[1], 8);
            if (LPM <= 4) r += __shfl_xor_sync(0xffffffffu, r, 4);
            if (LPM <= 2) r += __shfl_xor_sync(0xffffffffu, r, 2);
            if (pw != 0) {
                red[pw * 32] = r;
                bar_arrive(BAR_FIN, NPT);
            } else {
                bar_sync(BAR_FIN, NPT);
                r = (r + red[32]) + (red[64] + red[96]);
                if ((lane & 7) < LPM) out[oidx] = __float2bfloat16_rn(xv + r);
                TL(5);
            }
        }
    }
}

}

extern "C" void kernel_launch(void* const* d_in, const int* in_sizes, int n_in, void* d_out, int out_size) {
    (void)in_sizes; (void)n_in; (void)out_size;
    static Scratch* scr = nullptr;
    if (!scr) {
        cudaFuncSetAttribute(fused_decode_kernel, cudaFuncAttributeMaxDynamicSharedMemorySize, SM_TOTAL);
        cudaGetSymbolAddress(reinterpret_cast<void**>(&scr), g_scratch);
    }
    typedef const __nv_bfloat16* P;
    fused_decode_kernel<<<NCTA, NTHREADS, SM_TOTAL>>>((P)d_in[3], (P)d_in[1], (P)d_in[0], scr, (P)d_in[2], (P)d_in[4],
                                                      (P)d_in[6], (P)d_in[7], (P)d_in[8], (__nv_bfloat16*)d_out TN_ARG);
}
```

```cpp
#include <cuda_runtime.h>
#include <cuda_bf16.h>
#include <stdint.h>

namespace {

#define PACE_DT 636
#define PACE_LEAD 550
#define LATE_T 22380
#define LATE_DT 400
#define XPOS 1
#define EVICT 2
#define FFN_ST 8
#define E2_T 23900
#define E3_T 24920
#define LPM 4
#define PRE_ST 12

#define TN_E2 E2_T
#define TN_E3 E3_T
#define EPB 16

constexpr int D_MODEL = 448;
constexpr int SK      = 32768;
constexpr int WIN     = 4096;
constexpr int DH      = 256;
constexpr int QCOLS   = 4096;
constexpr int FF      = 1792;
constexpr int NCTA    = 128;
constexpr int NFFN    = 112;
constexpr int NPW     = 4;
constexpr int NPT     = NPW * 32;
constexpr int NTHREADS = 256 + NPT;
constexpr int NRED    = 224 / LPM;
constexpr int RSTEP   = LPM / 2;

constexpr int NS     = 11;
constexpr int SLOT   = 16384;
constexpr int XROW   = 912;
constexpr int S_K  = 0;
constexpr int S_V  = 16;
constexpr int S_DN = 32;
constexpr int S_WO = 33;
constexpr int NSTAGE = 35;
#define GU_FIRST 8
constexpr int S_GU = GU_FIRST;
constexpr int NBAR   = 40;
constexpr int B_X = NSTAGE, B_Q = NBAR + NSTAGE;

constexpr int SM_RING = 0;
constexpr int SM_STRIP = SM_RING + NS * SLOT;
constexpr int SM_S    = SM_STRIP + 448 * 64;
constexpr int SM_P    = SM_S + 2 * 520 * 4;
constexpr int SM_Q    = SM_P + 2 * 272 * 4;
constexpr int SM_XN   = SM_Q + 2 * 264 * 2;
constexpr int SM_X    = SM_XN + 2 * XROW;
constexpr int SM_RED  = SM_X + 1792 + 32;
constexpr int SM_STAT = SM_RED + 7 * 64 * 4;
constexpr int SM_OB   = SM_STAT + 2 * 8 * 2 * 4;
constexpr int SM_BAR  = SM_OB + 2 * 16 * 4;
constexpr int SM_TOTAL = SM_BAR + 2 * NBAR * 8;
static_assert(SM_Q % 16 == 0 && SM_XN % 16 == 0 && SM_X % 16 == 0 && SM_OB % 16 == 0 && SM_P % 16 == 0 && SM_BAR % 8 == 0, "align");
static_assert(S_GU + 13 <= S_V + FFN_ST, "the gate/up strip lands with stage S_GU + 13");

constexpr int SPIN_LIMIT = 1 << 22;

struct Scratch {
    uint4    part[NCTA * 2 * 8 * 8];
    uint4    outp[NRED * NCTA * LPM];
    uint4    q[8 * 2 * 128];
    uint2    ml[NCTA * 4];
    unsigned epoch[NCTA * 8];
};
__device__ Scratch g_scratch;

#define TL(i)

__device__ __forceinline__ void mbar_init(uint32_t bar, uint32_t cnt) {
    asm volatile("mbarrier.init.shared::cta.b64 [%0], %1;" :: "r"(bar), "r"(cnt) : "memory");
}
__device__ __forceinline__ void mbar_arrive(uint32_t bar, uint32_t cnt) {
    asm volatile("mbarrier.arrive.shared::cta.b64 _, [%0], %1;" :: "r"(bar), "r"(cnt) : "memory");
}
__device__ __forceinline__ bool mbar_try(uint32_t bar) {
    uint32_t ok;
    asm volatile("{\n.reg .pred p;\nmbarrier.try_wait.parity.shared::cta.b64 p, [%1], 0;\nselp.u32 %0, 1, 0, p;\n}"
                 : "=r"(ok) : "r"(bar) : "memory");
    return ok;
}
__device__ __forceinline__ bool mbar_test(uint32_t bar) {
    uint32_t ok;
    asm volatile("{\n.reg .pred p;\nmbarrier.test_wait.parity.shared::cta.b64 p, [%1], 0;\nselp.u32 %0, 1, 0, p;\n}"
                 : "=r"(ok) : "r"(bar) : "memory");
    return ok;
}
__device__ __forceinline__ uint32_t time_ns() { uint32_t t; asm volatile("mov.u32 %0, %globaltimer_lo;" : "=r"(t)); return t; }
__device__ __forceinline__ void mbar_wait(uint32_t bar) {
    asm volatile("{\n.reg .pred p;\nWAIT_LOOP:\nmbarrier.try_wait.parity.shared::cta.b64 p, [%0], 0;\n@!p bra WAIT_LOOP;\n}" :: "r"(bar) : "memory");
}
__device__ __forceinline__ void mbar_spin(uint32_t bar) {
    mbar_wait(bar);
}
__device__ __forceinline__ void cp_async16(uint32_t dst, const void* src) {
    asm volatile("cp.async.cg.shared.global [%0], [%1], 16;" :: "r"(dst), "l"(src) : "memory");
}
__device__ __forceinline__ void cp_async16_stream(uint32_t dst, const void* src) {
    asm volatile("{\n.reg .b64 pol;\ncreatepolicy.fractional.L2::evict_first.b64 pol, 1.0;\ncp.async.cg.shared.global.L2::cache_hint [%0], [%1], 16, pol;\n}" :: "r"(dst), "l"(src) : "memory");
}
__device__ __forceinline__ void cp_async_arrive(uint32_t bar) {
    asm volatile("cp.async.mbarrier.arrive.noinc.shared::cta.b64 [%0];" :: "r"(bar) : "memory");
}
__device__ __forceinline__ void bar_sync(int id, int n)   { asm volatile("bar.sync %0, %1;" :: "r"(id), "r"(n) : "memory"); }
__device__ __forceinline__ void bar_arrive(int id, int n) { asm volatile("bar.arrive %0, %1;" :: "r"(id), "r"(n) : "memory"); }

__device__ __forceinline__ uint2 ld_poll2(const void* p) {
    uint2 v;
    asm volatile("ld.relaxed.gpu.global.v2.u32 {%0,%1}, [%2];" : "=r"(v.x), "=r"(v.y) : "l"(p) : "memory");
    return v;
}
__device__ __forceinline__ uint4 ld_poll4(const void* p) {
    uint4 v;
    asm volatile("ld.relaxed.gpu.global.v4.u32 {%0,%1,%2,%3}, [%4];" : "=r"(v.x), "=r"(v.y), "=r"(v.z), "=r"(v.w) : "l"(p) : "memory");
    return v;
}
__device__ __forceinline__ void ld_poll4_if(uint4& v, const void* p, uint32_t bad) {
    asm volatile("{\n.reg .pred p;\n.reg .b32 t;\nand.b32 t, %5, 1;\nsetp.ne.u32 p, t, 0;\n"
                 "@p ld.relaxed.gpu.global.v4.u32 {%0,%1,%2,%3}, [%4];\n}"
                 : "+r"(v.x), "+r"(v.y), "+r"(v.z), "+r"(v.w) : "l"(p), "r"(bad) : "memory");
}
__device__ __forceinline__ void st_pub4(void* p, uint4 v) {
    asm volatile("st.relaxed.gpu.global.v4.u32 [%0], {%1,%2,%3,%4};" :: "l"(p), "r"(v.x), "r"(v.y), "r"(v.z), "r"(v.w) : "memory");
}
__device__ __forceinline__ void st_pub2(void* p, uint32_t a, uint32_t b) {
    asm volatile("st.relaxed.gpu.global.v2.u32 [%0], {%1,%2};" :: "l"(p), "r"(a), "r"(b) : "memory");
}
__device__ __forceinline__ void st_pub1(void* p, uint32_t a) {
    asm volatile("st.relaxed.gpu.global.u32 [%0], %1;" :: "l"(p), "r"(a) : "memory");
}
__device__ __forceinline__ uint32_t tagf(float v, uint32_t tag) { return (__float_as_uint(v) & ~1u) | tag; }
__device__ __forceinline__ uint32_t bad2(uint32_t a, uint32_t b, uint32_t tag) {
    uint32_t r;
    asm("lop3.b32 %0, %1, %2, %3, 0x7E;" : "=r"(r) : "r"(a), "r"(b), "r"(tag));
    return r;
}
__device__ __forceinline__ uint32_t bad4(const uint4& v, uint32_t tag) { return bad2(v.x, v.y, tag) | bad2(v.z, v.w, tag); }
__device__ __forceinline__ bool warp_bad(uint32_t bad) { return __any_sync(0xffffffffu, bad & 1u); }

__device__ __forceinline__ uint32_t or3(uint32_t a, uint32_t b, uint32_t c) {
    uint32_t r;
    asm("lop3.b32 %0, %1, %2, %3, 0xFE;" : "=r"(r) : "r"(a), "r"(b), "r"(c));
    return r;
}
template <int N>
__device__ __forceinline__ void poll_all(uint4 (&v)[N], const uint4* p, int s1, int s2, uint32_t tag) {
#pragma unroll
    for (int i = 0; i < N; i++) v[i] = ld_poll4(p + (i & 1) * s1 + (i >> 1) * s2);
    for (int it = 0;; it++) {
        uint32_t any = 0;
#pragma unroll
        for (int i = 0; i < N; i++) any = or3(any, bad2(v[i].x, v[i].y, tag), bad2(v[i].z, v[i].w, tag));
        if (__builtin_expect(!warp_bad(any), 1)) break;
#pragma unroll
        for (int i = 0; i < N; i++) ld_poll4_if(v[i], p + (i & 1) * s1 + (i >> 1) * s2, bad4(v[i], tag));
        if (it > SPIN_LIMIT) __trap();
    }
}

__device__ __forceinline__ void ldsm4(uint32_t addr, uint32_t (&a)[4]) {
    asm volatile("ldmatrix.sync.aligned.m8n8.x4.shared.b16 {%0,%1,%2,%3}, [%4];" : "=r"(a[0]), "=r"(a[1]), "=r"(a[2]), "=r"(a[3]) : "r"(addr) : "memory");
}
__device__ __forceinline__ void ldsm4t(uint32_t addr, uint32_t (&a)[4]) {
    asm volatile("ldmatrix.sync.aligned.m8n8.x4.trans.shared.b16 {%0,%1,%2,%3}, [%4];" : "=r"(a[0]), "=r"(a[1]), "=r"(a[2]), "=r"(a[3]) : "r"(addr) : "memory");
}
__device__ __forceinline__ void mma16816(float (&c)[4], const uint32_t (&a)[4], uint32_t b0, uint32_t b1) {
    asm volatile("mma.sync.aligned.m16n8k16.row.col.f32.bf16.bf16.f32 {%0,%1,%2,%3}, {%4,%5,%6,%7}, {%8,%9}, {%0,%1,%2,%3};"
                 : "+f"(c[0]), "+f"(c[1]), "+f"(c[2]), "+f"(c[3]) : "r"(a[0]), "r"(a[1]), "r"(a[2]), "r"(a[3]), "r"(b0), "r"(b1));
}
__device__ __forceinline__ float bf_lo(uint32_t u) { return __uint_as_float(u << 16); }
__device__ __forceinline__ float bf_hi(uint32_t u) { return __uint_as_float(u & 0xffff0000u); }
__device__ __forceinline__ float rbf(float v) { return __bfloat162float(__float2bfloat16_rn(v)); }
__device__ __forceinline__ uint32_t pack_bf(float lo, float hi) {
    uint32_t r;
    asm("cvt.rn.bf16x2.f32 %0, %1, %2;" : "=r"(r) : "f"(hi), "f"(lo));
    return r;
}
__device__ __forceinline__ float sel4(const float (&c)[4], int t) {
    float a = (t & 1) ? c[1] : c[0];
    float b = (t & 1) ? c[3] : c[2];
    return (t & 2) ? b : a;
}
__device__ __forceinline__ float ex2(float x) { float y; asm("ex2.approx.ftz.f32 %0, %1;" : "=f"(y) : "f"(x)); return y; }
__device__ __forceinline__ float sqrt_approx(float x) { float y; asm("sqrt.approx.f32 %0, %1;" : "=f"(y) : "f"(x)); return y; }

__device__ __forceinline__ constexpr uint32_t slot_of(int s) { return SM_RING + (s % NS) * SLOT; }

__device__ __forceinline__ void layernorm(unsigned char* smem, int lane) {
    uint32_t xs[2][7];
#pragma unroll
    for (int b = 0; b < 2; b++)
#pragma unroll
        for (int i = 0; i < 7; i++) xs[b][i] = reinterpret_cast<const uint32_t*>(smem + SM_X)[b * (D_MODEL / 2) + i * 32 + lane];
#pragma unroll
    for (int b = 0; b < 2; b++) {
        float sum = 0.f;
#pragma unroll
        for (int i = 0; i < 7; i++) sum += bf_lo(xs[b][i]) + bf_hi(xs[b][i]);
#pragma unroll
        for (int o = 16; o > 0; o >>= 1) sum += __shfl_xor_sync(0xffffffffu, sum, o);
        const float mean = sum * (1.0f / D_MODEL);
        float sq = 0.f;
#pragma unroll
        for (int i = 0; i < 7; i++) {
            const float d0 = bf_lo(xs[b][i]) - mean, d1 = bf_hi(xs[b][i]) - mean;
            sq = fmaf(d0, d0, fmaf(d1, d1, sq));
        }
#pragma unroll
        for (int o = 16; o > 0; o >>= 1) sq += __shfl_xor_sync(0xffffffffu, sq, o);
        const float mb = rbf(mean);
        const float sd = rbf(sqrt_approx(rbf(rbf(sq * (1.0f / D_MODEL)) + 1e-5f)));
#pragma unroll
        for (int i = 0; i < 7; i++)
            reinterpret_cast<uint32_t*>(smem + SM_XN + b * XROW)[i * 32 + lane] =
                pack_bf(__fdividef(rbf(bf_lo(xs[b][i]) - mb), sd), __fdividef(rbf(bf_hi(xs[b][i]) - mb), sd));
    }
}

__device__ __forceinline__ void strip_partial(uint32_t sb, uint32_t strip, unsigned char* smem, int warp, int lane) {
    float c[2][2][4];
#pragma unroll
    for (int n = 0; n < 2; n++)
#pragma unroll
        for (int e = 0; e < 4; e++) c[n][0][e] = c[n][1][e] = 0.f;
    const uint32_t ba = sb + SM_XN + (lane & 1) * XROW + (lane >> 3) * 16 + warp * 128;
    const uint32_t aa = sb + strip + (warp * 64 + (lane & 7) + (lane >> 4) * 8) * 64 + (((lane >> 3) & 1) ^ ((lane & 7) >> 1)) * 16;
#pragma unroll
    for (int k2 = 0; k2 < 2; k2++) {
        uint32_t b[4];
        ldsm4(ba + k2 * 64, b);
#pragma unroll
        for (int n = 0; n < 2; n++) {
            uint32_t a0[4], a1[4];
            ldsm4t((aa ^ (n * 32)) + k2 * 2048, a0);
            ldsm4t((aa ^ (n * 32)) + k2 * 2048 + 1024, a1);
            mma16816(c[n][0], a0, b[0], b[1]);
            mma16816(c[n][1], a1, b[2], b[3]);
        }
    }
    float* red = reinterpret_cast<float*>(smem + SM_RED) + warp * 64 + lane;
#pragma unroll
    for (int n = 0; n < 2; n++) red[n * 32] = sel4(c[n][0], lane & 3) + sel4(c[n][1], lane & 3);
}
__device__ __forceinline__ float strip_sum(const unsigned char* smem, int idx) {
    const float* red = reinterpret_cast<const float*>(smem + SM_RED) + idx;
    return ((red[0] + red[64]) + (red[128] + red[192])) + ((red[256] + red[320]) + red[384]);
}

struct Prod {
    uint32_t sb, kvdst, sdst, rdst[7], t0;
    const char *k, *v, *wo, *wd;
    const __nv_bfloat16* gu;
    bool ffn;
};
__host__ __device__ constexpr int bytes_before(int s) {
    return 28672 + (s <= S_DN ? s * 16384 : S_DN * 16384 + 12544 + (s - S_WO) * 14336) + (s <= S_GU ? 0 : s < S_GU + 14 ? s - S_GU : 14) * 1792;
}
__host__ __device__ constexpr int issue_time(int s) {
    return s < S_DN ? (int)((long long)bytes_before(s) * PACE_DT / 16384) - PACE_LEAD : LATE_T + (s - S_DN) * LATE_DT;
}

template <int S>
__device__ __forceinline__ void issue_stage(const Prod& p) {
    const uint32_t dst = p.sb + slot_of(S);
    if constexpr (S < S_DN) {
        const char* src = S < S_V ? p.k + (S - S_K) * 16384 : p.v + (S - S_V) * 16384;
#pragma unroll
        for (int i = 0; i < 8; i++) cp_async16_stream((p.kvdst ^ ((i & 1) * 64)) + slot_of(S) + i * 2048, src + i * 2048);
        if constexpr (S >= S_GU && S < S_GU + 14) {
            if (p.ffn) cp_async16(p.sdst + (S - S_GU) * 2048, p.gu + (size_t)(S - S_GU) * 32 * FF);
        }
    } else {
        if (S != S_DN || p.ffn) {
            const char* src = S != S_DN ? p.wo + (S - S_WO) * 14336 : p.wd;
#pragma unroll
            for (int i = 0; i < 7; i++) cp_async16(dst + p.rdst[i], src + i * 2048);
        }
    }
    cp_async_arrive(p.sb + SM_BAR + S * 8);
}
template <int S>
__device__ __forceinline__ void produce(Prod& p) {
    if constexpr (S < NSTAGE) {
        if constexpr (S == S_GU) mbar_wait(p.sb + SM_BAR + B_Q * 8);
        if constexpr (S >= NS) mbar_wait(p.sb + SM_BAR + (NBAR + S - NS) * 8);
        while (time_ns() - p.t0 < (uint32_t)issue_time(S)) {}
        issue_stage<S>(p);
        produce<S + 1>(p);
    }
}

__device__ __forceinline__ void load_x(uint32_t sb, const void* x, const void* epoch) {
    const uint32_t full0 = sb + SM_BAR;
    mbar_init(full0 + B_X * 8, 1);
    asm volatile("fence.mbarrier_init.release.cluster;" ::: "memory");
    asm volatile("mbarrier.arrive.expect_tx.shared::cta.b64 _, [%0], %1;" :: "r"(full0 + B_X * 8), "r"(1792 + EPB) : "memory");
    asm volatile("cp.async.bulk.shared::cluster.global.mbarrier::complete_tx::bytes [%0], [%1], %2, [%3];"
                 :: "r"(sb + SM_X), "l"(x), "r"(1792), "r"(full0 + B_X * 8) : "memory");
    asm volatile("cp.async.bulk.shared::cluster.global.mbarrier::complete_tx::bytes [%0], [%1], %2, [%3];"
                 :: "r"(sb + SM_X + 1792), "l"(epoch), "r"(EPB), "r"(full0 + B_X * 8) : "memory");
}

enum { BAR_OB = 1, BAR_CONS = 2, BAR_LN = 3, BAR_FF = 4, BAR_FIN = 5 };

__global__ void __launch_bounds__(NTHREADS, 1)
fused_decode_kernel(const __nv_bfloat16* __restrict__ wq, const __nv_bfloat16* __restrict__ kc, const __nv_bfloat16* __restrict__ x,
                    Scratch* __restrict__ scr, const __nv_bfloat16* __restrict__ vc, const __nv_bfloat16* __restrict__ wo,
                    const __nv_bfloat16* __restrict__ wg, const __nv_bfloat16* __restrict__ wu, const __nv_bfloat16* __restrict__ wd,
                    __nv_bfloat16* __restrict__ out) {
    extern __shared__ __align__(128) unsigned char smem[];
    const uint32_t sb = (uint32_t)__cvta_generic_to_shared(smem);
    const int tid = threadIdx.x, warp = tid >> 5, lane = tid & 31;
    const int cta = blockIdx.x;
    const uint32_t full0 = sb + SM_BAR, done0 = full0 + NBAR * 8;
    if (tid < 224) {
        const int row = warp * 64 + (lane >> 2);
        const char* src = reinterpret_cast<const char*>(wq) + (uint32_t)(row * (QCOLS * 2) + cta * 64 + (lane & 3) * 16);
        const uint32_t dst = sb + SM_STRIP + row * 64 + ((lane & 3) ^ (lane >> 3)) * 16;
#pragma unroll
        for (int i = 0; i < 8; i++) cp_async16(dst + i * 512, src + i * (8 * QCOLS * 2));
    }
    const int hkv = cta >> 4, j = cta & 15, bat = j >> 3, sp = j & 7;

    if (warp < 8) {
        const int g = lane >> 2, t = lane & 3;
        const uint32_t t0 = time_ns();
        if (warp == 0) TL(0);
        if (tid == 224) load_x(sb, x, &scr->epoch[cta * 8]);
        __syncthreads();
        mbar_wait(full0 + B_X * 8);
        const uint32_t epoch = *reinterpret_cast<const uint32_t*>(smem + SM_X + 1792);
        const uint32_t tag = (epoch + 1) & 1;
        uint32_t* qdst = reinterpret_cast<uint32_t*>(scr->q) + (hkv * 2 + (t & 1)) * 512 + j * 32 + warp * 16 + g + 8 * (t >> 1);
        if (warp < 2) st_pub1(qdst, tag ^ 1);
        if (warp == 7) {
            layernorm(smem, lane);
            bar_arrive(BAR_LN, 256);
            TL(13);
        } else {
            asm volatile("cp.async.wait_all;" ::: "memory");
            bar_sync(BAR_LN, 256);
            strip_partial(sb, SM_STRIP, smem, warp, lane);
        }
        bar_sync(BAR_CONS, 256);
        if (warp < 2) {
            st_pub1(qdst, (pack_bf(0.f, strip_sum(smem, tid)) & 0xffff0000u) | tag);
            if (warp == 0) TL(6);
        } else if (warp >= 4) {
            const int i = tid - 128;
            const uint4* qp = scr->q + (hkv * 2 + bat) * 128 + i;
            uint4 v;
            int it = 0;
            do {
                v = ld_poll4(qp);
                if (++it > SPIN_LIMIT) __trap();
            } while (warp_bad(bad4(v, tag)));
            *reinterpret_cast<uint2*>(smem + SM_Q + (i >> 6) * 528 + (i & 63) * 8) =
                make_uint2(__byte_perm(v.x, v.y, 0x7632), __byte_perm(v.z, v.w, 0x7632));
        }
        bar_sync(BAR_CONS, 256);
        if (tid == 96) { mbar_arrive(full0 + B_Q * 8, 8); scr->epoch[cta * 8] = epoch + 1; }
        if (warp == 0) TL(7);
        {
            uint32_t qf[8][4];
#pragma unroll
            for (int k2 = 0; k2 < 8; k2++) ldsm4(sb + SM_Q + (lane & 1) * 528 + k2 * 64 + (lane >> 3) * 16, qf[k2]);
            const int mt = warp & 1;
            const uint32_t aoff = (16 * mt + (lane & 15)) * 512 + ((lane >> 4) ^ (lane & 7)) * 16;
            float* sc = reinterpret_cast<float*>(smem + SM_S) + (t & 1) * 520 + (g >> 1) * 8 + (2 * mt + (t >> 1)) * 2 + (g & 1);
#pragma unroll 1
            for (int k = warp >> 1; k < 16; k += 4) {
                const int s = S_K + k;
                mbar_wait(full0 + s * 8);
                const uint32_t base = sb + SM_RING + (s >= NS ? s - NS : s) * SLOT + aoff;
                float c0[4] = {0.f, 0.f, 0.f, 0.f}, c1[4] = {0.f, 0.f, 0.f, 0.f};
#pragma unroll
                for (int k2 = 0; k2 < 8; k2++) {
                    uint32_t a0[4], a1[4];
                    ldsm4((base ^ ((k2 & 1) * 64)) + (k2 >> 1) * 128, a0);
                    ldsm4((base ^ ((k2 & 1) * 64 + 32)) + (k2 >> 1) * 128, a1);
                    mma16816(c0, a0, qf[k2][0], qf[k2][1]);
                    mma16816(c1, a1, qf[k2][2], qf[k2][3]);
                }
                __syncwarp();
                if (lane == 0) mbar_arrive(done0 + s * 8, 4);
                sc[k * 32] = rbf(sel4(c0, t) + sel4(c1, t));
            }
        }
        bar_sync(BAR_CONS, 256);
        if (warp == 0) TL(8);
        {
            constexpr float C = 0.0625f * 1.4426950408889634f;
            const float* sc = reinterpret_cast<const float*>(smem + SM_S);
            float* stat = reinterpret_cast<float*>(smem + SM_STAT);
            const float2 s0 = *reinterpret_cast<const float2*>(sc + 2 * tid);
            const float2 s1 = *reinterpret_cast<const float2*>(sc + 520 + 2 * tid);
            float m0 = fmaxf(s0.x, s0.y), m1 = fmaxf(s1.x, s1.y);
#pragma unroll
            for (int o = 16; o > 0; o >>= 1) {
                m0 = fmaxf(m0, __shfl_xor_sync(0xffffffffu, m0, o));
                m1 = fmaxf(m1, __shfl_xor_sync(0xffffffffu, m1, o));
            }
            if (lane == 0) *reinterpret_cast<float2*>(stat + warp * 2) = make_float2(m0, m1);
            bar_sync(BAR_CONS, 256);
#pragma unroll
            for (int w = 0; w < 8; w++) {
                const float2 mm = *reinterpret_cast<const float2*>(stat + w * 2);
                m0 = fmaxf(m0, mm.x); m1 = fmaxf(m1, mm.y);
            }
            const float p00 = ex2((s0.x - m0) * C), p01 = ex2((s0.y - m0) * C);
            const float p10 = ex2((s1.x - m1) * C), p11 = ex2((s1.y - m1) * C);
            uint32_t* ps = reinterpret_cast<uint32_t*>(smem + SM_P);
            ps[tid] = pack_bf(p00, p01);
            ps[272 + tid] = pack_bf(p10, p11);
            float l0 = p00 + p01, l1 = p10 + p11;
#pragma unroll
            for (int o = 16; o > 0; o >>= 1) {
                l0 += __shfl_xor_sync(0xffffffffu, l0, o);
                l1 += __shfl_xor_sync(0xffffffffu, l1, o);
            }
            if (lane == 0) *reinterpret_cast<float2*>(stat + 16 + warp * 2) = make_float2(l0, l1);
            bar_sync(BAR_CONS, 256);
            if (tid < 4) {
                float l = 0.f;
#pragma unroll
                for (int w = 0; w < 8; w++) l += stat[16 + w * 2 + (tid & 1)];
                st_pub2(scr->ml + cta * 4 + tid, tagf(((tid & 1) ? m1 : m0) * C, tag), tagf(l, tag));
            }
        }
        if (warp == 0) TL(9);
        uint4* odst = scr->outp + ((size_t)(tid / LPM) * NCTA + cta) * LPM + lane % LPM;
        uint32_t h0 = 0, h1 = 0;
        {
            float o0[4] = {0.f, 0.f, 0.f, 0.f}, o1[4] = {0.f, 0.f, 0.f, 0.f};
            float o2[4] = {0.f, 0.f, 0.f, 0.f}, o3[4] = {0.f, 0.f, 0.f, 0.f};
            const uint32_t aoff = ((lane & 7) + (lane >> 4) * 8) * 512 + ((warp * 4 + ((lane >> 3) & 1) * 2) ^ (lane & 7)) * 16;
            const uint4* ps = reinterpret_cast<const uint4*>(smem + SM_P + (g & 1) * 272 * 4) + t;
            uint32_t* dst = reinterpret_cast<uint32_t*>(scr->part) + ((size_t)(hkv * 16 + (t & 1) * 8 + warp) * 16 + j) * 32 +
                            (4 * (g & 3) + (t & 2) + (g >> 2)) * 2;
#pragma unroll
            for (int k = 0; k < 16; k++) {
                const uint4 pa = ps[k * 4];
                mbar_wait(full0 + (S_V + k) * 8);
                uint32_t a[4][4];
#pragma unroll
                for (int i = 0; i < 4; i++) ldsm4t(sb + (aoff ^ ((i & 1) * 16)) + slot_of(S_V + k) + (i >> 1) * 8192, a[i]);
                mma16816(o0, a[0], pa.x, pa.y);
                mma16816(o1, a[1], pa.x, pa.y);
                mma16816(o2, a[2], pa.z, pa.w);
                mma16816(o3, a[3], pa.z, pa.w);
                if (S_V + k + NS < NSTAGE) {
                    __syncwarp();
                    if (lane == 0) mbar_arrive(done0 + (S_V + k) * 8, 1);
                }
                if (k == FFN_ST && warp < 7 && cta < NFFN) {
                    strip_partial(sb, SM_STRIP, smem, warp, lane);
                    bar_sync(BAR_FF, 224);
                    float ga = rbf(strip_sum(smem, lane));
                    ga *= (ga > 0.f ? 1.f : 0.f);
                    const float hv = ga * rbf(strip_sum(smem, 32 + lane));
                    const uint32_t w = pack_bf(hv, __shfl_xor_sync(0xffffffffu, hv, 2));
                    h0 = __shfl_sync(0xffffffffu, w, 4 * t + (g & 1));
                    h1 = __shfl_sync(0xffffffffu, w, 4 * t + 16 + (g & 1));
                }
                if (k == FFN_ST && warp == 7) {
                    const uint2* mlp = scr->ml + (hkv * 16 + g) * 4 + (j >> 3);
                    uint2 a, b;
                    int it = 0;
                    do {
                        a = ld_poll2(mlp); b = ld_poll2(mlp + 32);
                        if (++it > SPIN_LIMIT) __trap();
                    } while (warp_bad(bad2(a.x, a.y, tag) | bad2(b.x, b.y, tag)));
                    float m[2] = {__uint_as_float(a.x), __uint_as_float(b.x)};
                    float l[2] = {__uint_as_float(a.y), __uint_as_float(b.y)};
#pragma unroll
                    for (int bb = 0; bb < 2; bb++) {
                        float M = m[bb];
                        M = fmaxf(M, __shfl_xor_sync(0xffffffffu, M, 4));
                        M = fmaxf(M, __shfl_xor_sync(0xffffffffu, M, 8));
                        M = fmaxf(M, __shfl_xor_sync(0xffffffffu, M, 16));
                        const float e = ex2(m[bb] - M);
                        float L = e * l[bb];
                        L += __shfl_xor_sync(0xffffffffu, L, 4);
                        L += __shfl_xor_sync(0xffffffffu, L, 8);
                        L += __shfl_xor_sync(0xffffffffu, L, 16);
                        (bb ? h1 : h0) = __float_as_uint(__fdividef(e, L));
                    }
                }
                if (k == PRE_ST) {
                    st_pub2(dst, tag ^ 1, tag ^ 1);
                    if (warp < 7) st_pub4(odst, make_uint4(tag ^ 1, tag ^ 1, tag ^ 1, tag ^ 1));
                }
            }
            const float v0 = sel4(o0, t) + sel4(o2, t), v1 = sel4(o1, t) + sel4(o3, t);
            st_pub2(dst, tagf(v0, tag), tagf(v1, tag));
        }
        if (warp == 0) TL(10);
        if (warp < 7) {
            float c[4][4];
#pragma unroll
            for (int m = 0; m < 4; m++)
#pragma unroll
                for (int e = 0; e < 4; e++) c[m][e] = 0.f;
            const int r7 = ((lane & 7) >> 1) + 4 * (lane >> 4);
            const uint32_t aoff = sb + (r7 + 8 * (lane & 1)) * 896 + ((warp * 8 + ((lane >> 3) & 1)) ^ r7 ^ ((lane & 1) << 2)) * 16;
            uint32_t a[4][4];
            if (cta < NFFN) {
                mbar_wait(full0 + S_DN * 8);
#pragma unroll
                for (int m = 0; m < 4; m++) ldsm4t((aoff ^ (m * 32)) + slot_of(S_DN), a[m]);
#pragma unroll
                for (int m = 0; m < 4; m++) mma16816(c[m], a[m], h0, h1);
            }
            mbar_wait(full0 + S_WO * 8);
#pragma unroll
            for (int m = 0; m < 4; m++) ldsm4t((aoff ^ (m * 32)) + slot_of(S_WO), a[m]);
            bar_sync(BAR_OB, 256);
            const uint4 ob = *reinterpret_cast<const uint4*>(smem + SM_OB + (g & 1) * 64 + t * 16);
#pragma unroll
            for (int m = 0; m < 4; m++) mma16816(c[m], a[m], ob.x, ob.y);
            mbar_spin(full0 + (S_WO + 1) * 8);
            uint32_t a2[4][4];
#pragma unroll
            for (int m = 0; m < 4; m++) ldsm4t((aoff ^ (m * 32)) + slot_of(S_WO + 1), a2[m]);
#pragma unroll
            for (int m = 0; m < 4; m++) mma16816(c[m], a2[m], ob.z, ob.w);
            uint4 r;
            r.x = tagf(sel4(c[0], t), tag); r.y = tagf(sel4(c[1], t), tag);
            r.z = tagf(sel4(c[2], t), tag); r.w = tagf(sel4(c[3], t), tag);
            st_pub4(odst, r);
            if (warp == 0) TL(12);
        } else {
            const uint4* pp = scr->part + (size_t)cta * 128 + g * 8 + t;
            uint32_t* obp = reinterpret_cast<uint32_t*>(smem + SM_OB) + (lane >> 4) * 16 + (t + 4 * ((lane >> 3) & 1)) * 2 + ((lane >> 2) & 1);
            { const uint32_t te = TN_E2; while (time_ns() - t0 < te) {} }
            TL(2);
            uint4 v[4];
            poll_all<4>(v, pp, 4, 64, tag);
            TL(3);
            float r8[8], r4[4], r2[2];
            const bool h16 = lane & 16, h8 = lane & 8, h4 = lane & 4;
            {
                const float wk = __uint_as_float(h16 ? h1 : h0), ws = __uint_as_float(h16 ? h0 : h1);
                const uint32_t f0[8] = {v[0].x, v[0].y, v[0].z, v[0].w, v[1].x, v[1].y, v[1].z, v[1].w};
                const uint32_t f1[8] = {v[2].x, v[2].y, v[2].z, v[2].w, v[3].x, v[3].y, v[3].z, v[3].w};
#pragma unroll
                for (int e = 0; e < 8; e++) {
                    const float keep = __uint_as_float(h16 ? f1[e] : f0[e]), send = __uint_as_float(h16 ? f0[e] : f1[e]);
                    r8[e] = fmaf(keep, wk, __shfl_xor_sync(0xffffffffu, send * ws, 16));
                }
            }
#pragma unroll
            for (int e = 0; e < 4; e++) {
                const float keep = h8 ? r8[4 + e] : r8[e], send = h8 ? r8[e] : r8[4 + e];
                r4[e] = keep + __shfl_xor_sync(0xffffffffu, send, 8);
            }
#pragma unroll
            for (int e = 0; e < 2; e++) {
                const float keep = h4 ? r4[2 + e] : r4[e], send = h4 ? r4[e] : r4[2 + e];
                r2[e] = keep + __shfl_xor_sync(0xffffffffu, send, 4);
            }
            *obp = pack_bf(r2[0], r2[1]);
            bar_arrive(BAR_OB, 256);
            TL(14);
        }
    } else if (warp < 8 + NPW) {
        const int pt = tid - 256, pw = warp - 8;
        Prod p;
        p.t0 = time_ns();
        if (lane == 0) {
            const int w = __shfl_sync(1u, pw, 0);
#pragma unroll
            for (int i = 0; i < 10; i++) {
                if (w * 10 + i != B_X) mbar_init(full0 + (w * 10 + i) * 8, NPT);
                mbar_init(done0 + (w * 10 + i) * 8, 8);
            }
        }
        const size_t kvoff = ((size_t)(bat * 8 + hkv) * SK + (SK - WIN) + sp * 512) * DH * 2 + pt * 16;
        p.sb = sb;
        p.kvdst = (sb + pt * 16) ^ (pw * 16);
        p.sdst = sb + SM_STRIP + (pt >> 2) * 64 + ((pt & 3) ^ ((pt >> 3) & 3)) * 16;
#pragma unroll
        for (int i = 0; i < 7; i++) {
            const int id = i * NPT + pt, row = id / 56;
            p.rdst[i] = (id ^ (row & 7) ^ ((row >> 3) << 2)) * 16;
        }
        p.k = reinterpret_cast<const char*>(kc) + kvoff;
        p.v = reinterpret_cast<const char*>(vc) + kvoff;
        p.wo = reinterpret_cast<const char*>(wo) + (size_t)cta * 28672 + pt * 16;
        p.wd = reinterpret_cast<const char*>(wd) + (size_t)cta * 14336 + pt * 16;
        p.gu = ((pt & 2) ? wu : wg) + cta * 16 + (pt & 1) * 8 + (size_t)(pt >> 2) * FF;
        p.ffn = cta < NFFN;
        asm volatile("" :: "l"(p.gu), "l"(p.wd));
        __syncthreads();
        produce<0>(p);
        if (pw == 0) TL(1);
        asm volatile("cp.async.wait_all;" ::: "memory");
        if (cta % RSTEP == 0 && cta < NRED * RSTEP) {
            constexpr int NL = LPM;
            const int rid = cta / RSTEP;
            mbar_wait(full0 + B_X * 8);
            const uint32_t tag = (*reinterpret_cast<const uint32_t*>(smem + SM_X + 1792) + 1) & 1;
            const uint4* op = scr->outp + (size_t)rid * (NCTA * LPM) + pw * (NL * 32) + lane;
            const int sl = rid * LPM + lane % LPM;
            const int oidx = (sl & 1) * D_MODEL + (sl >> 5) * 64 + (lane >> 3) * 16 + ((sl >> 2) & 7) + (sl & 2) * 4;
            const float xv = __bfloat162float(reinterpret_cast<const __nv_bfloat16*>(smem + SM_X)[oidx]);
            float* red = reinterpret_cast<float*>(smem + SM_S) + lane;
            __nv_bfloat16* optr = out + oidx;
            uint4 v[NL];
            { const uint32_t te = TN_E3; while (time_ns() - p.t0 < te) {} }
            poll_all<NL>(v, op, 32, 64, tag);
            if (pw == 0) TL(4);
            float a[NL][4];
#pragma unroll
            for (int i = 0; i < NL; i++) {
                a[i][0] = __uint_as_float(v[i].x); a[i][1] = __uint_as_float(v[i].y);
                a[i][2] = __uint_as_float(v[i].z); a[i][3] = __uint_as_float(v[i].w);
            }
#pragma unroll
            for (int o = NL / 2; o > 0; o >>= 1)
#pragma unroll
                for (int i = 0; i < o; i++)
#pragma unroll
                    for (int e = 0; e < 4; e++) a[i][e] += a[i + o][e];
            const bool h16 = lane & 16, h8 = lane & 8;
            float r2[2];
#pragma unroll
            for (int e = 0; e < 2; e++)
                r2[e] = (h16 ? a[0][2 + e] : a[0][e]) + __shfl_xor_sync(0xffffffffu, h16 ? a[0][e] : a[0][2 + e], 16);
            float r = (h8 ? r2[1] : r2[0]) + __shfl_xor_sync(0xffffffffu, h8 ? r2[0] : r2[1], 8);
            if (LPM <= 4) r += __shfl_xor_sync(0xffffffffu, r, 4);
            if (LPM <= 2) r += __shfl_xor_sync(0xffffffffu, r, 2);
            if (pw != 0) {
                red[pw * 32] = r;
                bar_arrive(BAR_FIN, NPT);
            } else {
                bar_sync(BAR_FIN, NPT);
                r = (r + red[32]) + (red[64] + red[96]);
                if ((lane & 7) < LPM) *optr = __float2bfloat16_rn(xv + r);
                TL(5);
            }
        }
    }
}

}

extern "C" void kernel_launch(void* const* d_in, const int* in_sizes, int n_in, void* d_out, int out_size) {
    (void)in_sizes; (void)n_in; (void)out_size;
    static Scratch* scr = nullptr;
    if (!scr) {
        cudaFuncSetAttribute(fused_decode_kernel, cudaFuncAttributeMaxDynamicSharedMemorySize, SM_TOTAL);
        cudaGetSymbolAddress(reinterpret_cast<void**>(&scr), g_scratch);
    }
    typedef const __nv_bfloat16* P;
    fused_decode_kernel<<<NCTA, NTHREADS, SM_TOTAL>>>((P)d_in[3], (P)d_in[1], (P)d_in[0], scr, (P)d_in[2], (P)d_in[4],
                                                      (P)d_in[6], (P)d_in[7], (P)d_in[8], (__nv_bfloat16*)d_out);
}
```

```cpp
#include <cuda_runtime.h>
#include <cuda_bf16.h>
#include <stdint.h>

namespace {

#define PACE_DT 636
#define PACE_LEAD 350
#define LATE_T 22450
#define LATE_DT 400
#define Q_T 4000
#define E2_T 24100
#define E3_T 24930
#ifndef M_NOM0
#define M_NOM0 5390
#define M_NOM1 9320
#define M_NOM2 13760
#define M_NOM3 17960
#endif
#define NM 4
#define MEND 6
#define NSLOT 11

#define TN_E2 E2_T
#define TN_E3 E3_T
#define TN_A LATE_T
#define TN_B LATE_DT
#define EPB 16

constexpr int D_MODEL = 448;
constexpr int SK      = 32768;
constexpr int WIN     = 4096;
constexpr int DH      = 256;
constexpr int QCOLS   = 4096;
constexpr int FF      = 1792;
constexpr int NCTA    = 128;
constexpr int NFFN    = 112;
constexpr int NRED    = 56;
constexpr int NPT     = 128;
constexpr int NTHREADS = 512;

constexpr int NS     = NSLOT;
constexpr int SLOT   = 16384;
constexpr int XROW   = 912;
constexpr int S_K = 0, S_V = 16, NSTAGE = 32;
constexpr int S_GU   = NS;
constexpr int FFN_ST = 10;
constexpr int PRE_ST = 12;
constexpr int NBAR   = 36;
constexpr int B_X = NSTAGE;

constexpr int SM_RING  = 0;
constexpr int SM_STRIP = SM_RING + NS * SLOT;
constexpr int SM_S    = SM_STRIP + 448 * 64;
constexpr int SM_P    = SM_S + 2 * 520 * 4;
constexpr int SM_Q    = SM_P + 2 * 272 * 4;
constexpr int SM_XN   = SM_Q + 2 * 264 * 2;
constexpr int SM_X    = SM_XN + 2 * XROW;
constexpr int SM_RED  = SM_X + 1792 + 32;
constexpr int SM_STAT = SM_RED + 7 * 64 * 4;
constexpr int SM_OB   = SM_STAT + 2 * 8 * 2 * 4;
constexpr int SM_H    = SM_OB + 2 * 16 * 4;
constexpr int SM_T0   = SM_H + 2 * 8 * 4;
constexpr int SM_BAR  = SM_T0 + 16;
constexpr int SM_TOTAL = SM_BAR + 2 * NBAR * 8;
static_assert(SM_Q % 16 == 0 && SM_XN % 16 == 0 && SM_X % 16 == 0 && SM_OB % 16 == 0 && SM_P % 16 == 0 && SM_T0 % 16 == 0, "align");
static_assert(S_GU + 13 <= S_V + FFN_ST, "the gate/up strip lands with stage S_GU + 13");
static_assert(2 * NS >= 16, "K stage -> slot mapping");

constexpr int SPIN_LIMIT = 1 << 22;

struct Scratch {
    uint4    part[NCTA * 2 * 8 * 8];
    uint4    outp[NRED * NCTA * 4];
    uint4    q[8 * 2 * 128];
    uint2    ml[NCTA * 4];
    uint2    prog[4 * 32 * 4];
    unsigned epoch[NCTA * 8];
};
__device__ Scratch g_scratch;

#define TL(i)

__device__ __forceinline__ void mbar_init(uint32_t bar, uint32_t cnt) {
    asm volatile("mbarrier.init.shared::cta.b64 [%0], %1;" :: "r"(bar), "r"(cnt) : "memory");
}
__device__ __forceinline__ void mbar_arrive(uint32_t bar, uint32_t cnt) {
    asm volatile("mbarrier.arrive.shared::cta.b64 _, [%0], %1;" :: "r"(bar), "r"(cnt) : "memory");
}
__device__ __forceinline__ bool mbar_try(uint32_t bar) {
    uint32_t ok;
    asm volatile("{\n.reg .pred p;\nmbarrier.try_wait.parity.shared::cta.b64 p, [%1], 0;\nselp.u32 %0, 1, 0, p;\n}"
                 : "=r"(ok) : "r"(bar) : "memory");
    return ok;
}
__device__ __forceinline__ uint32_t time_ns() { uint32_t t; asm volatile("mov.u32 %0, %globaltimer_lo;" : "=r"(t)); return t; }
__device__ __forceinline__ void wait_until(uint32_t t0, uint32_t dt) { while (time_ns() - t0 < dt) {} }
__device__ __forceinline__ void mbar_wait(uint32_t bar) {
    asm volatile("{\n.reg .pred p;\nWAIT_LOOP:\nmbarrier.try_wait.parity.shared::cta.b64 p, [%0], 0;\n@!p bra WAIT_LOOP;\n}" :: "r"(bar) : "memory");
}
__device__ __forceinline__ void cp_async16_strip(uint32_t dst, const void* src) {
    asm volatile("cp.async.cg.shared.global.L2::128B [%0], [%1], 16;" :: "r"(dst), "l"(src) : "memory");
}
__device__ __forceinline__ void cp_async16_stream(uint32_t dst, const void* src) {
    asm volatile("{\n.reg .b64 pol;\ncreatepolicy.fractional.L2::evict_first.b64 pol, 1.0;\n"
                 "cp.async.cg.shared.global.L2::cache_hint [%0], [%1], 16, pol;\n}" :: "r"(dst), "l"(src) : "memory");
}
__device__ __forceinline__ void cp_async_arrive(uint32_t bar) {
    asm volatile("cp.async.mbarrier.arrive.noinc.shared::cta.b64 [%0];" :: "r"(bar) : "memory");
}
__device__ __forceinline__ void bar_sync(int id, int n)   { asm volatile("bar.sync %0, %1;" :: "r"(id), "r"(n) : "memory"); }
__device__ __forceinline__ void bar_arrive(int id, int n) { asm volatile("bar.arrive %0, %1;" :: "r"(id), "r"(n) : "memory"); }

__device__ __forceinline__ uint2 ld_poll2(const void* p) {
    uint2 v;
    asm volatile("ld.relaxed.gpu.global.v2.u32 {%0,%1}, [%2];" : "=r"(v.x), "=r"(v.y) : "l"(p) : "memory");
    return v;
}
__device__ __forceinline__ uint4 ld_poll4(const void* p) {
    uint4 v;
    asm volatile("ld.relaxed.gpu.global.v4.u32 {%0,%1,%2,%3}, [%4];" : "=r"(v.x), "=r"(v.y), "=r"(v.z), "=r"(v.w) : "l"(p) : "memory");
    return v;
}
__device__ __forceinline__ void st_pub4(void* p, uint4 v) {
    asm volatile("st.relaxed.gpu.global.v4.u32 [%0], {%1,%2,%3,%4};" :: "l"(p), "r"(v.x), "r"(v.y), "r"(v.z), "r"(v.w) : "memory");
}
__device__ __forceinline__ void st_pub2(void* p, uint32_t a, uint32_t b) {
    asm volatile("st.relaxed.gpu.global.v2.u32 [%0], {%1,%2};" :: "l"(p), "r"(a), "r"(b) : "memory");
}
__device__ __forceinline__ void st_pub1(void* p, uint32_t a) {
    asm volatile("st.relaxed.gpu.global.u32 [%0], %1;" :: "l"(p), "r"(a) : "memory");
}
__device__ __forceinline__ uint32_t tagf(float v, uint32_t tag) {
    uint32_t r;
    asm("lop3.b32 %0, %1, 0xfffffffe, %2, 0xEA;" : "=r"(r) : "r"(__float_as_uint(v)), "r"(tag));
    return r;
}
__device__ __forceinline__ uint32_t pin(uint32_t v) {
    uint32_t r;
    asm volatile("shfl.sync.bfly.b32 %0, %1, 0, 0x1f, 0xffffffff;" : "=r"(r) : "r"(v));
    return r;
}
template <class T>
__device__ __forceinline__ T* pin(T* p) {
    const uint64_t u = reinterpret_cast<uint64_t>(p);
    return reinterpret_cast<T*>(((uint64_t)pin((uint32_t)(u >> 32)) << 32) | pin((uint32_t)u));
}
__device__ __forceinline__ void sts32(uint32_t addr, uint32_t v) { asm volatile("st.shared.u32 [%0], %1;" :: "r"(addr), "r"(v) : "memory"); }
__device__ __forceinline__ float lds32(uint32_t addr) { float v; asm volatile("ld.shared.f32 %0, [%1];" : "=f"(v) : "r"(addr) : "memory"); return v; }
__device__ __forceinline__ uint4 lds128(uint32_t addr) {
    uint4 v;
    asm volatile("ld.shared.v4.u32 {%0,%1,%2,%3}, [%4];" : "=r"(v.x), "=r"(v.y), "=r"(v.z), "=r"(v.w) : "r"(addr) : "memory");
    return v;
}
__device__ __forceinline__ uint32_t bad2(uint32_t a, uint32_t b, uint32_t tag) {
    uint32_t r;
    asm("lop3.b32 %0, %1, %2, %3, 0x7E;" : "=r"(r) : "r"(a), "r"(b), "r"(tag));
    return r;
}
__device__ __forceinline__ uint32_t bad4(const uint4& v, uint32_t tag) { return bad2(v.x, v.y, tag) | bad2(v.z, v.w, tag); }
__device__ __forceinline__ bool warp_bad(uint32_t bad) { return __any_sync(0xffffffffu, bad & 1u); }

__device__ __forceinline__ void poll4(float (&f)[2][4], const uint4* p, uint32_t tag, const float (&w)[4]) {
    asm volatile("{\n"
                 ".reg .pred p0, p1, p2, p3, q;\n"
                 ".reg .b32 a, b, m, it, v<16>;\n"
                 "setp.eq.u32 p0, 0, 0;\nsetp.eq.u32 p1, 0, 0;\nsetp.eq.u32 p2, 0, 0;\nsetp.eq.u32 p3, 0, 0;\n"
                 "mov.u32 it, %14;\n"
                 "POLL_LOOP:\n"
                 "@p0 ld.relaxed.gpu.global.v4.u32 {v0,v1,v2,v3}, [%8];\n"
                 "@p1 ld.relaxed.gpu.global.v4.u32 {v4,v5,v6,v7}, [%8+512];\n"
                 "@p2 ld.relaxed.gpu.global.v4.u32 {v8,v9,v10,v11}, [%8+1024];\n"
                 "@p3 ld.relaxed.gpu.global.v4.u32 {v12,v13,v14,v15}, [%8+1536];\n"
                 "sub.u32 it, it, 1;\n"
                 "min.u32 m, it, 1;\n"
                 "lop3.b32 a, v0, v1, %9, 0x7E;\nlop3.b32 b, v2, v3, %9, 0x7E;\nlop3.b32 a, a, b, m, 0xA8;\nsetp.ne.u32 p0, a, 0;\n"
                 "lop3.b32 a, v4, v5, %9, 0x7E;\nlop3.b32 b, v6, v7, %9, 0x7E;\nlop3.b32 a, a, b, m, 0xA8;\nsetp.ne.u32 p1, a, 0;\n"
                 "lop3.b32 a, v8, v9, %9, 0x7E;\nlop3.b32 b, v10, v11, %9, 0x7E;\nlop3.b32 a, a, b, m, 0xA8;\nsetp.ne.u32 p2, a, 0;\n"
                 "lop3.b32 a, v12, v13, %9, 0x7E;\nlop3.b32 b, v14, v15, %9, 0x7E;\nlop3.b32 a, a, b, m, 0xA8;\nsetp.ne.u32 p3, a, 0;\n"
                 "or.pred q, p0, p1;\nor.pred q, q, p2;\nor.pred q, q, p3;\n"
                 "mul.f32 %0, v0, %10;\nmul.f32 %1, v1, %10;\nmul.f32 %2, v2, %10;\nmul.f32 %3, v3, %10;\n"
                 "mul.f32 %4, v8, %12;\nmul.f32 %5, v9, %12;\nmul.f32 %6, v10, %12;\nmul.f32 %7, v11, %12;\n"
                 "vote.sync.any.pred q, q, 0xffffffff;\n"
                 "fma.rn.f32 %0, v4, %11, %0;\nfma.rn.f32 %1, v5, %11, %1;\nfma.rn.f32 %2, v6, %11, %2;\nfma.rn.f32 %3, v7, %11, %3;\n"
                 "fma.rn.f32 %4, v12, %13, %4;\nfma.rn.f32 %5, v13, %13, %5;\nfma.rn.f32 %6, v14, %13, %6;\nfma.rn.f32 %7, v15, %13, %7;\n"
                 "@q bra POLL_LOOP;\n"
                 "}"
                 : "=&f"(f[0][0]), "=&f"(f[0][1]), "=&f"(f[0][2]), "=&f"(f[0][3]), "=&f"(f[1][0]), "=&f"(f[1][1]), "=&f"(f[1][2]), "=&f"(f[1][3])
                 : "l"(p), "r"(tag), "f"(w[0]), "f"(w[1]), "f"(w[2]), "f"(w[3]), "n"(SPIN_LIMIT) : "memory");
}

__device__ __forceinline__ void ldsm4(uint32_t addr, uint32_t (&a)[4]) {
    asm volatile("ldmatrix.sync.aligned.m8n8.x4.shared.b16 {%0,%1,%2,%3}, [%4];" : "=r"(a[0]), "=r"(a[1]), "=r"(a[2]), "=r"(a[3]) : "r"(addr) : "memory");
}
__device__ __forceinline__ void ldsm4t(uint32_t addr, uint32_t (&a)[4]) {
    asm volatile("ldmatrix.sync.aligned.m8n8.x4.trans.shared.b16 {%0,%1,%2,%3}, [%4];" : "=r"(a[0]), "=r"(a[1]), "=r"(a[2]), "=r"(a[3]) : "r"(addr) : "memory");
}
__device__ __forceinline__ void mma16816(float (&c)[4], const uint32_t (&a)[4], uint32_t b0, uint32_t b1) {
    asm volatile("mma.sync.aligned.m16n8k16.row.col.f32.bf16.bf16.f32 {%0,%1,%2,%3}, {%4,%5,%6,%7}, {%8,%9}, {%0,%1,%2,%3};"
                 : "+f"(c[0]), "+f"(c[1]), "+f"(c[2]), "+f"(c[3]) : "r"(a[0]), "r"(a[1]), "r"(a[2]), "r"(a[3]), "r"(b0), "r"(b1));
}
__device__ __forceinline__ float bf_lo(uint32_t u) { return __uint_as_float(u << 16); }
__device__ __forceinline__ float bf_hi(uint32_t u) { return __uint_as_float(u & 0xffff0000u); }
__device__ __forceinline__ float rbf(float v) { return __bfloat162float(__float2bfloat16_rn(v)); }
__device__ __forceinline__ uint32_t pack_bf(float lo, float hi) {
    uint32_t r;
    asm("cvt.rn.bf16x2.f32 %0, %1, %2;" : "=r"(r) : "f"(hi), "f"(lo));
    return r;
}
__device__ __forceinline__ float sel4(const float (&c)[4], int t) {
    float a = (t & 1) ? c[1] : c[0];
    float b = (t & 1) ? c[3] : c[2];
    return (t & 2) ? b : a;
}
__device__ __forceinline__ float ex2(float x) { float y; asm("ex2.approx.ftz.f32 %0, %1;" : "=f"(y) : "f"(x)); return y; }
__device__ __forceinline__ float sqrt_approx(float x) { float y; asm("sqrt.approx.f32 %0, %1;" : "=f"(y) : "f"(x)); return y; }

__host__ __device__ constexpr uint32_t slot_of(int s) { return SM_RING + (s % NS) * SLOT; }

__device__ __forceinline__ void layernorm(unsigned char* smem, int lane) {
    uint32_t xs[2][7];
#pragma unroll
    for (int b = 0; b < 2; b++)
#pragma unroll
        for (int i = 0; i < 7; i++) xs[b][i] = reinterpret_cast<const uint32_t*>(smem + SM_X)[b * (D_MODEL / 2) + i * 32 + lane];
#pragma unroll
    for (int b = 0; b < 2; b++) {
        float sum = 0.f;
#pragma unroll
        for (int i = 0; i < 7; i++) sum += bf_lo(xs[b][i]) + bf_hi(xs[b][i]);
#pragma unroll
        for (int o = 16; o > 0; o >>= 1) sum += __shfl_xor_sync(0xffffffffu, sum, o);
        const float mean = sum * (1.0f / D_MODEL);
        float sq = 0.f;
#pragma unroll
        for (int i = 0; i < 7; i++) {
            const float d0 = bf_lo(xs[b][i]) - mean, d1 = bf_hi(xs[b][i]) - mean;
            sq = fmaf(d0, d0, fmaf(d1, d1, sq));
        }
#pragma unroll
        for (int o = 16; o > 0; o >>= 1) sq += __shfl_xor_sync(0xffffffffu, sq, o);
        const float mb = rbf(mean);
        const float sd = rbf(sqrt_approx(rbf(rbf(sq * (1.0f / D_MODEL)) + 1e-5f)));
#pragma unroll
        for (int i = 0; i < 7; i++)
            reinterpret_cast<uint32_t*>(smem + SM_XN + b * XROW)[i * 32 + lane] =
                pack_bf(__fdividef(rbf(bf_lo(xs[b][i]) - mb), sd), __fdividef(rbf(bf_hi(xs[b][i]) - mb), sd));
    }
}

__device__ __forceinline__ void strip_partial(uint32_t sb, uint32_t strip, unsigned char* smem, int warp, int lane) {
    float c[2][2][4];
#pragma unroll
    for (int n = 0; n < 2; n++)
#pragma unroll
        for (int e = 0; e < 4; e++) c[n][0][e] = c[n][1][e] = 0.f;
    const uint32_t ba = sb + SM_XN + (lane & 1) * XROW + (lane >> 3) * 16 + warp * 128;
    const uint32_t aa = sb + strip + (warp * 64 + (lane & 7) + (lane >> 4) * 8) * 64 + (((lane >> 3) & 1) ^ ((lane & 7) >> 1)) * 16;
#pragma unroll
    for (int k2 = 0; k2 < 2; k2++) {
        uint32_t b[4];
        ldsm4(ba + k2 * 64, b);
#pragma unroll
        for (int n = 0; n < 2; n++) {
            uint32_t a0[4], a1[4];
            ldsm4t((aa ^ (n * 32)) + k2 * 2048, a0);
            ldsm4t((aa ^ (n * 32)) + k2 * 2048 + 1024, a1);
            mma16816(c[n][0], a0, b[0], b[1]);
            mma16816(c[n][1], a1, b[2], b[3]);
        }
    }
    float* red = reinterpret_cast<float*>(smem + SM_RED) + warp * 64 + lane;
#pragma unroll
    for (int n = 0; n < 2; n++) red[n * 32] = sel4(c[n][0], lane & 3) + sel4(c[n][1], lane & 3);
}
__device__ __forceinline__ float strip_sum(const unsigned char* smem, int idx) {
    const float* red = reinterpret_cast<const float*>(smem + SM_RED) + idx;
    return ((red[0] + red[64]) + (red[128] + red[192])) + ((red[256] + red[320]) + red[384]);
}

__device__ __forceinline__ uint32_t time_base(uint32_t sb, int i) {
    uint32_t t;
    asm volatile("ld.volatile.shared.u32 %0, [%1];" : "=r"(t) : "r"(sb + SM_T0 + 4 * i) : "memory");
    return t;
}
__device__ __forceinline__ void wait_clock(uint32_t sb, int i, uint32_t dt) { while (time_ns() - time_base(sb, i) < dt) {} }

struct Prod {
    uint32_t sb, kvdst, sdst;
    const char *k, *v;
    const __nv_bfloat16* gu;
    bool ffn;
};
__host__ __device__ constexpr int bytes_before(int s) { return 28672 + s * 16384 + (s <= S_GU ? 0 : s < S_GU + 14 ? s - S_GU : 14) * 1792; }
__host__ __device__ constexpr int issue_time(int s) { return (int)((long long)bytes_before(s) * PACE_DT / 16384) - PACE_LEAD; }

template <int S>
__device__ __forceinline__ void produce(Prod& p) {
    if constexpr (S < NSTAGE) {
        if constexpr (S >= NS) mbar_wait(p.sb + SM_BAR + (NBAR + S - NS) * 8);
        wait_clock(p.sb, 0, issue_time(S));
        const char* src = (S < S_V ? p.k : p.v) + (S & 15) * (8 * SLOT);
#pragma unroll
        for (int i = 0; i < 8; i++) cp_async16_stream((p.kvdst ^ ((i & 1) * 64)) + slot_of(S) + i * 2048, src + i * 2048);
        if constexpr (S >= S_GU && S < S_GU + 14) {
            if (p.ffn) cp_async16_strip(p.sdst + (S - S_GU) * 2048, p.gu + (size_t)(S - S_GU) * 32 * FF);
        }
        cp_async_arrive(p.sb + SM_BAR + S * 8);
        produce<S + 1>(p);
    }
}

__device__ __forceinline__ void fetch16(uint32_t dst, const char* src) {
#pragma unroll
    for (int i = 0; i < 4; i++)
        asm volatile("cp.async.cg.shared.global [%0], [%1], 16;" :: "r"((dst ^ (((i & 1) ^ (i >> 1)) * 64)) + i * 512), "l"(src + i * (4 * 896)) : "memory");
}
template <int PENDING, int OFF>
__device__ __forceinline__ void frag16(uint32_t (&a)[4][4], uint32_t addr) {
    asm volatile("cp.async.wait_group %0;" :: "n"(PENDING) : "memory");
    __syncwarp();
#pragma unroll
    for (int m = 0; m < 4; m++) ldsm4t((addr ^ (m * 32)) + OFF, a[m]);
}

__device__ __forceinline__ void load_x(uint32_t sb, const void* x, const void* epoch) {
    const uint32_t full0 = sb + SM_BAR;
    mbar_init(full0 + B_X * 8, 1);
    asm volatile("fence.mbarrier_init.release.cluster;" ::: "memory");
    asm volatile("mbarrier.arrive.expect_tx.shared::cta.b64 _, [%0], %1;" :: "r"(full0 + B_X * 8), "r"(1792 + EPB) : "memory");
    asm volatile("cp.async.bulk.shared::cluster.global.mbarrier::complete_tx::bytes [%0], [%1], %2, [%3];"
                 :: "r"(sb + SM_X), "l"(x), "r"(1792), "r"(full0 + B_X * 8) : "memory");
    asm volatile("cp.async.bulk.shared::cluster.global.mbarrier::complete_tx::bytes [%0], [%1], %2, [%3];"
                 :: "r"(sb + SM_X + 1792), "l"(epoch), "r"(EPB), "r"(full0 + B_X * 8) : "memory");
}

enum { BAR_OB = 1, BAR_CONS = 2, BAR_LN = 3, BAR_FF = 4, BAR_FIN = 5, BAR_H = 6 };

__global__ void __launch_bounds__(NTHREADS, 1)
fused_decode_kernel(const __nv_bfloat16* __restrict__ wq, const __nv_bfloat16* __restrict__ kc, const __nv_bfloat16* __restrict__ x,
                    Scratch* __restrict__ scr, const __nv_bfloat16* __restrict__ vc, const __nv_bfloat16* __restrict__ wo,
                    const __nv_bfloat16* __restrict__ wg, const __nv_bfloat16* __restrict__ wu, const __nv_bfloat16* __restrict__ wd,
                    __nv_bfloat16* __restrict__ out) {
    extern __shared__ __align__(128) unsigned char smem[];
    const uint32_t sb = (uint32_t)__cvta_generic_to_shared(smem);
    const int tid = threadIdx.x, lane = tid & 31;
    const int cta = blockIdx.x;
    const uint32_t full0 = sb + SM_BAR, done0 = full0 + NBAR * 8;
    const uint32_t t0 = time_ns();
    if (tid < 224) {
        const int row = (tid >> 5) * 64 + (lane >> 2);
        const char* src = reinterpret_cast<const char*>(wq) + (uint32_t)(row * (QCOLS * 2) + cta * 64 + (lane & 3) * 16);
        const uint32_t dst = sb + SM_STRIP + row * 64 + ((lane & 3) ^ (lane >> 3)) * 16;
#pragma unroll
        for (int i = 0; i < 8; i++) cp_async16_strip(dst + i * 512, src + i * (8 * QCOLS * 2));
    }
    const int warp = __shfl_sync(0xffffffffu, tid >> 5, 0);
    const int hkv = cta >> 4, j = cta & 15, bat = j >> 3, sp = j & 7;
    const int g = lane >> 2, t = lane & 3;

    if (warp < 8) {
        if (warp == 0) TL(0);
        if (tid == 224) load_x(sb, x, &scr->epoch[cta * 8]);
        __syncthreads();
        mbar_wait(full0 + B_X * 8);
        const uint32_t epoch = *reinterpret_cast<const uint32_t*>(smem + SM_X + 1792);
        const uint32_t tag = pin((epoch + 1) & 1);
        uint32_t* qdst = reinterpret_cast<uint32_t*>(scr->q) + (hkv * 2 + (t & 1)) * 512 + j * 32 + warp * 16 + g + 8 * (t >> 1);
        if (warp == 7) {
            layernorm(smem, lane);
            bar_arrive(BAR_LN, 256);
            TL(13);
        } else {
            asm volatile("cp.async.wait_all;" ::: "memory");
            bar_sync(BAR_LN, 256);
            strip_partial(sb, SM_STRIP, smem, warp, lane);
        }
        bar_sync(BAR_CONS, 256);
        if (warp < 2) {
            st_pub1(qdst, (pack_bf(0.f, strip_sum(smem, tid)) & 0xffff0000u) | tag);
            if (warp == 0) TL(6);
        } else if (warp >= 4) {
            const int i = tid - 128;
            const uint4* qp = scr->q + (hkv * 2 + bat) * 128 + i;
            wait_until(t0, Q_T);
            uint4 v;
            int it = 0;
            do {
                v = ld_poll4(qp);
                if (++it > SPIN_LIMIT) __trap();
            } while (warp_bad(bad4(v, tag)));
            *reinterpret_cast<uint2*>(smem + SM_Q + (i >> 6) * 528 + (i & 63) * 8) =
                make_uint2(__byte_perm(v.x, v.y, 0x7632), __byte_perm(v.z, v.w, 0x7632));
        }
        bar_sync(BAR_CONS, 256);
        if (tid == 96) scr->epoch[cta * 8] = epoch + 1;
        if (warp == 0) TL(7);
        {
            uint32_t qf[8][4];
#pragma unroll
            for (int k2 = 0; k2 < 8; k2++) ldsm4(sb + SM_Q + (lane & 1) * 528 + k2 * 64 + (lane >> 3) * 16, qf[k2]);
            const int mt = warp & 1;
            const uint32_t aoff = (16 * mt + (lane & 15)) * 512 + ((lane >> 4) ^ (lane & 7)) * 16;
            float* sc = reinterpret_cast<float*>(smem + SM_S) + (t & 1) * 520 + (g >> 1) * 8 + (2 * mt + (t >> 1)) * 2 + (g & 1);
#pragma unroll 1
            for (int k = warp >> 1; k < 16; k += 4) {
                const int s = S_K + k;
                mbar_wait(full0 + s * 8);
                const uint32_t base = sb + SM_RING + (s >= NS ? s - NS : s) * SLOT + aoff;
                float c0[4] = {0.f, 0.f, 0.f, 0.f}, c1[4] = {0.f, 0.f, 0.f, 0.f};
#pragma unroll
                for (int k2 = 0; k2 < 8; k2++) {
                    uint32_t a0[4], a1[4];
                    ldsm4((base ^ ((k2 & 1) * 64)) + (k2 >> 1) * 128, a0);
                    ldsm4((base ^ ((k2 & 1) * 64 + 32)) + (k2 >> 1) * 128, a1);
                    mma16816(c0, a0, qf[k2][0], qf[k2][1]);
                    mma16816(c1, a1, qf[k2][2], qf[k2][3]);
                }
                __syncwarp();
                if (lane == 0) mbar_arrive(done0 + s * 8, 4);
                sc[k * 32] = rbf(sel4(c0, t) + sel4(c1, t));
            }
        }
        bar_sync(BAR_CONS, 256);
        if (warp == 0) TL(8);
        {
            constexpr float C = 0.0625f * 1.4426950408889634f;
            const float* sc = reinterpret_cast<const float*>(smem + SM_S);
            float* stat = reinterpret_cast<float*>(smem + SM_STAT);
            const float2 s0 = *reinterpret_cast<const float2*>(sc + 2 * tid);
            const float2 s1 = *reinterpret_cast<const float2*>(sc + 520 + 2 * tid);
            float m0 = fmaxf(s0.x, s0.y), m1 = fmaxf(s1.x, s1.y);
#pragma unroll
            for (int o = 16; o > 0; o >>= 1) {
                m0 = fmaxf(m0, __shfl_xor_sync(0xffffffffu, m0, o));
                m1 = fmaxf(m1, __shfl_xor_sync(0xffffffffu, m1, o));
            }
            if (lane == 0) *reinterpret_cast<float2*>(stat + warp * 2) = make_float2(m0, m1);
            bar_sync(BAR_CONS, 256);
#pragma unroll
            for (int w = 0; w < 8; w++) {
                const float2 mm = *reinterpret_cast<const float2*>(stat + w * 2);
                m0 = fmaxf(m0, mm.x); m1 = fmaxf(m1, mm.y);
            }
            const float p00 = ex2((s0.x - m0) * C), p01 = ex2((s0.y - m0) * C);
            const float p10 = ex2((s1.x - m1) * C), p11 = ex2((s1.y - m1) * C);
            uint32_t* ps = reinterpret_cast<uint32_t*>(smem + SM_P);
            ps[tid] = pack_bf(p00, p01);
            ps[272 + tid] = pack_bf(p10, p11);
            float l0 = p00 + p01, l1 = p10 + p11;
#pragma unroll
            for (int o = 16; o > 0; o >>= 1) {
                l0 += __shfl_xor_sync(0xffffffffu, l0, o);
                l1 += __shfl_xor_sync(0xffffffffu, l1, o);
            }
            if (lane == 0) *reinterpret_cast<float2*>(stat + 16 + warp * 2) = make_float2(l0, l1);
            bar_sync(BAR_CONS, 256);
            if (tid < 4) {
                float l = 0.f;
#pragma unroll
                for (int w = 0; w < 8; w++) l += stat[16 + w * 2 + (tid & 1)];
                st_pub2(scr->ml + cta * 4 + tid, tagf(((tid & 1) ? m1 : m0) * C, tag), tagf(l, tag));
            }
        }
        if (warp == 0) TL(9);
        float wgt[2] = {0.f, 0.f};
        {
            float o0[4] = {0.f, 0.f, 0.f, 0.f}, o1[4] = {0.f, 0.f, 0.f, 0.f};
            float o2[4] = {0.f, 0.f, 0.f, 0.f}, o3[4] = {0.f, 0.f, 0.f, 0.f};
            const uint32_t aoff = ((lane & 7) + (lane >> 4) * 8) * 512 + ((warp * 4 + ((lane >> 3) & 1) * 2) ^ (lane & 7)) * 16;
            const uint4* ps = reinterpret_cast<const uint4*>(smem + SM_P + (g & 1) * 272 * 4) + t;
            uint32_t* dst = reinterpret_cast<uint32_t*>(scr->part) + ((size_t)(hkv * 16 + (t & 1) * 8 + warp) * 16 + j) * 32 +
                            (4 * (g & 3) + (t & 2) + (g >> 2)) * 2;
#pragma unroll
            for (int k = 0; k < 16; k++) {
                const uint4 pa = ps[k * 4];
                mbar_wait(full0 + (S_V + k) * 8);
                uint32_t a[4][4];
#pragma unroll
                for (int i = 0; i < 4; i++) ldsm4t(sb + (aoff ^ ((i & 1) * 16)) + slot_of(S_V + k) + (i >> 1) * 8192, a[i]);
                mma16816(o0, a[0], pa.x, pa.y);
                mma16816(o1, a[1], pa.x, pa.y);
                mma16816(o2, a[2], pa.z, pa.w);
                mma16816(o3, a[3], pa.z, pa.w);
                if (S_V + k + NS < NSTAGE + 3) {
                    __syncwarp();
                    if (lane == 0) mbar_arrive(done0 + (S_V + k) * 8, 1);
                }
                if (k == FFN_ST && warp < 7) {
                    strip_partial(sb, SM_STRIP, smem, warp, lane);
                    bar_arrive(BAR_FF, 256);
                }
                if (k == FFN_ST && warp == 7) {
                    const uint2* mlp = scr->ml + (hkv * 16 + g) * 4 + (j >> 3);
                    uint2 a, b;
                    int it = 0;
                    do {
                        a = ld_poll2(mlp); b = ld_poll2(mlp + 32);
                        if (++it > SPIN_LIMIT) __trap();
                    } while (warp_bad(bad2(a.x, a.y, tag) | bad2(b.x, b.y, tag)));
                    float m[2] = {__uint_as_float(a.x), __uint_as_float(b.x)};
                    float l[2] = {__uint_as_float(a.y), __uint_as_float(b.y)};
#pragma unroll
                    for (int bb = 0; bb < 2; bb++) {
                        float M = m[bb];
                        M = fmaxf(M, __shfl_xor_sync(0xffffffffu, M, 4));
                        M = fmaxf(M, __shfl_xor_sync(0xffffffffu, M, 8));
                        M = fmaxf(M, __shfl_xor_sync(0xffffffffu, M, 16));
                        const float e = ex2(m[bb] - M);
                        float L = e * l[bb];
                        L += __shfl_xor_sync(0xffffffffu, L, 4);
                        L += __shfl_xor_sync(0xffffffffu, L, 8);
                        L += __shfl_xor_sync(0xffffffffu, L, 16);
                        wgt[bb] = __fdividef(e, L);
                    }
                    bar_sync(BAR_FF, 256);
                    float ga = rbf(strip_sum(smem, lane));
                    ga *= (ga > 0.f ? 1.f : 0.f);
                    const float hv = ga * rbf(strip_sum(smem, 32 + lane));
                    const uint32_t w = pack_bf(hv, __shfl_xor_sync(0xffffffffu, hv, 2));
                    if (!(t & 2)) reinterpret_cast<uint32_t*>(smem + SM_H)[(t & 1) * 8 + (g & 3) * 2 + (g >> 2)] = w;
                    bar_arrive(BAR_H, 256);
                }
                if (k == PRE_ST) st_pub2(dst, tag ^ 1, tag ^ 1);
            }
            const float v0 = sel4(o0, t) + sel4(o2, t), v1 = sel4(o1, t) + sel4(o3, t);
            st_pub2(dst, tagf(v0, tag), tagf(v1, tag));
        }
        if (warp == 0) TL(10);
        if (warp == 7) {
            const uint4* pp = pin(scr->part + (size_t)cta * 128 + lane);
            const uint32_t obaddr = pin(sb + SM_OB + (lane >> 4) * 64 + (lane & 7) * 8 + ((lane >> 3) & 1) * 4), ll = pin(lane);
            float w[4];
#pragma unroll
            for (int i = 0; i < 4; i++) w[i] = __shfl_sync(0xffffffffu, wgt[i >> 1], ((i & 1) * 4 + (lane >> 3)) * 4);
            wait_until(time_base(sb, 2), TN_E2);
            TL(2);
            float f[2][4];
            poll4(f, pp, tag, w);
            TL(3);
            const bool h16 = ll & 16, h8 = ll & 8;
            float r4[4], r2[2];
#pragma unroll
            for (int e = 0; e < 4; e++) r4[e] = (h16 ? f[1][e] : f[0][e]) + __shfl_xor_sync(0xffffffffu, h16 ? f[0][e] : f[1][e], 16);
#pragma unroll
            for (int e = 0; e < 2; e++) r2[e] = (h8 ? r4[2 + e] : r4[e]) + __shfl_xor_sync(0xffffffffu, h8 ? r4[e] : r4[2 + e], 8);
            sts32(obaddr, pack_bf(r2[0], r2[1]));
            bar_arrive(BAR_OB, 256);
            TL(14);
        } else if (warp < 4 && (cta & 1) == 0 && cta < 2 * NRED) {
            const uint4* op = pin(scr->outp + (size_t)(cta >> 1) * (NCTA * 4) + warp * 128 + lane);
            const int oidx = (t & 1) * D_MODEL + hkv * 64 + (lane >> 3) * 16 + (j >> 1) + (t >> 1) * 8;
            const float xv = __bfloat162float(reinterpret_cast<const __nv_bfloat16*>(smem + SM_X)[oidx]);
            __nv_bfloat16* optr = pin(out + oidx);
            const uint32_t red = pin(sb + SM_S + tid * 4), ll = pin(lane);
            const float one[4] = {1.f, 1.f, 1.f, 1.f};
            float f[2][4], a[4];
            wait_until(time_base(sb, 3), TN_E3);
            poll4(f, op, tag, one);
            if (warp == 0) TL(4);
#pragma unroll
            for (int e = 0; e < 4; e++) a[e] = f[0][e] + f[1][e];
            const bool h16 = ll & 16, h8 = ll & 8;
            float r2[2];
#pragma unroll
            for (int e = 0; e < 2; e++) r2[e] = (h16 ? a[2 + e] : a[e]) + __shfl_xor_sync(0xffffffffu, h16 ? a[e] : a[2 + e], 16);
            float r = (h8 ? r2[1] : r2[0]) + __shfl_xor_sync(0xffffffffu, h8 ? r2[0] : r2[1], 8);
            r += __shfl_xor_sync(0xffffffffu, r, 4);
            if (warp != 0) {
                sts32(red, __float_as_uint(r));
                bar_arrive(BAR_FIN, 128);
            } else {
                bar_sync(BAR_FIN, 128);
                r = ((xv + r) + lds32(red + 128)) + (lds32(red + 256) + lds32(red + 384));
                asm volatile("st.global.u16 [%0], %1;" :: "l"(optr), "h"(__bfloat16_as_ushort(__float2bfloat16_rn(r))) : "memory");
                TL(5);
            }
        }
    } else if (warp < 15) {
        const int pt = tid - 256, pw = warp - 8;
        const char* pdn = reinterpret_cast<const char*>(wd) + (size_t)cta * 14336 + (lane >> 3) * 896 + pw * 128 + (lane & 7) * 16;
        const char* pwo = reinterpret_cast<const char*>(wo) + (size_t)cta * 28672 + (lane >> 3) * 896 + pw * 128 + (lane & 7) * 16;
        if (pw < 4) {
            if (lane == 0) {
                const int w = pw;
#pragma unroll
                for (int i = 0; i < 9; i++) {
                    if (w * 9 + i != B_X) mbar_init(full0 + (w * 9 + i) * 8, NPT);
                    mbar_init(done0 + (w * 9 + i) * 8, 8);
                }
            }
            Prod p;
            const size_t kvoff = ((size_t)(bat * 8 + hkv) * SK + (SK - WIN)) * DH * 2 + sp * SLOT + pt * 16;
            p.sb = sb;
            p.kvdst = (sb + pt * 16) ^ (pw * 16);
            p.sdst = sb + SM_STRIP + (pt >> 2) * 64 + ((pt & 3) ^ ((pt >> 3) & 3)) * 16;
            p.k = reinterpret_cast<const char*>(kc) + kvoff;
            p.v = reinterpret_cast<const char*>(vc) + kvoff;
            p.gu = ((pt & 2) ? wu : wg) + cta * 16 + (pt & 1) * 8 + (size_t)(pt >> 2) * FF;
            p.ffn = cta < NFFN;
            __syncthreads();
            produce<0>(p);
        } else {
            __syncthreads();
        }
        mbar_wait(full0 + B_X * 8);
        const uint32_t tag = pin((*reinterpret_cast<const uint32_t*>(smem + SM_X + 1792) + 1) & 1);
        if (pw == 4 && (cta & 3) == 0) {
#pragma unroll 1
            for (int i = 0; i < 4; i++) {
                uint32_t sum = 0;
#pragma unroll
                for (int k = 0; k < NM; k++) {
                    mbar_wait(full0 + (MEND - NM + 1 + k + 6 * i) * 8);
                    sum += time_ns() - t0;
                }
                if (lane < 4) st_pub2(&scr->prog[i * 128 + cta + lane], ((t0 + sum / NM) & ~1u) | tag, (t0 & ~1u) | tag);
            }
        }
        mbar_wait(done0 + (NSTAGE + 2 - NS) * 8);
        bar_sync(BAR_H, 256);
        const uint2 h = *reinterpret_cast<const uint2*>(smem + SM_H + (g & 1) * 32 + t * 8);
        const uint32_t ta = TN_A, td = TN_B;
        uint4* odst = scr->outp + ((size_t)(pt >> 2) * NCTA + cta) * 4 + t;
        st_pub4(odst, make_uint4(tag ^ 1, tag ^ 1, tag ^ 1, tag ^ 1));
        const uint32_t fdst = (sb + pw * 2048 + lane * 16) ^ ((lane >> 3) * 16);
        wait_clock(sb, 1, ta);
        if (cta < NFFN) fetch16(fdst + slot_of(NSTAGE), pdn);
        asm volatile("cp.async.commit_group;" ::: "memory");
        wait_clock(sb, 1, ta + td);
        fetch16(fdst + slot_of(NSTAGE + 1), pwo);
        asm volatile("cp.async.commit_group;" ::: "memory");
        wait_clock(sb, 1, ta + 2 * td);
        fetch16(fdst + slot_of(NSTAGE + 2), pwo + 14336);
        asm volatile("cp.async.commit_group;" ::: "memory");
        if (pw == 0) TL(1);
        float c[4][4];
#pragma unroll
        for (int m = 0; m < 4; m++)
#pragma unroll
            for (int e = 0; e < 4; e++) c[m][e] = 0.f;
        const int r7 = ((lane & 7) >> 1) + 4 * (lane >> 4);
        const uint32_t aoff = sb + pw * 2048 + (r7 + 8 * (lane & 1)) * 128 + (((lane >> 3) & 1) ^ r7 ^ ((lane & 1) << 2)) * 16;
        const uint32_t obaddr = pin(sb + SM_OB + (g & 1) * 64 + t * 16), tt = pin(t);
        uint32_t a0[4][4], a1[4][4];
        frag16<2, slot_of(NSTAGE)>(a0, aoff);
        if (cta < NFFN) {
#pragma unroll
            for (int m = 0; m < 4; m++) mma16816(c[m], a0[m], h.x, h.y);
        }
        frag16<1, slot_of(NSTAGE + 1)>(a1, aoff);
        bar_sync(BAR_OB, 256);
        const uint4 ob = lds128(obaddr);
#pragma unroll
        for (int m = 0; m < 4; m++) mma16816(c[m], a1[m], ob.x, ob.y);
        frag16<0, slot_of(NSTAGE + 2)>(a0, aoff);
#pragma unroll
        for (int m = 0; m < 4; m++) mma16816(c[m], a0[m], ob.z, ob.w);
        uint4 r;
        r.x = tagf(sel4(c[0], tt), tag); r.y = tagf(sel4(c[1], tt), tag);
        r.z = tagf(sel4(c[2], tt), tag); r.w = tagf(sel4(c[3], tt), tag);
        st_pub4(odst, r);
        if (pw == 0) TL(12);
    } else if (warp == 15) {
        if (lane < 4) reinterpret_cast<uint32_t*>(smem + SM_T0)[lane] = t0;
        __syncthreads();
        mbar_wait(full0 + B_X * 8);
        const uint32_t tag = (*reinterpret_cast<const uint32_t*>(smem + SM_X + 1792) + 1) & 1;
#pragma unroll 1
        for (int i = 0; i < 4; i++) {
            mbar_wait(full0 + (MEND + 2 + 6 * i) * 8);
            uint2 v;
            int it = 0;
            do {
                v = ld_poll2(&scr->prog[i * 128 + lane * 4]);
                if (++it > SPIN_LIMIT) __trap();
            } while (warp_bad(bad2(v.x, v.y, tag)));
            const int nom = i == 0 ? M_NOM0 : i == 1 ? M_NOM1 : i == 2 ? M_NOM2 : M_NOM3;
            int base = (__reduce_add_sync(0xffffffffu, min(max((int)(v.x - t0), 0), 1 << 20)) >> 5) - nom;
            const int start = __reduce_add_sync(0xffffffffu, min(max((int)(v.y - t0), -(1 << 20)), 1 << 20)) >> 5;
            const int ahead = (lane == 0 ? nom : lane == 1 ? LATE_T : lane == 2 ? E2_T : E3_T - 150) - nom;
            const float rate = fminf(fmaxf(__fdividef((float)(base - start), (float)(nom - 500)), -0.01f), 0.045f);
            if (lane < 4) sts32(sb + SM_T0 + 4 * lane, t0 + base + (int)(rate * (float)ahead));
        }
        TL(15);
    }
}

}

extern "C" void kernel_launch(void* const* d_in, const int* in_sizes, int n_in, void* d_out, int out_size) {
    (void)in_sizes; (void)n_in; (void)out_size;
    static Scratch* scr = nullptr;
    if (!scr) {
        cudaFuncSetAttribute(fused_decode_kernel, cudaFuncAttributeMaxDynamicSharedMemorySize, SM_TOTAL);
        cudaGetSymbolAddress(reinterpret_cast<void**>(&scr), g_scratch);
    }
    typedef const __nv_bfloat16* P;
#define NGRID NCTA
    fused_decode_kernel<<<NGRID, NTHREADS, SM_TOTAL>>>((P)d_in[3], (P)d_in[1], (P)d_in[0], scr, (P)d_in[2], (P)d_in[4],
                                                      (P)d_in[6], (P)d_in[7], (P)d_in[8], (__nv_bfloat16*)d_out);
}
```

```cpp
#include <cuda_runtime.h>
#include <cuda_bf16.h>
#include <stdint.h>

namespace {

#define PACE_DT 636
#define PACE_LEAD 350
#define LATE_T 22450
#define LATE_DT 400
#define Q_T 4000
#define E2_T 24100
#define E3_T 24930
#ifndef M_NOM0
#define M_NOM0 5250
#define M_NOM1 9230
#define M_NOM2 13560
#define M_NOM3 17725
#endif
#define DEAD 80
#define NM 4
#define MEND 6
#define NSLOT 11

#define TN_E2 E2_T
#define TN_E3 E3_T
#define TN_A LATE_T
#define TN_B LATE_DT
#define EPB 16

constexpr int D_MODEL = 448;
constexpr int SK      = 32768;
constexpr int WIN     = 4096;
constexpr int DH      = 256;
constexpr int QCOLS   = 4096;
constexpr int FF      = 1792;
constexpr int NCTA    = 128;
constexpr int NFFN    = 112;
constexpr int NRED    = 56;
constexpr int NPT     = 128;
constexpr int NTHREADS = 512;

constexpr int NS     = NSLOT;
constexpr int SLOT   = 16384;
constexpr int XROW   = 912;
constexpr int S_K = 0, S_V = 16, NSTAGE = 32;
constexpr int S_GU   = NS;
constexpr int FFN_ST = 10;
constexpr int PRE_ST = 12;
constexpr int NBAR   = 36;
constexpr int B_X = NSTAGE;

constexpr int SM_RING  = 0;
constexpr int SM_STRIP = SM_RING + NS * SLOT;
constexpr int SM_S    = SM_STRIP + 448 * 64;
constexpr int SM_P    = SM_S + 2 * 520 * 4;
constexpr int SM_Q    = SM_P + 2 * 272 * 4;
constexpr int SM_XN   = SM_Q + 2 * 264 * 2;
constexpr int SM_X    = SM_XN + 2 * XROW;
constexpr int SM_RED  = SM_X + 1792 + 32;
constexpr int SM_STAT = SM_RED + 7 * 64 * 4;
constexpr int SM_OB   = SM_STAT + 2 * 8 * 2 * 4;
constexpr int SM_H    = SM_OB + 2 * 16 * 4;
constexpr int SM_T0   = SM_H + 2 * 8 * 4;
constexpr int SM_BAR  = SM_T0 + 16;
constexpr int SM_TOTAL = SM_BAR + 2 * NBAR * 8;
static_assert(SM_Q % 16 == 0 && SM_XN % 16 == 0 && SM_X % 16 == 0 && SM_OB % 16 == 0 && SM_P % 16 == 0 && SM_T0 % 16 == 0, "align");
static_assert(S_GU + 13 <= S_V + FFN_ST, "the gate/up strip lands with stage S_GU + 13");
static_assert(2 * NS >= 16, "K stage -> slot mapping");

constexpr int SPIN_LIMIT = 1 << 22;

struct Scratch {
    uint4    part[NCTA * 2 * 8 * 8];
    uint4    outp[NRED * NCTA * 4];
    uint4    q[8 * 2 * 128];
    uint2    ml[NCTA * 4];
    uint2    prog[4 * 32 * 4];
    unsigned epoch[NCTA * 8];
};
__device__ Scratch g_scratch;

#define TL(i)

__device__ __forceinline__ void mbar_init(uint32_t bar, uint32_t cnt) {
    asm volatile("mbarrier.init.shared::cta.b64 [%0], %1;" :: "r"(bar), "r"(cnt) : "memory");
}
__device__ __forceinline__ void mbar_arrive(uint32_t bar, uint32_t cnt) {
    asm volatile("mbarrier.arrive.shared::cta.b64 _, [%0], %1;" :: "r"(bar), "r"(cnt) : "memory");
}
__device__ __forceinline__ bool mbar_try(uint32_t bar) {
    uint32_t ok;
    asm volatile("{\n.reg .pred p;\nmbarrier.try_wait.parity.shared::cta.b64 p, [%1], 0;\nselp.u32 %0, 1, 0, p;\n}"
                 : "=r"(ok) : "r"(bar) : "memory");
    return ok;
}
__device__ __forceinline__ uint32_t time_ns() { uint32_t t; asm volatile("mov.u32 %0, %globaltimer_lo;" : "=r"(t)); return t; }
__device__ __forceinline__ void wait_until(uint32_t t0, uint32_t dt) { while (time_ns() - t0 < dt) {} }
__device__ __forceinline__ void mbar_wait(uint32_t bar) {
    asm volatile("{\n.reg .pred p;\nWAIT_LOOP:\nmbarrier.try_wait.parity.shared::cta.b64 p, [%0], 0;\n@!p bra WAIT_LOOP;\n}" :: "r"(bar) : "memory");
}
__device__ __forceinline__ void cp_async16_strip(uint32_t dst, const void* src) {
    asm volatile("cp.async.cg.shared.global.L2::128B [%0], [%1], 16;" :: "r"(dst), "l"(src) : "memory");
}
__device__ __forceinline__ void cp_async16_stream(uint32_t dst, const void* src) {
    asm volatile("{\n.reg .b64 pol;\ncreatepolicy.fractional.L2::evict_first.b64 pol, 1.0;\n"
                 "cp.async.cg.shared.global.L2::cache_hint [%0], [%1], 16, pol;\n}" :: "r"(dst), "l"(src) : "memory");
}
__device__ __forceinline__ void cp_async_arrive(uint32_t bar) {
    asm volatile("cp.async.mbarrier.arrive.noinc.shared::cta.b64 [%0];" :: "r"(bar) : "memory");
}
__device__ __forceinline__ void bar_sync(int id, int n)   { asm volatile("bar.sync %0, %1;" :: "r"(id), "r"(n) : "memory"); }
__device__ __forceinline__ void bar_arrive(int id, int n) { asm volatile("bar.arrive %0, %1;" :: "r"(id), "r"(n) : "memory"); }

__device__ __forceinline__ uint2 ld_poll2(const void* p) {
    uint2 v;
    asm volatile("ld.relaxed.gpu.global.v2.u32 {%0,%1}, [%2];" : "=r"(v.x), "=r"(v.y) : "l"(p) : "memory");
    return v;
}
__device__ __forceinline__ uint4 ld_poll4(const void* p) {
    uint4 v;
    asm volatile("ld.relaxed.gpu.global.v4.u32 {%0,%1,%2,%3}, [%4];" : "=r"(v.x), "=r"(v.y), "=r"(v.z), "=r"(v.w) : "l"(p) : "memory");
    return v;
}
__device__ __forceinline__ void st_pub4(void* p, uint4 v) {
    asm volatile("st.relaxed.gpu.global.v4.u32 [%0], {%1,%2,%3,%4};" :: "l"(p), "r"(v.x), "r"(v.y), "r"(v.z), "r"(v.w) : "memory");
}
__device__ __forceinline__ void st_pub2(void* p, uint32_t a, uint32_t b) {
    asm volatile("st.relaxed.gpu.global.v2.u32 [%0], {%1,%2};" :: "l"(p), "r"(a), "r"(b) : "memory");
}
__device__ __forceinline__ void st_pub1(void* p, uint32_t a) {
    asm volatile("st.relaxed.gpu.global.u32 [%0], %1;" :: "l"(p), "r"(a) : "memory");
}
__device__ __forceinline__ uint32_t tagf(float v, uint32_t tag) {
    uint32_t r;
    asm("lop3.b32 %0, %1, 0xfffffffe, %2, 0xEA;" : "=r"(r) : "r"(__float_as_uint(v)), "r"(tag));
    return r;
}
__device__ __forceinline__ uint32_t pin(uint32_t v) {
    uint32_t r;
    asm volatile("shfl.sync.bfly.b32 %0, %1, 0, 0x1f, 0xffffffff;" : "=r"(r) : "r"(v));
    return r;
}
template <class T>
__device__ __forceinline__ T* pin(T* p) {
    const uint64_t u = reinterpret_cast<uint64_t>(p);
    return reinterpret_cast<T*>(((uint64_t)pin((uint32_t)(u >> 32)) << 32) | pin((uint32_t)u));
}
__device__ __forceinline__ void sts32(uint32_t addr, uint32_t v) { asm volatile("st.shared.u32 [%0], %1;" :: "r"(addr), "r"(v) : "memory"); }
__device__ __forceinline__ float lds32(uint32_t addr) { float v; asm volatile("ld.shared.f32 %0, [%1];" : "=f"(v) : "r"(addr) : "memory"); return v; }
__device__ __forceinline__ uint4 lds128(uint32_t addr) {
    uint4 v;
    asm volatile("ld.shared.v4.u32 {%0,%1,%2,%3}, [%4];" : "=r"(v.x), "=r"(v.y), "=r"(v.z), "=r"(v.w) : "r"(addr) : "memory");
    return v;
}
__device__ __forceinline__ uint32_t bad2(uint32_t a, uint32_t b, uint32_t tag) {
    uint32_t r;
    asm("lop3.b32 %0, %1, %2, %3, 0x7E;" : "=r"(r) : "r"(a), "r"(b), "r"(tag));
    return r;
}
__device__ __forceinline__ uint32_t bad4(const uint4& v, uint32_t tag) { return bad2(v.x, v.y, tag) | bad2(v.z, v.w, tag); }
__device__ __forceinline__ bool warp_bad(uint32_t bad) { return __any_sync(0xffffffffu, bad & 1u); }

__device__ __forceinline__ void poll4(float (&f)[2][4], const uint4* p, uint32_t tag, const float (&w)[4]) {
    asm volatile("{\n"
                 ".reg .pred p0, p1, p2, p3, q;\n"
                 ".reg .b32 a, b, m, it, v<16>;\n"
                 "setp.eq.u32 p0, 0, 0;\nsetp.eq.u32 p1, 0, 0;\nsetp.eq.u32 p2, 0, 0;\nsetp.eq.u32 p3, 0, 0;\n"
                 "mov.u32 it, %14;\n"
                 "POLL_LOOP:\n"
                 "@p0 ld.relaxed.gpu.global.v4.u32 {v0,v1,v2,v3}, [%8];\n"
                 "@p1 ld.relaxed.gpu.global.v4.u32 {v4,v5,v6,v7}, [%8+512];\n"
                 "@p2 ld.relaxed.gpu.global.v4.u32 {v8,v9,v10,v11}, [%8+1024];\n"
                 "@p3 ld.relaxed.gpu.global.v4.u32 {v12,v13,v14,v15}, [%8+1536];\n"
                 "sub.u32 it, it, 1;\n"
                 "min.u32 m, it, 1;\n"
                 "lop3.b32 a, v0, v1, %9, 0x7E;\nlop3.b32 b, v2, v3, %9, 0x7E;\nlop3.b32 a, a, b, m, 0xA8;\nsetp.ne.u32 p0, a, 0;\n"
                 "lop3.b32 a, v4, v5, %9, 0x7E;\nlop3.b32 b, v6, v7, %9, 0x7E;\nlop3.b32 a, a, b, m, 0xA8;\nsetp.ne.u32 p1, a, 0;\n"
                 "lop3.b32 a, v8, v9, %9, 0x7E;\nlop3.b32 b, v10, v11, %9, 0x7E;\nlop3.b32 a, a, b, m, 0xA8;\nsetp.ne.u32 p2, a, 0;\n"
                 "lop3.b32 a, v12, v13, %9, 0x7E;\nlop3.b32 b, v14, v15, %9, 0x7E;\nlop3.b32 a, a, b, m, 0xA8;\nsetp.ne.u32 p3, a, 0;\n"
                 "or.pred q, p0, p1;\nor.pred q, q, p2;\nor.pred q, q, p3;\n"
                 "mul.f32 %0, v0, %10;\nmul.f32 %1, v1, %10;\nmul.f32 %2, v2, %10;\nmul.f32 %3, v3, %10;\n"
                 "mul.f32 %4, v8, %12;\nmul.f32 %5, v9, %12;\nmul.f32 %6, v10, %12;\nmul.f32 %7, v11, %12;\n"
                 "vote.sync.any.pred q, q, 0xffffffff;\n"
                 "fma.rn.f32 %0, v4, %11, %0;\nfma.rn.f32 %1, v5, %11, %1;\nfma.rn.f32 %2, v6, %11, %2;\nfma.rn.f32 %3, v7, %11, %3;\n"
                 "fma.rn.f32 %4, v12, %13, %4;\nfma.rn.f32 %5, v13, %13, %5;\nfma.rn.f32 %6, v14, %13, %6;\nfma.rn.f32 %7, v15, %13, %7;\n"
                 "@q bra POLL_LOOP;\n"
                 "}"
                 : "=&f"(f[0][0]), "=&f"(f[0][1]), "=&f"(f[0][2]), "=&f"(f[0][3]), "=&f"(f[1][0]), "=&f"(f[1][1]), "=&f"(f[1][2]), "=&f"(f[1][3])
                 : "l"(p), "r"(tag), "f"(w[0]), "f"(w[1]), "f"(w[2]), "f"(w[3]), "n"(SPIN_LIMIT) : "memory");
}

__device__ __forceinline__ void ldsm4(uint32_t addr, uint32_t (&a)[4]) {
    asm volatile("ldmatrix.sync.aligned.m8n8.x4.shared.b16 {%0,%1,%2,%3}, [%4];" : "=r"(a[0]), "=r"(a[1]), "=r"(a[2]), "=r"(a[3]) : "r"(addr) : "memory");
}
__device__ __forceinline__ void ldsm4t(uint32_t addr, uint32_t (&a)[4]) {
    asm volatile("ldmatrix.sync.aligned.m8n8.x4.trans.shared.b16 {%0,%1,%2,%3}, [%4];" : "=r"(a[0]), "=r"(a[1]), "=r"(a[2]), "=r"(a[3]) : "r"(addr) : "memory");
}
__device__ __forceinline__ void mma16816(float (&c)[4], const uint32_t (&a)[4], uint32_t b0, uint32_t b1) {
    asm volatile("mma.sync.aligned.m16n8k16.row.col.f32.bf16.bf16.f32 {%0,%1,%2,%3}, {%4,%5,%6,%7}, {%8,%9}, {%0,%1,%2,%3};"
                 : "+f"(c[0]), "+f"(c[1]), "+f"(c[2]), "+f"(c[3]) : "r"(a[0]), "r"(a[1]), "r"(a[2]), "r"(a[3]), "r"(b0), "r"(b1));
}
__device__ __forceinline__ float bf_lo(uint32_t u) { return __uint_as_float(u << 16); }
__device__ __forceinline__ float bf_hi(uint32_t u) { return __uint_as_float(u & 0xffff0000u); }
__device__ __forceinline__ float rbf(float v) { return __bfloat162float(__float2bfloat16_rn(v)); }
__device__ __forceinline__ uint32_t pack_bf(float lo, float hi) {
    uint32_t r;
    asm("cvt.rn.bf16x2.f32 %0, %1, %2;" : "=r"(r) : "f"(hi), "f"(lo));
    return r;
}
__device__ __forceinline__ float sel4(const float (&c)[4], int t) {
    float a = (t & 1) ? c[1] : c[0];
    float b = (t & 1) ? c[3] : c[2];
    return (t & 2) ? b : a;
}
__device__ __forceinline__ float ex2(float x) { float y; asm("ex2.approx.ftz.f32 %0, %1;" : "=f"(y) : "f"(x)); return y; }
__device__ __forceinline__ float sqrt_approx(float x) { float y; asm("sqrt.approx.f32 %0, %1;" : "=f"(y) : "f"(x)); return y; }

__host__ __device__ constexpr uint32_t slot_of(int s) { return SM_RING + (s % NS) * SLOT; }

__device__ __forceinline__ void layernorm(unsigned char* smem, int lane) {
    uint32_t xs[2][7];
#pragma unroll
    for (int b = 0; b < 2; b++)
#pragma unroll
        for (int i = 0; i < 7; i++) xs[b][i] = reinterpret_cast<const uint32_t*>(smem + SM_X)[b * (D_MODEL / 2) + i * 32 + lane];
#pragma unroll
    for (int b = 0; b < 2; b++) {
        float sum = 0.f;
#pragma unroll
        for (int i = 0; i < 7; i++) sum += bf_lo(xs[b][i]) + bf_hi(xs[b][i]);
#pragma unroll
        for (int o = 16; o > 0; o >>= 1) sum += __shfl_xor_sync(0xffffffffu, sum, o);
        const float mean = sum * (1.0f / D_MODEL);
        float sq = 0.f;
#pragma unroll
        for (int i = 0; i < 7; i++) {
            const float d0 = bf_lo(xs[b][i]) - mean, d1 = bf_hi(xs[b][i]) - mean;
            sq = fmaf(d0, d0, fmaf(d1, d1, sq));
        }
#pragma unroll
        for (int o = 16; o > 0; o >>= 1) sq += __shfl_xor_sync(0xffffffffu, sq, o);
        const float mb = rbf(mean);
        const float sd = rbf(sqrt_approx(rbf(rbf(sq * (1.0f / D_MODEL)) + 1e-5f)));
#pragma unroll
        for (int i = 0; i < 7; i++)
            reinterpret_cast<uint32_t*>(smem + SM_XN + b * XROW)[i * 32 + lane] =
                pack_bf(__fdividef(rbf(bf_lo(xs[b][i]) - mb), sd), __fdividef(rbf(bf_hi(xs[b][i]) - mb), sd));
    }
}

__device__ __forceinline__ void strip_partial(uint32_t sb, uint32_t strip, unsigned char* smem, int warp, int lane) {
    float c[2][2][4];
#pragma unroll
    for (int n = 0; n < 2; n++)
#pragma unroll
        for (int e = 0; e < 4; e++) c[n][0][e] = c[n][1][e] = 0.f;
    const uint32_t ba = sb + SM_XN + (lane & 1) * XROW + (lane >> 3) * 16 + warp * 128;
    const uint32_t aa = sb + strip + (warp * 64 + (lane & 7) + (lane >> 4) * 8) * 64 + (((lane >> 3) & 1) ^ ((lane & 7) >> 1)) * 16;
#pragma unroll
    for (int k2 = 0; k2 < 2; k2++) {
        uint32_t b[4];
        ldsm4(ba + k2 * 64, b);
#pragma unroll
        for (int n = 0; n < 2; n++) {
            uint32_t a0[4], a1[4];
            ldsm4t((aa ^ (n * 32)) + k2 * 2048, a0);
            ldsm4t((aa ^ (n * 32)) + k2 * 2048 + 1024, a1);
            mma16816(c[n][0], a0, b[0], b[1]);
            mma16816(c[n][1], a1, b[2], b[3]);
        }
    }
    float* red = reinterpret_cast<float*>(smem + SM_RED) + warp * 64 + lane;
#pragma unroll
    for (int n = 0; n < 2; n++) red[n * 32] = sel4(c[n][0], lane & 3) + sel4(c[n][1], lane & 3);
}
__device__ __forceinline__ float strip_sum(const unsigned char* smem, int idx) {
    const float* red = reinterpret_cast<const float*>(smem + SM_RED) + idx;
    return ((red[0] + red[64]) + (red[128] + red[192])) + ((red[256] + red[320]) + red[384]);
}

__device__ __forceinline__ uint32_t time_base(uint32_t sb, int i) {
    uint32_t t;
    asm volatile("ld.volatile.shared.u32 %0, [%1];" : "=r"(t) : "r"(sb + SM_T0 + 4 * i) : "memory");
    return t;
}
__device__ __forceinline__ void wait_clock(uint32_t sb, int i, uint32_t dt) { while (time_ns() - time_base(sb, i) < dt) {} }

struct Prod {
    uint32_t sb, kvdst, sdst;
    const char *k, *v;
    const __nv_bfloat16* gu;
    bool ffn;
};
__host__ __device__ constexpr int bytes_before(int s) { return 28672 + s * 16384 + (s <= S_GU ? 0 : s < S_GU + 14 ? s - S_GU : 14) * 1792; }
__host__ __device__ constexpr int issue_time(int s) { return (int)((long long)bytes_before(s) * PACE_DT / 16384) - PACE_LEAD; }

template <int S>
__device__ __forceinline__ void produce(Prod& p) {
    if constexpr (S < NSTAGE) {
        if constexpr (S >= NS) mbar_wait(p.sb + SM_BAR + (NBAR + S - NS) * 8);
        wait_clock(p.sb, 0, issue_time(S));
        const char* src = (S < S_V ? p.k : p.v) + (S & 15) * (8 * SLOT);
#pragma unroll
        for (int i = 0; i < 8; i++) cp_async16_stream((p.kvdst ^ ((i & 1) * 64)) + slot_of(S) + i * 2048, src + i * 2048);
        if constexpr (S >= S_GU && S < S_GU + 14) {
            if (p.ffn) cp_async16_strip(p.sdst + (S - S_GU) * 2048, p.gu + (size_t)(S - S_GU) * 32 * FF);
        }
        cp_async_arrive(p.sb + SM_BAR + S * 8);
        produce<S + 1>(p);
    }
}

__device__ __forceinline__ void fetch16(uint32_t dst, const char* src) {
#pragma unroll
    for (int i = 0; i < 4; i++)
        asm volatile("cp.async.cg.shared.global [%0], [%1], 16;" :: "r"((dst ^ (((i & 1) ^ (i >> 1)) * 64)) + i * 512), "l"(src + i * (4 * 896)) : "memory");
}
template <int PENDING, int OFF>
__device__ __forceinline__ void frag16(uint32_t (&a)[4][4], uint32_t addr) {
    asm volatile("cp.async.wait_group %0;" :: "n"(PENDING) : "memory");
    __syncwarp();
#pragma unroll
    for (int m = 0; m < 4; m++) ldsm4t((addr ^ (m * 32)) + OFF, a[m]);
}

__device__ __forceinline__ void load_x(uint32_t sb, const void* x, const void* epoch) {
    const uint32_t full0 = sb + SM_BAR;
    mbar_init(full0 + B_X * 8, 1);
    asm volatile("fence.mbarrier_init.release.cluster;" ::: "memory");
    asm volatile("mbarrier.arrive.expect_tx.shared::cta.b64 _, [%0], %1;" :: "r"(full0 + B_X * 8), "r"(1792 + EPB) : "memory");
    asm volatile("cp.async.bulk.shared::cluster.global.mbarrier::complete_tx::bytes [%0], [%1], %2, [%3];"
                 :: "r"(sb + SM_X), "l"(x), "r"(1792), "r"(full0 + B_X * 8) : "memory");
    asm volatile("cp.async.bulk.shared::cluster.global.mbarrier::complete_tx::bytes [%0], [%1], %2, [%3];"
                 :: "r"(sb + SM_X + 1792), "l"(epoch), "r"(EPB), "r"(full0 + B_X * 8) : "memory");
}

enum { BAR_OB = 1, BAR_CONS = 2, BAR_LN = 3, BAR_FF = 4, BAR_FIN = 5, BAR_H = 6 };

__global__ void __launch_bounds__(NTHREADS, 1)
fused_decode_kernel(const __nv_bfloat16* __restrict__ wq, const __nv_bfloat16* __restrict__ kc, const __nv_bfloat16* __restrict__ x,
                    Scratch* __restrict__ scr, const __nv_bfloat16* __restrict__ vc, const __nv_bfloat16* __restrict__ wo,
                    const __nv_bfloat16* __restrict__ wg, const __nv_bfloat16* __restrict__ wu, const __nv_bfloat16* __restrict__ wd,
                    __nv_bfloat16* __restrict__ out) {
    extern __shared__ __align__(128) unsigned char smem[];
    const uint32_t sb = (uint32_t)__cvta_generic_to_shared(smem);
    const int tid = threadIdx.x, lane = tid & 31;
    const int cta = blockIdx.x;
    const uint32_t full0 = sb + SM_BAR, done0 = full0 + NBAR * 8;
    const uint32_t t0 = time_ns();
    if (tid < 224) {
        const int row = (tid >> 5) * 64 + (lane >> 2);
        const char* src = reinterpret_cast<const char*>(wq) + (uint32_t)(row * (QCOLS * 2) + cta * 64 + (lane & 3) * 16);
        const uint32_t dst = sb + SM_STRIP + row * 64 + ((lane & 3) ^ (lane >> 3)) * 16;
#pragma unroll
        for (int i = 0; i < 8; i++) cp_async16_strip(dst + i * 512, src + i * (8 * QCOLS * 2));
    }
    const int warp = __shfl_sync(0xffffffffu, tid >> 5, 0);
    const int hkv = cta >> 4, j = cta & 15, bat = j >> 3, sp = j & 7;
    const int g = lane >> 2, t = lane & 3;

    if (warp < 8) {
        if (warp == 0) TL(0);
        if (tid == 224) load_x(sb, x, &scr->epoch[cta * 8]);
        __syncthreads();
        mbar_wait(full0 + B_X * 8);
        const uint32_t epoch = *reinterpret_cast<const uint32_t*>(smem + SM_X + 1792);
        const uint32_t tag = pin((epoch + 1) & 1);
        uint32_t* qdst = reinterpret_cast<uint32_t*>(scr->q) + (hkv * 2 + (t & 1)) * 512 + j * 32 + warp * 16 + g + 8 * (t >> 1);
        if (warp == 7) {
            layernorm(smem, lane);
            bar_arrive(BAR_LN, 256);
            TL(13);
        } else {
            asm volatile("cp.async.wait_all;" ::: "memory");
            bar_sync(BAR_LN, 256);
            strip_partial(sb, SM_STRIP, smem, warp, lane);
        }
        bar_sync(BAR_CONS, 256);
        if (warp < 2) {
            st_pub1(qdst, (pack_bf(0.f, strip_sum(smem, tid)) & 0xffff0000u) | tag);
            if (warp == 0) TL(6);
        } else if (warp >= 4) {
            const int i = tid - 128;
            const uint4* qp = scr->q + (hkv * 2 + bat) * 128 + i;
            wait_until(t0, Q_T);
            uint4 v;
            int it = 0;
            do {
                v = ld_poll4(qp);
                if (++it > SPIN_LIMIT) __trap();
            } while (warp_bad(bad4(v, tag)));
            *reinterpret_cast<uint2*>(smem + SM_Q + (i >> 6) * 528 + (i & 63) * 8) =
                make_uint2(__byte_perm(v.x, v.y, 0x7632), __byte_perm(v.z, v.w, 0x7632));
        }
        bar_sync(BAR_CONS, 256);
        if (tid == 96) scr->epoch[cta * 8] = epoch + 1;
        if (warp == 0) TL(7);
        {
            uint32_t qf[8][4];
#pragma unroll
            for (int k2 = 0; k2 < 8; k2++) ldsm4(sb + SM_Q + (lane & 1) * 528 + k2 * 64 + (lane >> 3) * 16, qf[k2]);
            const int mt = warp & 1;
            const uint32_t aoff = (16 * mt + (lane & 15)) * 512 + ((lane >> 4) ^ (lane & 7)) * 16;
            float* sc = reinterpret_cast<float*>(smem + SM_S) + (t & 1) * 520 + (g >> 1) * 8 + (2 * mt + (t >> 1)) * 2 + (g & 1);
#pragma unroll 1
            for (int k = warp >> 1; k < 16; k += 4) {
                const int s = S_K + k;
                mbar_wait(full0 + s * 8);
                const uint32_t base = sb + SM_RING + (s >= NS ? s - NS : s) * SLOT + aoff;
                float c0[4] = {0.f, 0.f, 0.f, 0.f}, c1[4] = {0.f, 0.f, 0.f, 0.f};
#pragma unroll
                for (int k2 = 0; k2 < 8; k2++) {
                    uint32_t a0[4], a1[4];
                    ldsm4((base ^ ((k2 & 1) * 64)) + (k2 >> 1) * 128, a0);
                    ldsm4((base ^ ((k2 & 1) * 64 + 32)) + (k2 >> 1) * 128, a1);
                    mma16816(c0, a0, qf[k2][0], qf[k2][1]);
                    mma16816(c1, a1, qf[k2][2], qf[k2][3]);
                }
                __syncwarp();
                if (lane == 0) mbar_arrive(done0 + s * 8, 4);
                sc[k * 32] = rbf(sel4(c0, t) + sel4(c1, t));
            }
        }
        bar_sync(BAR_CONS, 256);
        if (warp == 0) TL(8);
        {
            constexpr float C = 0.0625f * 1.4426950408889634f;
            const float* sc = reinterpret_cast<const float*>(smem + SM_S);
            float* stat = reinterpret_cast<float*>(smem + SM_STAT);
            const float2 s0 = *reinterpret_cast<const float2*>(sc + 2 * tid);
            const float2 s1 = *reinterpret_cast<const float2*>(sc + 520 + 2 * tid);
            float m0 = fmaxf(s0.x, s0.y), m1 = fmaxf(s1.x, s1.y);
#pragma unroll
            for (int o = 16; o > 0; o >>= 1) {
                m0 = fmaxf(m0, __shfl_xor_sync(0xffffffffu, m0, o));
                m1 = fmaxf(m1, __shfl_xor_sync(0xffffffffu, m1, o));
            }
            if (lane == 0) *reinterpret_cast<float2*>(stat + warp * 2) = make_float2(m0, m1);
            bar_sync(BAR_CONS, 256);
#pragma unroll
            for (int w = 0; w < 8; w++) {
                const float2 mm = *reinterpret_cast<const float2*>(stat + w * 2);
                m0 = fmaxf(m0, mm.x); m1 = fmaxf(m1, mm.y);
            }
            const float p00 = ex2((s0.x - m0) * C), p01 = ex2((s0.y - m0) * C);
            const float p10 = ex2((s1.x - m1) * C), p11 = ex2((s1.y - m1) * C);
            uint32_t* ps = reinterpret_cast<uint32_t*>(smem + SM_P);
            ps[tid] = pack_bf(p00, p01);
            ps[272 + tid] = pack_bf(p10, p11);
            float l0 = p00 + p01, l1 = p10 + p11;
#pragma unroll
            for (int o = 16; o > 0; o >>= 1) {
                l0 += __shfl_xor_sync(0xffffffffu, l0, o);
                l1 += __shfl_xor_sync(0xffffffffu, l1, o);
            }
            if (lane == 0) *reinterpret_cast<float2*>(stat + 16 + warp * 2) = make_float2(l0, l1);
            bar_sync(BAR_CONS, 256);
            if (tid < 4) {
                float l = 0.f;
#pragma unroll
                for (int w = 0; w < 8; w++) l += stat[16 + w * 2 + (tid & 1)];
                st_pub2(scr->ml + cta * 4 + tid, tagf(((tid & 1) ? m1 : m0) * C, tag), tagf(l, tag));
            }
        }
        if (warp == 0) TL(9);
        float wgt[2] = {0.f, 0.f};
        {
            float o0[4] = {0.f, 0.f, 0.f, 0.f}, o1[4] = {0.f, 0.f, 0.f, 0.f};
            float o2[4] = {0.f, 0.f, 0.f, 0.f}, o3[4] = {0.f, 0.f, 0.f, 0.f};
            const uint32_t aoff = ((lane & 7) + (lane >> 4) * 8) * 512 + ((warp * 4 + ((lane >> 3) & 1) * 2) ^ (lane & 7)) * 16;
            const uint4* ps = reinterpret_cast<const uint4*>(smem + SM_P + (g & 1) * 272 * 4) + t;
            uint32_t* dst = reinterpret_cast<uint32_t*>(scr->part) + ((size_t)(hkv * 16 + (t & 1) * 8 + warp) * 16 + j) * 32 +
                            (4 * (g & 3) + (t & 2) + (g >> 2)) * 2;
#pragma unroll
            for (int k = 0; k < 16; k++) {
                const uint4 pa = ps[k * 4];
                mbar_wait(full0 + (S_V + k) * 8);
                uint32_t a[4][4];
#pragma unroll
                for (int i = 0; i < 4; i++) ldsm4t(sb + (aoff ^ ((i & 1) * 16)) + slot_of(S_V + k) + (i >> 1) * 8192, a[i]);
                mma16816(o0, a[0], pa.x, pa.y);
                mma16816(o1, a[1], pa.x, pa.y);
                mma16816(o2, a[2], pa.z, pa.w);
                mma16816(o3, a[3], pa.z, pa.w);
                if (S_V + k + NS < NSTAGE + 3) {
                    __syncwarp();
                    if (lane == 0) mbar_arrive(done0 + (S_V + k) * 8, 1);
                }
                if (k == FFN_ST && warp < 7) {
                    strip_partial(sb, SM_STRIP, smem, warp, lane);
                    bar_arrive(BAR_FF, 256);
                }
                if (k == FFN_ST && warp == 7) {
                    const uint2* mlp = scr->ml + (hkv * 16 + g) * 4 + (j >> 3);
                    uint2 a, b;
                    int it = 0;
                    do {
                        a = ld_poll2(mlp); b = ld_poll2(mlp + 32);
                        if (++it > SPIN_LIMIT) __trap();
                    } while (warp_bad(bad2(a.x, a.y, tag) | bad2(b.x, b.y, tag)));
                    float m[2] = {__uint_as_float(a.x), __uint_as_float(b.x)};
                    float l[2] = {__uint_as_float(a.y), __uint_as_float(b.y)};
#pragma unroll
                    for (int bb = 0; bb < 2; bb++) {
                        float M = m[bb];
                        M = fmaxf(M, __shfl_xor_sync(0xffffffffu, M, 4));
                        M = fmaxf(M, __shfl_xor_sync(0xffffffffu, M, 8));
                        M = fmaxf(M, __shfl_xor_sync(0xffffffffu, M, 16));
                        const float e = ex2(m[bb] - M);
                        float L = e * l[bb];
                        L += __shfl_xor_sync(0xffffffffu, L, 4);
                        L += __shfl_xor_sync(0xffffffffu, L, 8);
                        L += __shfl_xor_sync(0xffffffffu, L, 16);
                        wgt[bb] = __fdividef(e, L);
                    }
                    bar_sync(BAR_FF, 256);
                    float ga = rbf(strip_sum(smem, lane));
                    ga *= (ga > 0.f ? 1.f : 0.f);
                    const float hv = ga * rbf(strip_sum(smem, 32 + lane));
                    const uint32_t w = pack_bf(hv, __shfl_xor_sync(0xffffffffu, hv, 2));
                    if (!(t & 2)) reinterpret_cast<uint32_t*>(smem + SM_H)[(t & 1) * 8 + (g & 3) * 2 + (g >> 2)] = w;
                    bar_arrive(BAR_H, 256);
                }
                if (k == PRE_ST) st_pub2(dst, tag ^ 1, tag ^ 1);
            }
            const float v0 = sel4(o0, t) + sel4(o2, t), v1 = sel4(o1, t) + sel4(o3, t);
            st_pub2(dst, tagf(v0, tag), tagf(v1, tag));
        }
        if (warp == 0) TL(10);
        if (warp == 7) {
            const uint4* pp = pin(scr->part + (size_t)cta * 128 + lane);
            const uint32_t obaddr = pin(sb + SM_OB + (lane >> 4) * 64 + (lane & 7) * 8 + ((lane >> 3) & 1) * 4), ll = pin(lane);
            float w[4];
#pragma unroll
            for (int i = 0; i < 4; i++) w[i] = __shfl_sync(0xffffffffu, wgt[i >> 1], ((i & 1) * 4 + (lane >> 3)) * 4);
            wait_until(time_base(sb, 2), TN_E2);
            TL(2);
            float f[2][4];
            poll4(f, pp, tag, w);
            TL(3);
            const bool h16 = ll & 16, h8 = ll & 8;
            float r4[4], r2[2];
#pragma unroll
            for (int e = 0; e < 4; e++) r4[e] = (h16 ? f[1][e] : f[0][e]) + __shfl_xor_sync(0xffffffffu, h16 ? f[0][e] : f[1][e], 16);
#pragma unroll
            for (int e = 0; e < 2; e++) r2[e] = (h8 ? r4[2 + e] : r4[e]) + __shfl_xor_sync(0xffffffffu, h8 ? r4[e] : r4[2 + e], 8);
            sts32(obaddr, pack_bf(r2[0], r2[1]));
            bar_arrive(BAR_OB, 256);
            TL(14);
        } else if (warp < 4 && (cta & 1) == 0 && cta < 2 * NRED) {
            const uint4* op = pin(scr->outp + (size_t)(cta >> 1) * (NCTA * 4) + warp * 128 + lane);
            const int oidx = (t & 1) * D_MODEL + hkv * 64 + (lane >> 3) * 16 + (j >> 1) + (t >> 1) * 8;
            const float xv = __bfloat162float(reinterpret_cast<const __nv_bfloat16*>(smem + SM_X)[oidx]);
            __nv_bfloat16* optr = pin(out + oidx);
            const uint32_t red = pin(sb + SM_S + tid * 4), ll = pin(lane);
            const float one[4] = {1.f, 1.f, 1.f, 1.f};
            float f[2][4], a[4];
            wait_until(time_base(sb, 3), TN_E3);
            poll4(f, op, tag, one);
            if (warp == 0) TL(4);
#pragma unroll
            for (int e = 0; e < 4; e++) a[e] = f[0][e] + f[1][e];
            const bool h16 = ll & 16, h8 = ll & 8;
            float r2[2];
#pragma unroll
            for (int e = 0; e < 2; e++) r2[e] = (h16 ? a[2 + e] : a[e]) + __shfl_xor_sync(0xffffffffu, h16 ? a[e] : a[2 + e], 16);
            float r = (h8 ? r2[1] : r2[0]) + __shfl_xor_sync(0xffffffffu, h8 ? r2[0] : r2[1], 8);
            r += __shfl_xor_sync(0xffffffffu, r, 4);
            if (warp != 0) {
                sts32(red, __float_as_uint(r));
                bar_arrive(BAR_FIN, 128);
            } else {
                bar_sync(BAR_FIN, 128);
                r = ((xv + r) + lds32(red + 128)) + (lds32(red + 256) + lds32(red + 384));
                asm volatile("st.global.u16 [%0], %1;" :: "l"(optr), "h"(__bfloat16_as_ushort(__float2bfloat16_rn(r))) : "memory");
                TL(5);
            }
        }
    } else if (warp < 15) {
        const int pt = tid - 256, pw = warp - 8;
        const char* pdn = reinterpret_cast<const char*>(wd) + (size_t)cta * 14336 + (lane >> 3) * 896 + pw * 128 + (lane & 7) * 16;
        const char* pwo = reinterpret_cast<const char*>(wo) + (size_t)cta * 28672 + (lane >> 3) * 896 + pw * 128 + (lane & 7) * 16;
        if (pw < 4) {
            if (lane == 0) {
                const int w = pw;
#pragma unroll
                for (int i = 0; i < 9; i++) {
                    if (w * 9 + i != B_X) mbar_init(full0 + (w * 9 + i) * 8, NPT);
                    mbar_init(done0 + (w * 9 + i) * 8, 8);
                }
            }
            Prod p;
            const size_t kvoff = ((size_t)(bat * 8 + hkv) * SK + (SK - WIN)) * DH * 2 + sp * SLOT + pt * 16;
            p.sb = sb;
            p.kvdst = (sb + pt * 16) ^ (pw * 16);
            p.sdst = sb + SM_STRIP + (pt >> 2) * 64 + ((pt & 3) ^ ((pt >> 3) & 3)) * 16;
            p.k = reinterpret_cast<const char*>(kc) + kvoff;
            p.v = reinterpret_cast<const char*>(vc) + kvoff;
            p.gu = ((pt & 2) ? wu : wg) + cta * 16 + (pt & 1) * 8 + (size_t)(pt >> 2) * FF;
            p.ffn = cta < NFFN;
            __syncthreads();
            produce<0>(p);
        } else {
            __syncthreads();
        }
        mbar_wait(full0 + B_X * 8);
        const uint32_t tag = pin((*reinterpret_cast<const uint32_t*>(smem + SM_X + 1792) + 1) & 1);
        if (pw == 4 && (cta & 3) == 0) {
#pragma unroll 1
            for (int i = 0; i < 4; i++) {
                uint32_t sum = 0;
#pragma unroll
                for (int k = 0; k < NM; k++) {
                    mbar_wait(full0 + (MEND - NM + 1 + k + 6 * i) * 8);
                    sum += time_ns() - t0;
                }
                if (lane < 4) st_pub2(&scr->prog[i * 128 + cta + lane], ((t0 + sum / NM) & ~1u) | tag, (t0 & ~1u) | tag);
            }
        }
        mbar_wait(done0 + (NSTAGE + 2 - NS) * 8);
        bar_sync(BAR_H, 256);
        const uint2 h = *reinterpret_cast<const uint2*>(smem + SM_H + (g & 1) * 32 + t * 8);
        const uint32_t ta = TN_A, td = TN_B;
        uint4* odst = scr->outp + ((size_t)(pt >> 2) * NCTA + cta) * 4 + t;
        st_pub4(odst, make_uint4(tag ^ 1, tag ^ 1, tag ^ 1, tag ^ 1));
        const uint32_t fdst = (sb + pw * 2048 + lane * 16) ^ ((lane >> 3) * 16);
        wait_clock(sb, 1, ta);
        if (cta < NFFN) fetch16(fdst + slot_of(NSTAGE), pdn);
        asm volatile("cp.async.commit_group;" ::: "memory");
        wait_clock(sb, 1, ta + td);
        fetch16(fdst + slot_of(NSTAGE + 1), pwo);
        asm volatile("cp.async.commit_group;" ::: "memory");
        wait_clock(sb, 1, ta + 2 * td);
        fetch16(fdst + slot_of(NSTAGE + 2), pwo + 14336);
        asm volatile("cp.async.commit_group;" ::: "memory");
        if (pw == 0) TL(1);
        float c[4][4];
#pragma unroll
        for (int m = 0; m < 4; m++)
#pragma unroll
            for (int e = 0; e < 4; e++) c[m][e] = 0.f;
        const int r7 = ((lane & 7) >> 1) + 4 * (lane >> 4);
        const uint32_t aoff = sb + pw * 2048 + (r7 + 8 * (lane & 1)) * 128 + (((lane >> 3) & 1) ^ r7 ^ ((lane & 1) << 2)) * 16;
        const uint32_t obaddr = pin(sb + SM_OB + (g & 1) * 64 + t * 16), tt = pin(t);
        uint32_t a0[4][4], a1[4][4];
        frag16<2, slot_of(NSTAGE)>(a0, aoff);
        if (cta < NFFN) {
#pragma unroll
            for (int m = 0; m < 4; m++) mma16816(c[m], a0[m], h.x, h.y);
        }
        frag16<1, slot_of(NSTAGE + 1)>(a1, aoff);
        bar_sync(BAR_OB, 256);
        const uint4 ob = lds128(obaddr);
#pragma unroll
        for (int m = 0; m < 4; m++) mma16816(c[m], a1[m], ob.x, ob.y);
        frag16<0, slot_of(NSTAGE + 2)>(a0, aoff);
#pragma unroll
        for (int m = 0; m < 4; m++) mma16816(c[m], a0[m], ob.z, ob.w);
        uint4 r;
        r.x = tagf(sel4(c[0], tt), tag); r.y = tagf(sel4(c[1], tt), tag);
        r.z = tagf(sel4(c[2], tt), tag); r.w = tagf(sel4(c[3], tt), tag);
        st_pub4(odst, r);
        if (pw == 0) TL(12);
    } else if (warp == 15) {
        if (lane < 4) reinterpret_cast<uint32_t*>(smem + SM_T0)[lane] = t0;
        __syncthreads();
        mbar_wait(full0 + B_X * 8);
        const uint32_t tag = (*reinterpret_cast<const uint32_t*>(smem + SM_X + 1792) + 1) & 1;
#pragma unroll 1
        for (int i = 0; i < 4; i++) {
            mbar_wait(full0 + (MEND + 2 + 6 * i) * 8);
            uint2 v;
            int it = 0;
            do {
                v = ld_poll2(&scr->prog[i * 128 + lane * 4]);
                if (++it > SPIN_LIMIT) __trap();
            } while (warp_bad(bad2(v.x, v.y, tag)));
            const int nom = i == 0 ? M_NOM0 : i == 1 ? M_NOM1 : i == 2 ? M_NOM2 : M_NOM3;
            int base = (__reduce_add_sync(0xffffffffu, min(max((int)(v.x - t0), 0), 1 << 20)) >> 5) - nom;
            const int start = __reduce_add_sync(0xffffffffu, min(max((int)(v.y - t0), -(1 << 20)), 1 << 20)) >> 5;
            base = start + max(min(base - start, 2 * (base - start - DEAD)), 0);
            const int ahead = (lane == 0 ? nom : lane == 1 ? LATE_T : lane == 2 ? E2_T : E3_T - 150) - nom;
            const float rate = fminf(fmaxf(__fdividef((float)(base - start), (float)(nom - 500)), -0.01f), 0.045f);
            if (lane < 4) sts32(sb + SM_T0 + 4 * lane, t0 + base + (int)(rate * (float)ahead));
        }
        TL(15);
    }
}

}

extern "C" void kernel_launch(void* const* d_in, const int* in_sizes, int n_in, void* d_out, int out_size) {
    (void)in_sizes; (void)n_in; (void)out_size;
    static Scratch* scr = nullptr;
    if (!scr) {
        cudaFuncSetAttribute(fused_decode_kernel, cudaFuncAttributeMaxDynamicSharedMemorySize, SM_TOTAL);
        cudaGetSymbolAddress(reinterpret_cast<void**>(&scr), g_scratch);
    }
    typedef const __nv_bfloat16* P;
#define NGRID NCTA
    fused_decode_kernel<<<NGRID, NTHREADS, SM_TOTAL>>>((P)d_in[3], (P)d_in[1], (P)d_in[0], scr, (P)d_in[2], (P)d_in[4],
                                                      (P)d_in[6], (P)d_in[7], (P)d_in[8], (__nv_bfloat16*)d_out);
}
```

```cpp
#include <cuda_runtime.h>
#include <cuda_bf16.h>
#include <stdint.h>

namespace {

#define PACE_DT 636
#define PACE_LEAD 350
#define LATE_T 22420
#define LATE_DT 400
#define Q_T 4000
#define E2_T 24050
#define E3_T 24890
#ifndef M_NOM0
#define M_NOM0 5250
#define M_NOM1 9230
#define M_NOM2 13560
#define M_NOM3 17725
#endif
#define DEAD 100
#define NM 4
#define MEND 6
#define NSLOT 11

#define TN_E2 E2_T
#define TN_E3 E3_T
#define TN_A LATE_T
#define TN_B LATE_DT
#define EPB 16

constexpr int D_MODEL = 448;
constexpr int SK      = 32768;
constexpr int WIN     = 4096;
constexpr int DH      = 256;
constexpr int QCOLS   = 4096;
constexpr int FF      = 1792;
constexpr int NCTA    = 128;
constexpr int NFFN    = 112;
constexpr int NRED    = 56;
constexpr int NPT     = 128;
constexpr int NTHREADS = 512;

constexpr int NS     = NSLOT;
constexpr int SLOT   = 16384;
constexpr int XROW   = 912;
constexpr int S_K = 0, S_V = 16, NSTAGE = 32;
constexpr int S_GU   = NS;
constexpr int FFN_ST = 10;
constexpr int PRE_ST = 12;
constexpr int NBAR   = 36;
constexpr int B_X = NSTAGE;

constexpr int SM_RING  = 0;
constexpr int SM_STRIP = SM_RING + NS * SLOT;
constexpr int SM_S    = SM_STRIP + 448 * 64;
constexpr int SM_P    = SM_S + 2 * 520 * 4;
constexpr int SM_Q    = SM_P + 2 * 272 * 4;
constexpr int SM_XN   = SM_Q + 2 * 264 * 2;
constexpr int SM_X    = SM_XN + 2 * XROW;
constexpr int SM_RED  = SM_X + 1792 + 32;
constexpr int SM_STAT = SM_RED + 7 * 64 * 4;
constexpr int SM_OB   = SM_STAT + 2 * 8 * 2 * 4;
constexpr int SM_H    = SM_OB + 2 * 16 * 4;
constexpr int SM_T0   = SM_H + 2 * 8 * 4;
constexpr int SM_BAR  = SM_T0 + 16;
constexpr int SM_TOTAL = SM_BAR + 2 * NBAR * 8;
static_assert(SM_Q % 16 == 0 && SM_XN % 16 == 0 && SM_X % 16 == 0 && SM_OB % 16 == 0 && SM_P % 16 == 0 && SM_T0 % 16 == 0, "align");
static_assert(S_GU + 13 <= S_V + FFN_ST, "the gate/up strip lands with stage S_GU + 13");
static_assert(2 * NS >= 16, "K stage -> slot mapping");

constexpr int SPIN_LIMIT = 1 << 22;

struct Scratch {
    uint4    part[NCTA * 2 * 8 * 8];
    uint4    outp[NRED * NCTA * 4];
    uint4    q[8 * 2 * 128];
    uint2    ml[NCTA * 4];
    uint2    prog[4 * 32 * 4];
    unsigned epoch[NCTA * 8];
};
__device__ Scratch g_scratch;

#define TL(i)

__device__ __forceinline__ void mbar_init(uint32_t bar, uint32_t cnt) {
    asm volatile("mbarrier.init.shared::cta.b64 [%0], %1;" :: "r"(bar), "r"(cnt) : "memory");
}
__device__ __forceinline__ void mbar_arrive(uint32_t bar, uint32_t cnt) {
    asm volatile("mbarrier.arrive.shared::cta.b64 _, [%0], %1;" :: "r"(bar), "r"(cnt) : "memory");
}
__device__ __forceinline__ bool mbar_try(uint32_t bar) {
    uint32_t ok;
    asm volatile("{\n.reg .pred p;\nmbarrier.try_wait.parity.shared::cta.b64 p, [%1], 0;\nselp.u32 %0, 1, 0, p;\n}"
                 : "=r"(ok) : "r"(bar) : "memory");
    return ok;
}
__device__ __forceinline__ uint32_t time_ns() { uint32_t t; asm volatile("mov.u32 %0, %globaltimer_lo;" : "=r"(t)); return t; }
__device__ __forceinline__ void wait_until(uint32_t t0, uint32_t dt) { while (time_ns() - t0 < dt) {} }
__device__ __forceinline__ void mbar_wait(uint32_t bar) {
    asm volatile("{\n.reg .pred p;\nWAIT_LOOP:\nmbarrier.try_wait.parity.shared::cta.b64 p, [%0], 0;\n@!p bra WAIT_LOOP;\n}" :: "r"(bar) : "memory");
}
__device__ __forceinline__ void cp_async16_strip(uint32_t dst, const void* src) {
    asm volatile("cp.async.cg.shared.global.L2::128B [%0], [%1], 16;" :: "r"(dst), "l"(src) : "memory");
}
__device__ __forceinline__ void cp_async16_stream(uint32_t dst, const void* src) {
    asm volatile("{\n.reg .b64 pol;\ncreatepolicy.fractional.L2::evict_first.b64 pol, 1.0;\n"
                 "cp.async.cg.shared.global.L2::cache_hint [%0], [%1], 16, pol;\n}" :: "r"(dst), "l"(src) : "memory");
}
__device__ __forceinline__ void cp_async_arrive(uint32_t bar) {
    asm volatile("cp.async.mbarrier.arrive.noinc.shared::cta.b64 [%0];" :: "r"(bar) : "memory");
}
__device__ __forceinline__ void bar_sync(int id, int n)   { asm volatile("bar.sync %0, %1;" :: "r"(id), "r"(n) : "memory"); }
__device__ __forceinline__ void bar_arrive(int id, int n) { asm volatile("bar.arrive %0, %1;" :: "r"(id), "r"(n) : "memory"); }

__device__ __forceinline__ uint2 ld_poll2(const void* p) {
    uint2 v;
    asm volatile("ld.relaxed.gpu.global.v2.u32 {%0,%1}, [%2];" : "=r"(v.x), "=r"(v.y) : "l"(p) : "memory");
    return v;
}
__device__ __forceinline__ uint4 ld_poll4(const void* p) {
    uint4 v;
    asm volatile("ld.relaxed.gpu.global.v4.u32 {%0,%1,%2,%3}, [%4];" : "=r"(v.x), "=r"(v.y), "=r"(v.z), "=r"(v.w) : "l"(p) : "memory");
    return v;
}
__device__ __forceinline__ void st_pub4(void* p, uint4 v) {
    asm volatile("st.relaxed.gpu.global.v4.u32 [%0], {%1,%2,%3,%4};" :: "l"(p), "r"(v.x), "r"(v.y), "r"(v.z), "r"(v.w) : "memory");
}
__device__ __forceinline__ void st_pub2(void* p, uint32_t a, uint32_t b) {
    asm volatile("st.relaxed.gpu.global.v2.u32 [%0], {%1,%2};" :: "l"(p), "r"(a), "r"(b) : "memory");
}
__device__ __forceinline__ void st_pub1(void* p, uint32_t a) {
    asm volatile("st.relaxed.gpu.global.u32 [%0], %1;" :: "l"(p), "r"(a) : "memory");
}
__device__ __forceinline__ uint32_t tagf(float v, uint32_t tag) {
    uint32_t r;
    asm("lop3.b32 %0, %1, 0xfffffffe, %2, 0xEA;" : "=r"(r) : "r"(__float_as_uint(v)), "r"(tag));
    return r;
}
__device__ __forceinline__ uint32_t pin(uint32_t v) {
    uint32_t r;
    asm volatile("shfl.sync.bfly.b32 %0, %1, 0, 0x1f, 0xffffffff;" : "=r"(r) : "r"(v));
    return r;
}
template <class T>
__device__ __forceinline__ T* pin(T* p) {
    const uint64_t u = reinterpret_cast<uint64_t>(p);
    return reinterpret_cast<T*>(((uint64_t)pin((uint32_t)(u >> 32)) << 32) | pin((uint32_t)u));
}
__device__ __forceinline__ void sts32(uint32_t addr, uint32_t v) { asm volatile("st.shared.u32 [%0], %1;" :: "r"(addr), "r"(v) : "memory"); }
__device__ __forceinline__ float lds32(uint32_t addr) { float v; asm volatile("ld.shared.f32 %0, [%1];" : "=f"(v) : "r"(addr) : "memory"); return v; }
__device__ __forceinline__ uint4 lds128(uint32_t addr) {
    uint4 v;
    asm volatile("ld.shared.v4.u32 {%0,%1,%2,%3}, [%4];" : "=r"(v.x), "=r"(v.y), "=r"(v.z), "=r"(v.w) : "r"(addr) : "memory");
    return v;
}
__device__ __forceinline__ uint32_t bad2(uint32_t a, uint32_t b, uint32_t tag) {
    uint32_t r;
    asm("lop3.b32 %0, %1, %2, %3, 0x7E;" : "=r"(r) : "r"(a), "r"(b), "r"(tag));
    return r;
}
__device__ __forceinline__ uint32_t bad4(const uint4& v, uint32_t tag) { return bad2(v.x, v.y, tag) | bad2(v.z, v.w, tag); }
__device__ __forceinline__ bool warp_bad(uint32_t bad) { return __any_sync(0xffffffffu, bad & 1u); }

__device__ __forceinline__ void poll4(float (&f)[2][4], const uint4* p, uint32_t tag, const float (&w)[4]) {
    asm volatile("{\n"
                 ".reg .pred p0, p1, p2, p3, q;\n"
                 ".reg .b32 a, b, m, it, v<16>;\n"
                 "setp.eq.u32 p0, 0, 0;\nsetp.eq.u32 p1, 0, 0;\nsetp.eq.u32 p2, 0, 0;\nsetp.eq.u32 p3, 0, 0;\n"
                 "mov.u32 it, %14;\n"
                 "POLL_LOOP:\n"
                 "@p0 ld.relaxed.gpu.global.v4.u32 {v0,v1,v2,v3}, [%8];\n"
                 "@p1 ld.relaxed.gpu.global.v4.u32 {v4,v5,v6,v7}, [%8+512];\n"
                 "@p2 ld.relaxed.gpu.global.v4.u32 {v8,v9,v10,v11}, [%8+1024];\n"
                 "@p3 ld.relaxed.gpu.global.v4.u32 {v12,v13,v14,v15}, [%8+1536];\n"
                 "sub.u32 it, it, 1;\n"
                 "min.u32 m, it, 1;\n"
                 "lop3.b32 a, v0, v1, %9, 0x7E;\nlop3.b32 b, v2, v3, %9, 0x7E;\nlop3.b32 a, a, b, m, 0xA8;\nsetp.ne.u32 p0, a, 0;\n"
                 "lop3.b32 a, v4, v5, %9, 0x7E;\nlop3.b32 b, v6, v7, %9, 0x7E;\nlop3.b32 a, a, b, m, 0xA8;\nsetp.ne.u32 p1, a, 0;\n"
                 "lop3.b32 a, v8, v9, %9, 0x7E;\nlop3.b32 b, v10, v11, %9, 0x7E;\nlop3.b32 a, a, b, m, 0xA8;\nsetp.ne.u32 p2, a, 0;\n"
                 "lop3.b32 a, v12, v13, %9, 0x7E;\nlop3.b32 b, v14, v15, %9, 0x7E;\nlop3.b32 a, a, b, m, 0xA8;\nsetp.ne.u32 p3, a, 0;\n"
                 "or.pred q, p0, p1;\nor.pred q, q, p2;\nor.pred q, q, p3;\n"
                 "mul.f32 %0, v0, %10;\nmul.f32 %1, v1, %10;\nmul.f32 %2, v2, %10;\nmul.f32 %3, v3, %10;\n"
                 "mul.f32 %4, v8, %12;\nmul.f32 %5, v9, %12;\nmul.f32 %6, v10, %12;\nmul.f32 %7, v11, %12;\n"
                 "vote.sync.any.pred q, q, 0xffffffff;\n"
                 "fma.rn.f32 %0, v4, %11, %0;\nfma.rn.f32 %1, v5, %11, %1;\nfma.rn.f32 %2, v6, %11, %2;\nfma.rn.f32 %3, v7, %11, %3;\n"
                 "fma.rn.f32 %4, v12, %13, %4;\nfma.rn.f32 %5, v13, %13, %5;\nfma.rn.f32 %6, v14, %13, %6;\nfma.rn.f32 %7, v15, %13, %7;\n"
                 "@q bra POLL_LOOP;\n"
                 "}"
                 : "=&f"(f[0][0]), "=&f"(f[0][1]), "=&f"(f[0][2]), "=&f"(f[0][3]), "=&f"(f[1][0]), "=&f"(f[1][1]), "=&f"(f[1][2]), "=&f"(f[1][3])
                 : "l"(p), "r"(tag), "f"(w[0]), "f"(w[1]), "f"(w[2]), "f"(w[3]), "n"(SPIN_LIMIT) : "memory");
}

__device__ __forceinline__ void ldsm4(uint32_t addr, uint32_t (&a)[4]) {
    asm volatile("ldmatrix.sync.aligned.m8n8.x4.shared.b16 {%0,%1,%2,%3}, [%4];" : "=r"(a[0]), "=r"(a[1]), "=r"(a[2]), "=r"(a[3]) : "r"(addr) : "memory");
}
__device__ __forceinline__ void ldsm4t(uint32_t addr, uint32_t (&a)[4]) {
    asm volatile("ldmatrix.sync.aligned.m8n8.x4.trans.shared.b16 {%0,%1,%2,%3}, [%4];" : "=r"(a[0]), "=r"(a[1]), "=r"(a[2]), "=r"(a[3]) : "r"(addr) : "memory");
}
__device__ __forceinline__ void mma16816(float (&c)[4], const uint32_t (&a)[4], uint32_t b0, uint32_t b1) {
    asm volatile("mma.sync.aligned.m16n8k16.row.col.f32.bf16.bf16.f32 {%0,%1,%2,%3}, {%4,%5,%6,%7}, {%8,%9}, {%0,%1,%2,%3};"
                 : "+f"(c[0]), "+f"(c[1]), "+f"(c[2]), "+f"(c[3]) : "r"(a[0]), "r"(a[1]), "r"(a[2]), "r"(a[3]), "r"(b0), "r"(b1));
}
__device__ __forceinline__ float bf_lo(uint32_t u) { return __uint_as_float(u << 16); }
__device__ __forceinline__ float bf_hi(uint32_t u) { return __uint_as_float(u & 0xffff0000u); }
__device__ __forceinline__ float rbf(float v) { return __bfloat162float(__float2bfloat16_rn(v)); }
__device__ __forceinline__ uint32_t pack_bf(float lo, float hi) {
    uint32_t r;
    asm("cvt.rn.bf16x2.f32 %0, %1, %2;" : "=r"(r) : "f"(hi), "f"(lo));
    return r;
}
__device__ __forceinline__ float sel4(const float (&c)[4], int t) {
    float a = (t & 1) ? c[1] : c[0];
    float b = (t & 1) ? c[3] : c[2];
    return (t & 2) ? b : a;
}
__device__ __forceinline__ float ex2(float x) { float y; asm("ex2.approx.ftz.f32 %0, %1;" : "=f"(y) : "f"(x)); return y; }
__device__ __forceinline__ float sqrt_approx(float x) { float y; asm("sqrt.approx.f32 %0, %1;" : "=f"(y) : "f"(x)); return y; }

__host__ __device__ constexpr uint32_t slot_of(int s) { return SM_RING + (s % NS) * SLOT; }

__device__ __forceinline__ void layernorm(unsigned char* smem, int lane) {
    uint32_t xs[2][7];
#pragma unroll
    for (int b = 0; b < 2; b++)
#pragma unroll
        for (int i = 0; i < 7; i++) xs[b][i] = reinterpret_cast<const uint32_t*>(smem + SM_X)[b * (D_MODEL / 2) + i * 32 + lane];
#pragma unroll
    for (int b = 0; b < 2; b++) {
        float sum = 0.f;
#pragma unroll
        for (int i = 0; i < 7; i++) sum += bf_lo(xs[b][i]) + bf_hi(xs[b][i]);
#pragma unroll
        for (int o = 16; o > 0; o >>= 1) sum += __shfl_xor_sync(0xffffffffu, sum, o);
        const float mean = sum * (1.0f / D_MODEL);
        float sq = 0.f;
#pragma unroll
        for (int i = 0; i < 7; i++) {
            const float d0 = bf_lo(xs[b][i]) - mean, d1 = bf_hi(xs[b][i]) - mean;
            sq = fmaf(d0, d0, fmaf(d1, d1, sq));
        }
#pragma unroll
        for (int o = 16; o > 0; o >>= 1) sq += __shfl_xor_sync(0xffffffffu, sq, o);
        const float mb = rbf(mean);
        const float sd = rbf(sqrt_approx(rbf(rbf(sq * (1.0f / D_MODEL)) + 1e-5f)));
#pragma unroll
        for (int i = 0; i < 7; i++)
            reinterpret_cast<uint32_t*>(smem + SM_XN + b * XROW)[i * 32 + lane] =
                pack_bf(__fdividef(rbf(bf_lo(xs[b][i]) - mb), sd), __fdividef(rbf(bf_hi(xs[b][i]) - mb), sd));
    }
}

__device__ __forceinline__ void strip_partial(uint32_t sb, uint32_t strip, unsigned char* smem, int warp, int lane) {
    float c[2][2][4];
#pragma unroll
    for (int n = 0; n < 2; n++)
#pragma unroll
        for (int e = 0; e < 4; e++) c[n][0][e] = c[n][1][e] = 0.f;
    const uint32_t ba = sb + SM_XN + (lane & 1) * XROW + (lane >> 3) * 16 + warp * 128;
    const uint32_t aa = sb + strip + (warp * 64 + (lane & 7) + (lane >> 4) * 8) * 64 + (((lane >> 3) & 1) ^ ((lane & 7) >> 1)) * 16;
#pragma unroll
    for (int k2 = 0; k2 < 2; k2++) {
        uint32_t b[4];
        ldsm4(ba + k2 * 64, b);
#pragma unroll
        for (int n = 0; n < 2; n++) {
            uint32_t a0[4], a1[4];
            ldsm4t((aa ^ (n * 32)) + k2 * 2048, a0);
            ldsm4t((aa ^ (n * 32)) + k2 * 2048 + 1024, a1);
            mma16816(c[n][0], a0, b[0], b[1]);
            mma16816(c[n][1], a1, b[2], b[3]);
        }
    }
    float* red = reinterpret_cast<float*>(smem + SM_RED) + warp * 64 + lane;
#pragma unroll
    for (int n = 0; n < 2; n++) red[n * 32] = sel4(c[n][0], lane & 3) + sel4(c[n][1], lane & 3);
}
__device__ __forceinline__ float strip_sum(const unsigned char* smem, int idx) {
    const float* red = reinterpret_cast<const float*>(smem + SM_RED) + idx;
    return ((red[0] + red[64]) + (red[128] + red[192])) + ((red[256] + red[320]) + red[384]);
}

__device__ __forceinline__ uint32_t time_base(uint32_t sb, int i) {
    uint32_t t;
    asm volatile("ld.volatile.shared.u32 %0, [%1];" : "=r"(t) : "r"(sb + SM_T0 + 4 * i) : "memory");
    return t;
}
__device__ __forceinline__ void wait_clock(uint32_t sb, int i, uint32_t dt) { while (time_ns() - time_base(sb, i) < dt) {} }

struct Prod {
    uint32_t sb, kvdst, sdst;
    const char *k, *v;
    const __nv_bfloat16* gu;
    bool ffn;
};
__host__ __device__ constexpr int bytes_before(int s) { return 28672 + s * 16384 + (s <= S_GU ? 0 : s < S_GU + 14 ? s - S_GU : 14) * 1792; }
__host__ __device__ constexpr int issue_time(int s) { return (int)((long long)bytes_before(s) * PACE_DT / 16384) - PACE_LEAD; }

template <int S>
__device__ __forceinline__ void produce(Prod& p) {
    if constexpr (S < NSTAGE) {
        if constexpr (S >= NS) mbar_wait(p.sb + SM_BAR + (NBAR + S - NS) * 8);
        wait_clock(p.sb, 0, issue_time(S));
        const char* src = (S < S_V ? p.k : p.v) + (S & 15) * (8 * SLOT);
#pragma unroll
        for (int i = 0; i < 8; i++) cp_async16_stream((p.kvdst ^ ((i & 1) * 64)) + slot_of(S) + i * 2048, src + i * 2048);
        if constexpr (S >= S_GU && S < S_GU + 14) {
            if (p.ffn) cp_async16_strip(p.sdst + (S - S_GU) * 2048, p.gu + (size_t)(S - S_GU) * 32 * FF);
        }
        cp_async_arrive(p.sb + SM_BAR + S * 8);
        produce<S + 1>(p);
    }
}

__device__ __forceinline__ void fetch16(uint32_t dst, const char* src) {
#pragma unroll
    for (int i = 0; i < 4; i++)
        asm volatile("cp.async.cg.shared.global [%0], [%1], 16;" :: "r"((dst ^ (((i & 1) ^ (i >> 1)) * 64)) + i * 512), "l"(src + i * (4 * 896)) : "memory");
}
template <int PENDING, int OFF>
__device__ __forceinline__ void frag16(uint32_t (&a)[4][4], uint32_t addr) {
    asm volatile("cp.async.wait_group %0;" :: "n"(PENDING) : "memory");
    __syncwarp();
#pragma unroll
    for (int m = 0; m < 4; m++) ldsm4t((addr ^ (m * 32)) + OFF, a[m]);
}

__device__ __forceinline__ void load_x(uint32_t sb, const void* x, const void* epoch) {
    const uint32_t full0 = sb + SM_BAR;
    mbar_init(full0 + B_X * 8, 1);
    asm volatile("fence.mbarrier_init.release.cluster;" ::: "memory");
    asm volatile("mbarrier.arrive.expect_tx.shared::cta.b64 _, [%0], %1;" :: "r"(full0 + B_X * 8), "r"(1792 + EPB) : "memory");
    asm volatile("cp.async.bulk.shared::cluster.global.mbarrier::complete_tx::bytes [%0], [%1], %2, [%3];"
                 :: "r"(sb + SM_X), "l"(x), "r"(1792), "r"(full0 + B_X * 8) : "memory");
    asm volatile("cp.async.bulk.shared::cluster.global.mbarrier::complete_tx::bytes [%0], [%1], %2, [%3];"
                 :: "r"(sb + SM_X + 1792), "l"(epoch), "r"(EPB), "r"(full0 + B_X * 8) : "memory");
}

enum { BAR_OB = 1, BAR_CONS = 2, BAR_LN = 3, BAR_FF = 4, BAR_FIN = 5, BAR_H = 6 };

__global__ void __launch_bounds__(NTHREADS, 1)
fused_decode_kernel(const __nv_bfloat16* __restrict__ wq, const __nv_bfloat16* __restrict__ kc, const __nv_bfloat16* __restrict__ x,
                    Scratch* __restrict__ scr, const __nv_bfloat16* __restrict__ vc, const __nv_bfloat16* __restrict__ wo,
                    const __nv_bfloat16* __restrict__ wg, const __nv_bfloat16* __restrict__ wu, const __nv_bfloat16* __restrict__ wd,
                    __nv_bfloat16* __restrict__ out) {
    extern __shared__ __align__(128) unsigned char smem[];
    const uint32_t sb = (uint32_t)__cvta_generic_to_shared(smem);
    const int tid = threadIdx.x, lane = tid & 31;
    const int cta = blockIdx.x;
    const uint32_t full0 = sb + SM_BAR, done0 = full0 + NBAR * 8;
    const uint32_t t0 = time_ns();
    if (tid < 224) {
        const int row = (tid >> 5) * 64 + (lane >> 2);
        const char* src = reinterpret_cast<const char*>(wq) + (uint32_t)(row * (QCOLS * 2) + cta * 64 + (lane & 3) * 16);
        const uint32_t dst = sb + SM_STRIP + row * 64 + ((lane & 3) ^ (lane >> 3)) * 16;
#pragma unroll
        for (int i = 0; i < 8; i++) cp_async16_strip(dst + i * 512, src + i * (8 * QCOLS * 2));
    }
    const int warp = __shfl_sync(0xffffffffu, tid >> 5, 0);
    const int hkv = cta >> 4, j = cta & 15, bat = j >> 3, sp = j & 7;
    const int g = lane >> 2, t = lane & 3;

    if (warp < 8) {
        if (warp == 0) TL(0);
        if (tid == 224) load_x(sb, x, &scr->epoch[cta * 8]);
        __syncthreads();
        mbar_wait(full0 + B_X * 8);
        const uint32_t epoch = *reinterpret_cast<const uint32_t*>(smem + SM_X + 1792);
        const uint32_t tag = pin((epoch + 1) & 1);
        uint32_t* qdst = reinterpret_cast<uint32_t*>(scr->q) + (hkv * 2 + (t & 1)) * 512 + j * 32 + warp * 16 + g + 8 * (t >> 1);
        if (warp == 7) {
            layernorm(smem, lane);
            bar_arrive(BAR_LN, 256);
            TL(13);
        } else {
            asm volatile("cp.async.wait_all;" ::: "memory");
            bar_sync(BAR_LN, 256);
            strip_partial(sb, SM_STRIP, smem, warp, lane);
        }
        bar_sync(BAR_CONS, 256);
        if (warp < 2) {
            st_pub1(qdst, (pack_bf(0.f, strip_sum(smem, tid)) & 0xffff0000u) | tag);
            if (warp == 0) TL(6);
        } else if (warp >= 4) {
            const int i = tid - 128;
            const uint4* qp = scr->q + (hkv * 2 + bat) * 128 + i;
            wait_until(t0, Q_T);
            uint4 v;
            int it = 0;
            do {
                v = ld_poll4(qp);
                if (++it > SPIN_LIMIT) __trap();
            } while (warp_bad(bad4(v, tag)));
            *reinterpret_cast<uint2*>(smem + SM_Q + (i >> 6) * 528 + (i & 63) * 8) =
                make_uint2(__byte_perm(v.x, v.y, 0x7632), __byte_perm(v.z, v.w, 0x7632));
        }
        bar_sync(BAR_CONS, 256);
        if (tid == 96) scr->epoch[cta * 8] = epoch + 1;
        if (warp == 0) TL(7);
        {
            uint32_t qf[8][4];
#pragma unroll
            for (int k2 = 0; k2 < 8; k2++) ldsm4(sb + SM_Q + (lane & 1) * 528 + k2 * 64 + (lane >> 3) * 16, qf[k2]);
            const int mt = warp & 1;
            const uint32_t aoff = (16 * mt + (lane & 15)) * 512 + ((lane >> 4) ^ (lane & 7)) * 16;
            float* sc = reinterpret_cast<float*>(smem + SM_S) + (t & 1) * 520 + (g >> 1) * 8 + (2 * mt + (t >> 1)) * 2 + (g & 1);
#pragma unroll 1
            for (int k = warp >> 1; k < 16; k += 4) {
                const int s = S_K + k;
                mbar_wait(full0 + s * 8);
                const uint32_t base = sb + SM_RING + (s >= NS ? s - NS : s) * SLOT + aoff;
                float c0[4] = {0.f, 0.f, 0.f, 0.f}, c1[4] = {0.f, 0.f, 0.f, 0.f};
#pragma unroll
                for (int k2 = 0; k2 < 8; k2++) {
                    uint32_t a0[4], a1[4];
                    ldsm4((base ^ ((k2 & 1) * 64)) + (k2 >> 1) * 128, a0);
                    ldsm4((base ^ ((k2 & 1) * 64 + 32)) + (k2 >> 1) * 128, a1);
                    mma16816(c0, a0, qf[k2][0], qf[k2][1]);
                    mma16816(c1, a1, qf[k2][2], qf[k2][3]);
                }
                __syncwarp();
                if (lane == 0) mbar_arrive(done0 + s * 8, 4);
                sc[k * 32] = rbf(sel4(c0, t) + sel4(c1, t));
            }
        }
        bar_sync(BAR_CONS, 256);
        if (warp == 0) TL(8);
        {
            constexpr float C = 0.0625f * 1.4426950408889634f;
            const float* sc = reinterpret_cast<const float*>(smem + SM_S);
            float* stat = reinterpret_cast<float*>(smem + SM_STAT);
            const float2 s0 = *reinterpret_cast<const float2*>(sc + 2 * tid);
            const float2 s1 = *reinterpret_cast<const float2*>(sc + 520 + 2 * tid);
            float m0 = fmaxf(s0.x, s0.y), m1 = fmaxf(s1.x, s1.y);
#pragma unroll
            for (int o = 16; o > 0; o >>= 1) {
                m0 = fmaxf(m0, __shfl_xor_sync(0xffffffffu, m0, o));
                m1 = fmaxf(m1, __shfl_xor_sync(0xffffffffu, m1, o));
            }
            if (lane == 0) *reinterpret_cast<float2*>(stat + warp * 2) = make_float2(m0, m1);
            bar_sync(BAR_CONS, 256);
#pragma unroll
            for (int w = 0; w < 8; w++) {
                const float2 mm = *reinterpret_cast<const float2*>(stat + w * 2);
                m0 = fmaxf(m0, mm.x); m1 = fmaxf(m1, mm.y);
            }
            const float p00 = ex2((s0.x - m0) * C), p01 = ex2((s0.y - m0) * C);
            const float p10 = ex2((s1.x - m1) * C), p11 = ex2((s1.y - m1) * C);
            uint32_t* ps = reinterpret_cast<uint32_t*>(smem + SM_P);
            ps[tid] = pack_bf(p00, p01);
            ps[272 + tid] = pack_bf(p10, p11);
            float l0 = p00 + p01, l1 = p10 + p11;
#pragma unroll
            for (int o = 16; o > 0; o >>= 1) {
                l0 += __shfl_xor_sync(0xffffffffu, l0, o);
                l1 += __shfl_xor_sync(0xffffffffu, l1, o);
            }
            if (lane == 0) *reinterpret_cast<float2*>(stat + 16 + warp * 2) = make_float2(l0, l1);
            bar_sync(BAR_CONS, 256);
            if (tid < 4) {
                float l = 0.f;
#pragma unroll
                for (int w = 0; w < 8; w++) l += stat[16 + w * 2 + (tid & 1)];
                st_pub2(scr->ml + cta * 4 + tid, tagf(((tid & 1) ? m1 : m0) * C, tag), tagf(l, tag));
            }
        }
        if (warp == 0) TL(9);
        float wgt[2] = {0.f, 0.f};
        {
            float o0[4] = {0.f, 0.f, 0.f, 0.f}, o1[4] = {0.f, 0.f, 0.f, 0.f};
            float o2[4] = {0.f, 0.f, 0.f, 0.f}, o3[4] = {0.f, 0.f, 0.f, 0.f};
            const uint32_t aoff = ((lane & 7) + (lane >> 4) * 8) * 512 + ((warp * 4 + ((lane >> 3) & 1) * 2) ^ (lane & 7)) * 16;
            const uint4* ps = reinterpret_cast<const uint4*>(smem + SM_P + (g & 1) * 272 * 4) + t;
            uint32_t* dst = reinterpret_cast<uint32_t*>(scr->part) + ((size_t)(hkv * 16 + (t & 1) * 8 + warp) * 16 + j) * 32 +
                            (4 * (g & 3) + (t & 2) + (g >> 2)) * 2;
#pragma unroll
            for (int k = 0; k < 16; k++) {
                const uint4 pa = ps[k * 4];
                mbar_wait(full0 + (S_V + k) * 8);
                uint32_t a[4][4];
#pragma unroll
                for (int i = 0; i < 4; i++) ldsm4t(sb + (aoff ^ ((i & 1) * 16)) + slot_of(S_V + k) + (i >> 1) * 8192, a[i]);
                mma16816(o0, a[0], pa.x, pa.y);
                mma16816(o1, a[1], pa.x, pa.y);
                mma16816(o2, a[2], pa.z, pa.w);
                mma16816(o3, a[3], pa.z, pa.w);
                if (S_V + k + NS < NSTAGE + 3) {
                    __syncwarp();
                    if (lane == 0) mbar_arrive(done0 + (S_V + k) * 8, 1);
                }
                if (k == FFN_ST && warp < 7) {
                    strip_partial(sb, SM_STRIP, smem, warp, lane);
                    bar_arrive(BAR_FF, 256);
                }
                if (k == FFN_ST && warp == 7) {
                    const uint2* mlp = scr->ml + (hkv * 16 + g) * 4 + (j >> 3);
                    uint2 a, b;
                    int it = 0;
                    do {
                        a = ld_poll2(mlp); b = ld_poll2(mlp + 32);
                        if (++it > SPIN_LIMIT) __trap();
                    } while (warp_bad(bad2(a.x, a.y, tag) | bad2(b.x, b.y, tag)));
                    float m[2] = {__uint_as_float(a.x), __uint_as_float(b.x)};
                    float l[2] = {__uint_as_float(a.y), __uint_as_float(b.y)};
#pragma unroll
                    for (int bb = 0; bb < 2; bb++) {
                        float M = m[bb];
                        M = fmaxf(M, __shfl_xor_sync(0xffffffffu, M, 4));
                        M = fmaxf(M, __shfl_xor_sync(0xffffffffu, M, 8));
                        M = fmaxf(M, __shfl_xor_sync(0xffffffffu, M, 16));
                        const float e = ex2(m[bb] - M);
                        float L = e * l[bb];
                        L += __shfl_xor_sync(0xffffffffu, L, 4);
                        L += __shfl_xor_sync(0xffffffffu, L, 8);
                        L += __shfl_xor_sync(0xffffffffu, L, 16);
                        wgt[bb] = __fdividef(e, L);
                    }
                    bar_sync(BAR_FF, 256);
                    float ga = rbf(strip_sum(smem, lane));
                    ga *= (ga > 0.f ? 1.f : 0.f);
                    const float hv = ga * rbf(strip_sum(smem, 32 + lane));
                    const uint32_t w = pack_bf(hv, __shfl_xor_sync(0xffffffffu, hv, 2));
                    if (!(t & 2)) reinterpret_cast<uint32_t*>(smem + SM_H)[(t & 1) * 8 + (g & 3) * 2 + (g >> 2)] = w;
                    bar_arrive(BAR_H, 256);
                }
                if (k == PRE_ST) st_pub2(dst, tag ^ 1, tag ^ 1);
            }
            const float v0 = sel4(o0, t) + sel4(o2, t), v1 = sel4(o1, t) + sel4(o3, t);
            st_pub2(dst, tagf(v0, tag), tagf(v1, tag));
        }
        if (warp == 0) TL(10);
        if (warp == 7) {
            const uint4* pp = pin(scr->part + (size_t)cta * 128 + lane);
            const uint32_t obaddr = pin(sb + SM_OB + (lane >> 4) * 64 + (lane & 7) * 8 + ((lane >> 3) & 1) * 4), ll = pin(lane);
            float w[4];
#pragma unroll
            for (int i = 0; i < 4; i++) w[i] = __shfl_sync(0xffffffffu, wgt[i >> 1], ((i & 1) * 4 + (lane >> 3)) * 4);
            wait_until(time_base(sb, 2), TN_E2);
            TL(2);
            float f[2][4];
            poll4(f, pp, tag, w);
            TL(3);
            const bool h16 = ll & 16, h8 = ll & 8;
            float r4[4], r2[2];
#pragma unroll
            for (int e = 0; e < 4; e++) r4[e] = (h16 ? f[1][e] : f[0][e]) + __shfl_xor_sync(0xffffffffu, h16 ? f[0][e] : f[1][e], 16);
#pragma unroll
            for (int e = 0; e < 2; e++) r2[e] = (h8 ? r4[2 + e] : r4[e]) + __shfl_xor_sync(0xffffffffu, h8 ? r4[e] : r4[2 + e], 8);
            sts32(obaddr, pack_bf(r2[0], r2[1]));
            bar_arrive(BAR_OB, 256);
            TL(14);
        } else if (warp < 4 && (cta & 1) == 0 && cta < 2 * NRED) {
            const uint4* op = pin(scr->outp + (size_t)(cta >> 1) * (NCTA * 4) + warp * 128 + lane);
            const int oidx = (t & 1) * D_MODEL + hkv * 64 + (lane >> 3) * 16 + (j >> 1) + (t >> 1) * 8;
            const float xv = __bfloat162float(reinterpret_cast<const __nv_bfloat16*>(smem + SM_X)[oidx]);
            __nv_bfloat16* optr = pin(out + oidx);
            const uint32_t red = pin(sb + SM_S + tid * 4), ll = pin(lane);
            const float one[4] = {1.f, 1.f, 1.f, 1.f};
            float f[2][4], a[4];
            wait_until(time_base(sb, 3), TN_E3);
            poll4(f, op, tag, one);
            if (warp == 0) TL(4);
#pragma unroll
            for (int e = 0; e < 4; e++) a[e] = f[0][e] + f[1][e];
            const bool h16 = ll & 16, h8 = ll & 8;
            float r2[2];
#pragma unroll
            for (int e = 0; e < 2; e++) r2[e] = (h16 ? a[2 + e] : a[e]) + __shfl_xor_sync(0xffffffffu, h16 ? a[e] : a[2 + e], 16);
            float r = (h8 ? r2[1] : r2[0]) + __shfl_xor_sync(0xffffffffu, h8 ? r2[0] : r2[1], 8);
            r += __shfl_xor_sync(0xffffffffu, r, 4);
            if (warp != 0) {
                sts32(red, __float_as_uint(r));
                bar_arrive(BAR_FIN, 128);
            } else {
                bar_sync(BAR_FIN, 128);
                r = ((xv + r) + lds32(red + 128)) + (lds32(red + 256) + lds32(red + 384));
                asm volatile("st.global.u16 [%0], %1;" :: "l"(optr), "h"(__bfloat16_as_ushort(__float2bfloat16_rn(r))) : "memory");
                TL(5);
            }
        }
    } else if (warp < 15) {
        const int pt = tid - 256, pw = warp - 8;
        const char* pdn = reinterpret_cast<const char*>(wd) + (size_t)cta * 14336 + (lane >> 3) * 896 + pw * 128 + (lane & 7) * 16;
        const char* pwo = reinterpret_cast<const char*>(wo) + (size_t)cta * 28672 + (lane >> 3) * 896 + pw * 128 + (lane & 7) * 16;
        if (pw < 4) {
            if (lane == 0) {
                const int w = pw;
#pragma unroll
                for (int i = 0; i < 9; i++) {
                    if (w * 9 + i != B_X) mbar_init(full0 + (w * 9 + i) * 8, NPT);
                    mbar_init(done0 + (w * 9 + i) * 8, 8);
                }
            }
            Prod p;
            const size_t kvoff = ((size_t)(bat * 8 + hkv) * SK + (SK - WIN)) * DH * 2 + sp * SLOT + pt * 16;
            p.sb = sb;
            p.kvdst = (sb + pt * 16) ^ (pw * 16);
            p.sdst = sb + SM_STRIP + (pt >> 2) * 64 + ((pt & 3) ^ ((pt >> 3) & 3)) * 16;
            p.k = reinterpret_cast<const char*>(kc) + kvoff;
            p.v = reinterpret_cast<const char*>(vc) + kvoff;
            p.gu = ((pt & 2) ? wu : wg) + cta * 16 + (pt & 1) * 8 + (size_t)(pt >> 2) * FF;
            p.ffn = cta < NFFN;
            __syncthreads();
            produce<0>(p);
        } else {
            __syncthreads();
        }
        mbar_wait(full0 + B_X * 8);
        const uint32_t tag = pin((*reinterpret_cast<const uint32_t*>(smem + SM_X + 1792) + 1) & 1);
        if (pw == 4 && (cta & 3) == 0) {
#pragma unroll 1
            for (int i = 0; i < 4; i++) {
                uint32_t sum = 0;
#pragma unroll
                for (int k = 0; k < NM; k++) {
                    mbar_wait(full0 + (MEND - NM + 1 + k + 6 * i) * 8);
                    sum += time_ns() - t0;
                }
                if (lane < 4) st_pub2(&scr->prog[i * 128 + cta + lane], ((t0 + sum / NM) & ~1u) | tag, (t0 & ~1u) | tag);
            }
        }
        mbar_wait(done0 + (NSTAGE + 2 - NS) * 8);
        bar_sync(BAR_H, 256);
        const uint2 h = *reinterpret_cast<const uint2*>(smem + SM_H + (g & 1) * 32 + t * 8);
        const uint32_t ta = TN_A, td = TN_B;
        uint4* odst = scr->outp + ((size_t)(pt >> 2) * NCTA + cta) * 4 + t;
        st_pub4(odst, make_uint4(tag ^ 1, tag ^ 1, tag ^ 1, tag ^ 1));
        const uint32_t fdst = (sb + pw * 2048 + lane * 16) ^ ((lane >> 3) * 16);
        wait_clock(sb, 1, ta);
        if (cta < NFFN) fetch16(fdst + slot_of(NSTAGE), pdn);
        asm volatile("cp.async.commit_group;" ::: "memory");
        wait_clock(sb, 1, ta + td);
        fetch16(fdst + slot_of(NSTAGE + 1), pwo);
        asm volatile("cp.async.commit_group;" ::: "memory");
        wait_clock(sb, 1, ta + 2 * td);
        fetch16(fdst + slot_of(NSTAGE + 2), pwo + 14336);
        asm volatile("cp.async.commit_group;" ::: "memory");
        if (pw == 0) TL(1);
        float c[4][4];
#pragma unroll
        for (int m = 0; m < 4; m++)
#pragma unroll
            for (int e = 0; e < 4; e++) c[m][e] = 0.f;
        const int r7 = ((lane & 7) >> 1) + 4 * (lane >> 4);
        const uint32_t aoff = sb + pw * 2048 + (r7 + 8 * (lane & 1)) * 128 + (((lane >> 3) & 1) ^ r7 ^ ((lane & 1) << 2)) * 16;
        const uint32_t obaddr = pin(sb + SM_OB + (g & 1) * 64 + t * 16), tt = pin(t);
        uint32_t a0[4][4], a1[4][4];
        frag16<2, slot_of(NSTAGE)>(a0, aoff);
        if (cta < NFFN) {
#pragma unroll
            for (int m = 0; m < 4; m++) mma16816(c[m], a0[m], h.x, h.y);
        }
        frag16<1, slot_of(NSTAGE + 1)>(a1, aoff);
        bar_sync(BAR_OB, 256);
        const uint4 ob = lds128(obaddr);
#pragma unroll
        for (int m = 0; m < 4; m++) mma16816(c[m], a1[m], ob.x, ob.y);
        frag16<0, slot_of(NSTAGE + 2)>(a0, aoff);
#pragma unroll
        for (int m = 0; m < 4; m++) mma16816(c[m], a0[m], ob.z, ob.w);
        uint4 r;
        r.x = tagf(sel4(c[0], tt), tag); r.y = tagf(sel4(c[1], tt), tag);
        r.z = tagf(sel4(c[2], tt), tag); r.w = tagf(sel4(c[3], tt), tag);
        st_pub4(odst, r);
        if (pw == 0) TL(12);
    } else if (warp == 15) {
        if (lane < 4) reinterpret_cast<uint32_t*>(smem + SM_T0)[lane] = t0;
        __syncthreads();
        mbar_wait(full0 + B_X * 8);
        const uint32_t tag = (*reinterpret_cast<const uint32_t*>(smem + SM_X + 1792) + 1) & 1;
#pragma unroll 1
        for (int i = 0; i < 4; i++) {
            mbar_wait(full0 + (MEND + 2 + 6 * i) * 8);
            uint2 v;
            int it = 0;
            do {
                v = ld_poll2(&scr->prog[i * 128 + lane * 4]);
                if (++it > SPIN_LIMIT) __trap();
            } while (warp_bad(bad2(v.x, v.y, tag)));
            const int nom = i == 0 ? M_NOM0 : i == 1 ? M_NOM1 : i == 2 ? M_NOM2 : M_NOM3;
            int base = (__reduce_add_sync(0xffffffffu, min(max((int)(v.x - t0), 0), 1 << 20)) >> 5) - nom;
            const int start = __reduce_add_sync(0xffffffffu, min(max((int)(v.y - t0), -(1 << 20)), 1 << 20)) >> 5;
            base = start + max(min(base - start, 2 * (base - start - DEAD)), 0);
            const int ahead = (lane == 0 ? nom : lane == 1 ? LATE_T : lane == 2 ? E2_T : E3_T - 150) - nom;
            const float rate = fminf(fmaxf(__fdividef((float)(base - start), (float)(nom - 500)), -0.01f), 0.045f);
            if (lane < 4) sts32(sb + SM_T0 + 4 * lane, t0 + base + (int)(rate * (float)ahead));
        }
        TL(15);
    }
}

}

extern "C" void kernel_launch(void* const* d_in, const int* in_sizes, int n_in, void* d_out, int out_size) {
    (void)in_sizes; (void)n_in; (void)out_size;
    static Scratch* scr = nullptr;
    if (!scr) {
        cudaFuncSetAttribute(fused_decode_kernel, cudaFuncAttributeMaxDynamicSharedMemorySize, SM_TOTAL);
        cudaGetSymbolAddress(reinterpret_cast<void**>(&scr), g_scratch);
    }
    typedef const __nv_bfloat16* P;
#define NGRID NCTA
    fused_decode_kernel<<<NGRID, NTHREADS, SM_TOTAL>>>((P)d_in[3], (P)d_in[1], (P)d_in[0], scr, (P)d_in[2], (P)d_in[4],
                                                      (P)d_in[6], (P)d_in[7], (P)d_in[8], (__nv_bfloat16*)d_out);
}
```

```cpp
#include <cuda_runtime.h>
#include <cuda_bf16.h>
#include <stdint.h>

namespace {

constexpr int PACE_DT = 636;
constexpr int PACE_LEAD = 350;
constexpr int LATE_T = 22400;
constexpr int LATE_DT = 400;
constexpr int Q_T = 4000;
constexpr int E2_T = 24050;
constexpr int E3_T = 24830;
constexpr int M_NOM0 = 5250;
constexpr int M_NOM1 = 9230;
constexpr int M_NOM2 = 13560;
constexpr int M_NOM3 = 17725;
constexpr int DEAD = 100;
constexpr int NM = 4;
constexpr int MEND = 6;
constexpr int NSLOT = 11;

constexpr int D_MODEL = 448;
constexpr int SK      = 32768;
constexpr int WIN     = 4096;
constexpr int DH      = 256;
constexpr int QCOLS   = 4096;
constexpr int FF      = 1792;
constexpr int NCTA    = 128;
constexpr int NFFN    = 112;
constexpr int NRED    = 56;
constexpr int NPT     = 128;
constexpr int NTHREADS = 512;

constexpr int NS     = NSLOT;
constexpr int SLOT   = 16384;
constexpr int XROW   = 912;
constexpr int S_K = 0, S_V = 16, NSTAGE = 32;
constexpr int S_GU   = NS;
constexpr int FFN_ST = 10;
constexpr int PRE_ST = 12;
constexpr int NBAR   = 36;
constexpr int B_X = NSTAGE;

constexpr int SM_RING  = 0;
constexpr int SM_STRIP = SM_RING + NS * SLOT;
constexpr int SM_S    = SM_STRIP + 448 * 64;
constexpr int SM_P    = SM_S + 2 * 520 * 4;
constexpr int SM_Q    = SM_P + 2 * 272 * 4;
constexpr int SM_XN   = SM_Q + 2 * 264 * 2;
constexpr int SM_X    = SM_XN + 2 * XROW;
constexpr int SM_RED  = SM_X + 1792 + 32;
constexpr int SM_STAT = SM_RED + 7 * 64 * 4;
constexpr int SM_OB   = SM_STAT + 2 * 8 * 2 * 4;
constexpr int SM_H    = SM_OB + 2 * 16 * 4;
constexpr int SM_T0   = SM_H + 2 * 8 * 4;
constexpr int SM_BAR  = SM_T0 + 16;
constexpr int SM_TOTAL = SM_BAR + 2 * NBAR * 8;
static_assert(SM_Q % 16 == 0 && SM_XN % 16 == 0 && SM_X % 16 == 0 && SM_OB % 16 == 0 && SM_P % 16 == 0 && SM_T0 % 16 == 0, "align");
static_assert(S_GU + 13 <= S_V + FFN_ST, "the gate/up strip lands with stage S_GU + 13");
static_assert(2 * NS >= 16, "K stage -> slot mapping");

constexpr int SPIN_LIMIT = 1 << 22;
constexpr float SCALE_LOG2E = 0.0625f * 1.4426950408889634f;

struct __align__(1024) Scratch {
    uint4    part[NCTA * 2 * 8 * 8];
    uint4    outp[NRED * NCTA * 4];
    uint4    q[8 * 2 * 128];
    uint2    ml[NCTA * 4];
    uint2    prog[4 * 32 * 4];
    unsigned epoch[NCTA * 8];
};
__device__ Scratch g_scratch;

__device__ __forceinline__ void mbar_init(uint32_t bar, uint32_t cnt) {
    asm volatile("mbarrier.init.shared::cta.b64 [%0], %1;" :: "r"(bar), "r"(cnt) : "memory");
}
__device__ __forceinline__ void mbar_arrive(uint32_t bar, uint32_t cnt) {
    asm volatile("mbarrier.arrive.shared::cta.b64 _, [%0], %1;" :: "r"(bar), "r"(cnt) : "memory");
}
__device__ __forceinline__ uint32_t time_ns() { uint32_t t; asm volatile("mov.u32 %0, %globaltimer_lo;" : "=r"(t)); return t; }
__device__ __forceinline__ void wait_until(uint32_t t0, uint32_t dt) { while (time_ns() - t0 < dt) {} }
__device__ __forceinline__ void mbar_wait(uint32_t bar) {
    asm volatile("{\n.reg .pred p;\nWAIT_LOOP:\nmbarrier.try_wait.parity.shared::cta.b64 p, [%0], 0;\n@!p bra WAIT_LOOP;\n}" :: "r"(bar) : "memory");
}
__device__ __forceinline__ void cp_async16_strip(uint32_t dst, const void* src) {
    asm volatile("cp.async.cg.shared.global.L2::128B [%0], [%1], 16;" :: "r"(dst), "l"(src) : "memory");
}
__device__ __forceinline__ void cp_async16_stream(uint32_t dst, const void* src) {
    asm volatile("{\n.reg .b64 pol;\ncreatepolicy.fractional.L2::evict_first.b64 pol, 1.0;\n"
                 "cp.async.cg.shared.global.L2::cache_hint [%0], [%1], 16, pol;\n}" :: "r"(dst), "l"(src) : "memory");
}
__device__ __forceinline__ void cp_async_arrive(uint32_t bar) {
    asm volatile("cp.async.mbarrier.arrive.noinc.shared::cta.b64 [%0];" :: "r"(bar) : "memory");
}
__device__ __forceinline__ void bar_sync(int id, int n)   { asm volatile("bar.sync %0, %1;" :: "r"(id), "r"(n) : "memory"); }
__device__ __forceinline__ void bar_arrive(int id, int n) { asm volatile("bar.arrive %0, %1;" :: "r"(id), "r"(n) : "memory"); }

__device__ __forceinline__ uint2 ld_poll2(const void* p) {
    uint2 v;
    asm volatile("ld.relaxed.gpu.global.v2.u32 {%0,%1}, [%2];" : "=r"(v.x), "=r"(v.y) : "l"(p) : "memory");
    return v;
}
__device__ __forceinline__ uint4 ld_poll4(const void* p) {
    uint4 v;
    asm volatile("ld.relaxed.gpu.global.v4.u32 {%0,%1,%2,%3}, [%4];" : "=r"(v.x), "=r"(v.y), "=r"(v.z), "=r"(v.w) : "l"(p) : "memory");
    return v;
}
__device__ __forceinline__ void st_pub4(void* p, uint4 v) {
    asm volatile("st.relaxed.gpu.global.v4.u32 [%0], {%1,%2,%3,%4};" :: "l"(p), "r"(v.x), "r"(v.y), "r"(v.z), "r"(v.w) : "memory");
}
__device__ __forceinline__ void st_pub2(void* p, uint32_t a, uint32_t b) {
    asm volatile("st.relaxed.gpu.global.v2.u32 [%0], {%1,%2};" :: "l"(p), "r"(a), "r"(b) : "memory");
}
__device__ __forceinline__ void st_pub1(void* p, uint32_t a) {
    asm volatile("st.relaxed.gpu.global.u32 [%0], %1;" :: "l"(p), "r"(a) : "memory");
}
__device__ __forceinline__ uint32_t tagf(float v, uint32_t tag) {
    uint32_t r;
    asm("lop3.b32 %0, %1, 0xfffffffe, %2, 0xEA;" : "=r"(r) : "r"(__float_as_uint(v)), "r"(tag));
    return r;
}
__device__ __forceinline__ uint32_t pin(uint32_t v) {
    uint32_t r;
    asm volatile("shfl.sync.bfly.b32 %0, %1, 0, 0x1f, 0xffffffff;" : "=r"(r) : "r"(v));
    return r;
}
template <class T>
__device__ __forceinline__ T* pin(T* p) {
    const uint64_t u = reinterpret_cast<uint64_t>(p);
    return reinterpret_cast<T*>(((uint64_t)pin((uint32_t)(u >> 32)) << 32) | pin((uint32_t)u));
}
__device__ __forceinline__ void sts32(uint32_t addr, uint32_t v) { asm volatile("st.shared.u32 [%0], %1;" :: "r"(addr), "r"(v) : "memory"); }
__device__ __forceinline__ float lds32(uint32_t addr) { float v; asm volatile("ld.shared.f32 %0, [%1];" : "=f"(v) : "r"(addr) : "memory"); return v; }
__device__ __forceinline__ uint4 lds128(uint32_t addr) {
    uint4 v;
    asm volatile("ld.shared.v4.u32 {%0,%1,%2,%3}, [%4];" : "=r"(v.x), "=r"(v.y), "=r"(v.z), "=r"(v.w) : "r"(addr) : "memory");
    return v;
}
__device__ __forceinline__ uint32_t bad2(uint32_t a, uint32_t b, uint32_t tag) {
    uint32_t r;
    asm("lop3.b32 %0, %1, %2, %3, 0x7E;" : "=r"(r) : "r"(a), "r"(b), "r"(tag));
    return r;
}
__device__ __forceinline__ uint32_t bad4(const uint4& v, uint32_t tag) { return bad2(v.x, v.y, tag) | bad2(v.z, v.w, tag); }
__device__ __forceinline__ bool warp_bad(uint32_t bad) { return __any_sync(0xffffffffu, bad & 1u); }

__device__ __forceinline__ void poll4(float (&f)[2][4], const uint4* p, uint32_t tag, const float (&w)[4]) {
    asm volatile("{\n"
                 ".reg .pred p0, p1, p2, p3, q;\n"
                 ".reg .b32 a, b, m, it, v<16>;\n"
                 "setp.eq.u32 p0, 0, 0;\nsetp.eq.u32 p1, 0, 0;\nsetp.eq.u32 p2, 0, 0;\nsetp.eq.u32 p3, 0, 0;\n"
                 "mov.u32 it, %14;\n"
                 "POLL_LOOP:\n"
                 "@p0 ld.relaxed.gpu.global.v4.u32 {v0,v1,v2,v3}, [%8];\n"
                 "@p1 ld.relaxed.gpu.global.v4.u32 {v4,v5,v6,v7}, [%8+512];\n"
                 "@p2 ld.relaxed.gpu.global.v4.u32 {v8,v9,v10,v11}, [%8+1024];\n"
                 "@p3 ld.relaxed.gpu.global.v4.u32 {v12,v13,v14,v15}, [%8+1536];\n"
                 "sub.u32 it, it, 1;\n"
                 "min.u32 m, it, 1;\n"
                 "lop3.b32 a, v0, v1, %9, 0x7E;\nlop3.b32 b, v2, v3, %9, 0x7E;\nlop3.b32 a, a, b, m, 0xA8;\nsetp.ne.u32 p0, a, 0;\n"
                 "lop3.b32 a, v4, v5, %9, 0x7E;\nlop3.b32 b, v6, v7, %9, 0x7E;\nlop3.b32 a, a, b, m, 0xA8;\nsetp.ne.u32 p1, a, 0;\n"
                 "lop3.b32 a, v8, v9, %9, 0x7E;\nlop3.b32 b, v10, v11, %9, 0x7E;\nlop3.b32 a, a, b, m, 0xA8;\nsetp.ne.u32 p2, a, 0;\n"
                 "lop3.b32 a, v12, v13, %9, 0x7E;\nlop3.b32 b, v14, v15, %9, 0x7E;\nlop3.b32 a, a, b, m, 0xA8;\nsetp.ne.u32 p3, a, 0;\n"
                 "or.pred q, p0, p1;\nor.pred q, q, p2;\nor.pred q, q, p3;\n"
                 "mul.f32 %0, v0, %10;\nmul.f32 %1, v1, %10;\nmul.f32 %2, v2, %10;\nmul.f32 %3, v3, %10;\n"
                 "mul.f32 %4, v8, %12;\nmul.f32 %5, v9, %12;\nmul.f32 %6, v10, %12;\nmul.f32 %7, v11, %12;\n"
                 "vote.sync.any.pred q, q, 0xffffffff;\n"
                 "fma.rn.f32 %0, v4, %11, %0;\nfma.rn.f32 %1, v5, %11, %1;\nfma.rn.f32 %2, v6, %11, %2;\nfma.rn.f32 %3, v7, %11, %3;\n"
                 "fma.rn.f32 %4, v12, %13, %4;\nfma.rn.f32 %5, v13, %13, %5;\nfma.rn.f32 %6, v14, %13, %6;\nfma.rn.f32 %7, v15, %13, %7;\n"
                 "@q bra POLL_LOOP;\n"
                 "}"
                 : "=&f"(f[0][0]), "=&f"(f[0][1]), "=&f"(f[0][2]), "=&f"(f[0][3]), "=&f"(f[1][0]), "=&f"(f[1][1]), "=&f"(f[1][2]), "=&f"(f[1][3])
                 : "l"(p), "r"(tag), "f"(w[0]), "f"(w[1]), "f"(w[2]), "f"(w[3]), "n"(SPIN_LIMIT) : "memory");
}

__device__ __forceinline__ void poll4_sum(float (&keep)[2], float (&recv)[2], const uint4* p, uint32_t tag, uint32_t hi) {
    asm volatile("{\n"
                 ".reg .pred p0, p1, p2, p3, q, h;\n"
                 ".reg .b32 a, b, m, it, v<16>;\n"
                 ".reg .f32 s<8>;\n"
                 "setp.eq.u32 p0, 0, 0;\nsetp.eq.u32 p1, 0, 0;\nsetp.eq.u32 p2, 0, 0;\nsetp.eq.u32 p3, 0, 0;\n"
                 "setp.ne.u32 h, %6, 0;\n"
                 "mov.u32 it, %7;\n"
                 "POLL_LOOP:\n"
                 "@p0 ld.relaxed.gpu.global.v4.u32 {v0,v1,v2,v3}, [%4];\n"
                 "@p1 ld.relaxed.gpu.global.v4.u32 {v4,v5,v6,v7}, [%4+512];\n"
                 "@p2 ld.relaxed.gpu.global.v4.u32 {v8,v9,v10,v11}, [%4+1024];\n"
                 "@p3 ld.relaxed.gpu.global.v4.u32 {v12,v13,v14,v15}, [%4+1536];\n"
                 "sub.u32 it, it, 1;\n"
                 "min.u32 m, it, 1;\n"
                 "add.f32 s0, v0, v4;\nadd.f32 s1, v1, v5;\nadd.f32 s2, v2, v6;\nadd.f32 s3, v3, v7;\n"
                 "add.f32 s4, v8, v12;\nadd.f32 s5, v9, v13;\nadd.f32 s6, v10, v14;\nadd.f32 s7, v11, v15;\n"
                 "add.f32 s0, s0, s4;\nadd.f32 s1, s1, s5;\nadd.f32 s2, s2, s6;\nadd.f32 s3, s3, s7;\n"
                 "selp.f32 s4, s0, s2, h;\nselp.f32 s5, s1, s3, h;\nselp.f32 %0, s2, s0, h;\nselp.f32 %1, s3, s1, h;\n"
                 "shfl.sync.bfly.b32 %2, s4, 16, 0x1f, 0xffffffff;\nshfl.sync.bfly.b32 %3, s5, 16, 0x1f, 0xffffffff;\n"
                 "lop3.b32 a, v0, v1, %5, 0x7E;\nlop3.b32 b, v2, v3, %5, 0x7E;\nlop3.b32 a, a, b, m, 0xA8;\nsetp.ne.u32 p0, a, 0;\n"
                 "lop3.b32 a, v4, v5, %5, 0x7E;\nlop3.b32 b, v6, v7, %5, 0x7E;\nlop3.b32 a, a, b, m, 0xA8;\nsetp.ne.u32 p1, a, 0;\n"
                 "lop3.b32 a, v8, v9, %5, 0x7E;\nlop3.b32 b, v10, v11, %5, 0x7E;\nlop3.b32 a, a, b, m, 0xA8;\nsetp.ne.u32 p2, a, 0;\n"
                 "lop3.b32 a, v12, v13, %5, 0x7E;\nlop3.b32 b, v14, v15, %5, 0x7E;\nlop3.b32 a, a, b, m, 0xA8;\nsetp.ne.u32 p3, a, 0;\n"
                 "or.pred q, p0, p1;\nor.pred q, q, p2;\nor.pred q, q, p3;\n"
                 "vote.sync.any.pred q, q, 0xffffffff;\n"
                 "@q bra POLL_LOOP;\n"
                 "}"
                 : "=&f"(keep[0]), "=&f"(keep[1]), "=&f"(recv[0]), "=&f"(recv[1])
                 : "l"(p), "r"(tag), "r"(hi), "n"(SPIN_LIMIT) : "memory");
}

__device__ __forceinline__ void ldsm4(uint32_t addr, uint32_t (&a)[4]) {
    asm volatile("ldmatrix.sync.aligned.m8n8.x4.shared.b16 {%0,%1,%2,%3}, [%4];" : "=r"(a[0]), "=r"(a[1]), "=r"(a[2]), "=r"(a[3]) : "r"(addr) : "memory");
}
__device__ __forceinline__ void ldsm4t(uint32_t addr, uint32_t (&a)[4]) {
    asm volatile("ldmatrix.sync.aligned.m8n8.x4.trans.shared.b16 {%0,%1,%2,%3}, [%4];" : "=r"(a[0]), "=r"(a[1]), "=r"(a[2]), "=r"(a[3]) : "r"(addr) : "memory");
}
__device__ __forceinline__ void mma16816(float (&c)[4], const uint32_t (&a)[4], uint32_t b0, uint32_t b1) {
    asm volatile("mma.sync.aligned.m16n8k16.row.col.f32.bf16.bf16.f32 {%0,%1,%2,%3}, {%4,%5,%6,%7}, {%8,%9}, {%0,%1,%2,%3};"
                 : "+f"(c[0]), "+f"(c[1]), "+f"(c[2]), "+f"(c[3]) : "r"(a[0]), "r"(a[1]), "r"(a[2]), "r"(a[3]), "r"(b0), "r"(b1));
}
__device__ __forceinline__ float bf_lo(uint32_t u) { return __uint_as_float(u << 16); }
__device__ __forceinline__ float bf_hi(uint32_t u) { return __uint_as_float(u & 0xffff0000u); }
__device__ __forceinline__ float rbf(float v) { return __bfloat162float(__float2bfloat16_rn(v)); }
__device__ __forceinline__ uint32_t pack_bf(float lo, float hi) {
    uint32_t r;
    asm("cvt.rn.bf16x2.f32 %0, %1, %2;" : "=r"(r) : "f"(hi), "f"(lo));
    return r;
}
__device__ __forceinline__ float sel4(const float (&c)[4], int t) {
    float a = (t & 1) ? c[1] : c[0];
    float b = (t & 1) ? c[3] : c[2];
    return (t & 2) ? b : a;
}
__device__ __forceinline__ float ex2(float x) { float y; asm("ex2.approx.ftz.f32 %0, %1;" : "=f"(y) : "f"(x)); return y; }
__device__ __forceinline__ float sqrt_approx(float x) { float y; asm("sqrt.approx.f32 %0, %1;" : "=f"(y) : "f"(x)); return y; }

__host__ __device__ constexpr uint32_t slot_of(int s) { return SM_RING + (s % NS) * SLOT; }

__device__ __forceinline__ void layernorm(unsigned char* smem, int lane) {
    uint32_t xs[2][7];
#pragma unroll
    for (int b = 0; b < 2; b++)
#pragma unroll
        for (int i = 0; i < 7; i++) xs[b][i] = reinterpret_cast<const uint32_t*>(smem + SM_X)[b * (D_MODEL / 2) + i * 32 + lane];
#pragma unroll
    for (int b = 0; b < 2; b++) {
        float sum = 0.f;
#pragma unroll
        for (int i = 0; i < 7; i++) sum += bf_lo(xs[b][i]) + bf_hi(xs[b][i]);
#pragma unroll
        for (int o = 16; o > 0; o >>= 1) sum += __shfl_xor_sync(0xffffffffu, sum, o);
        const float mean = sum * (1.0f / D_MODEL);
        float sq = 0.f;
#pragma unroll
        for (int i = 0; i < 7; i++) {
            const float d0 = bf_lo(xs[b][i]) - mean, d1 = bf_hi(xs[b][i]) - mean;
            sq = fmaf(d0, d0, fmaf(d1, d1, sq));
        }
#pragma unroll
        for (int o = 16; o > 0; o >>= 1) sq += __shfl_xor_sync(0xffffffffu, sq, o);
        const float mb = rbf(mean);
        const float sd = rbf(sqrt_approx(rbf(rbf(sq * (1.0f / D_MODEL)) + 1e-5f)));
#pragma unroll
        for (int i = 0; i < 7; i++)
            reinterpret_cast<uint32_t*>(smem + SM_XN + b * XROW)[i * 32 + lane] =
                pack_bf(__fdividef(rbf(bf_lo(xs[b][i]) - mb), sd), __fdividef(rbf(bf_hi(xs[b][i]) - mb), sd));
    }
}

__device__ __forceinline__ void strip_partial(uint32_t sb, uint32_t strip, unsigned char* smem, int warp, int lane) {
    float c[2][2][4];
#pragma unroll
    for (int n = 0; n < 2; n++)
#pragma unroll
        for (int e = 0; e < 4; e++) c[n][0][e] = c[n][1][e] = 0.f;
    const uint32_t ba = sb + SM_XN + (lane & 1) * XROW + (lane >> 3) * 16 + warp * 128;
    const uint32_t aa = sb + strip + (warp * 64 + (lane & 7) + (lane >> 4) * 8) * 64 + (((lane >> 3) & 1) ^ ((lane & 7) >> 1)) * 16;
#pragma unroll
    for (int k2 = 0; k2 < 2; k2++) {
        uint32_t b[4];
        ldsm4(ba + k2 * 64, b);
#pragma unroll
        for (int n = 0; n < 2; n++) {
            uint32_t a0[4], a1[4];
            ldsm4t((aa ^ (n * 32)) + k2 * 2048, a0);
            ldsm4t((aa ^ (n * 32)) + k2 * 2048 + 1024, a1);
            mma16816(c[n][0], a0, b[0], b[1]);
            mma16816(c[n][1], a1, b[2], b[3]);
        }
    }
    float* red = reinterpret_cast<float*>(smem + SM_RED) + warp * 64 + lane;
#pragma unroll
    for (int n = 0; n < 2; n++) red[n * 32] = sel4(c[n][0], lane & 3) + sel4(c[n][1], lane & 3);
}
__device__ __forceinline__ float strip_sum(const unsigned char* smem, int idx) {
    const float* red = reinterpret_cast<const float*>(smem + SM_RED) + idx;
    return ((red[0] + red[64]) + (red[128] + red[192])) + ((red[256] + red[320]) + red[384]);
}

__device__ __forceinline__ uint32_t time_base(uint32_t sb, int i) {
    uint32_t t;
    asm volatile("ld.volatile.shared.u32 %0, [%1];" : "=r"(t) : "r"(sb + SM_T0 + 4 * i) : "memory");
    return t;
}
__device__ __forceinline__ void wait_clock(uint32_t sb, int i, uint32_t dt) { while (time_ns() - time_base(sb, i) < dt) {} }

struct Prod {
    uint32_t sb, kvdst, sdst;
    const char *k, *v;
    const __nv_bfloat16* gu;
    bool ffn;
};
__host__ __device__ constexpr int bytes_before(int s) { return 28672 + s * 16384 + (s <= S_GU ? 0 : s < S_GU + 14 ? s - S_GU : 14) * 1792; }
__host__ __device__ constexpr int issue_time(int s) {
    return (int)((long long)bytes_before(s) * PACE_DT / 16384) - PACE_LEAD;
}

template <int S>
__device__ __forceinline__ void produce(Prod& p) {
    if constexpr (S < NSTAGE) {
        if constexpr (S >= NS) mbar_wait(p.sb + SM_BAR + (NBAR + S - NS) * 8);
        wait_clock(p.sb, 0, issue_time(S));
        const char* src = (S < S_V ? p.k : p.v) + (S & 15) * (8 * SLOT);
#pragma unroll
        for (int i = 0; i < 8; i++) cp_async16_stream((p.kvdst ^ ((i & 1) * 64)) + slot_of(S) + i * 2048, src + i * 2048);
        if constexpr (S >= S_GU && S < S_GU + 14) {
            if (p.ffn) cp_async16_strip(p.sdst + (S - S_GU) * 2048, p.gu + (size_t)(S - S_GU) * 32 * FF);
        }
        cp_async_arrive(p.sb + SM_BAR + S * 8);
        produce<S + 1>(p);
    }
}

__device__ __forceinline__ void fetch16(uint32_t dst, const char* src) {
#pragma unroll
    for (int i = 0; i < 4; i++)
        asm volatile("cp.async.cg.shared.global [%0], [%1], 16;" :: "r"((dst ^ (((i & 1) ^ (i >> 1)) * 64)) + i * 512), "l"(src + i * (4 * 896)) : "memory");
}
template <int PENDING, int OFF>
__device__ __forceinline__ void frag16(uint32_t (&a)[4][4], uint32_t addr) {
    asm volatile("cp.async.wait_group %0;" :: "n"(PENDING) : "memory");
    __syncwarp();
#pragma unroll
    for (int m = 0; m < 4; m++) ldsm4t((addr ^ (m * 32)) + OFF, a[m]);
}

__device__ __forceinline__ void load_x(uint32_t sb, const void* x, const void* epoch) {
    const uint32_t full0 = sb + SM_BAR;
    mbar_init(full0 + B_X * 8, 1);
    asm volatile("fence.mbarrier_init.release.cluster;" ::: "memory");
    asm volatile("mbarrier.arrive.expect_tx.shared::cta.b64 _, [%0], %1;" :: "r"(full0 + B_X * 8), "r"(1792 + 16) : "memory");
    asm volatile("cp.async.bulk.shared::cluster.global.mbarrier::complete_tx::bytes [%0], [%1], %2, [%3];"
                 :: "r"(sb + SM_X), "l"(x), "r"(1792), "r"(full0 + B_X * 8) : "memory");
    asm volatile("cp.async.bulk.shared::cluster.global.mbarrier::complete_tx::bytes [%0], [%1], %2, [%3];"
                 :: "r"(sb + SM_X + 1792), "l"(epoch), "r"(16), "r"(full0 + B_X * 8) : "memory");
}

enum { BAR_OB = 1, BAR_CONS = 2, BAR_LN = 3, BAR_FF = 4, BAR_FIN = 5, BAR_H = 6 };

__global__ void __launch_bounds__(NTHREADS, 1)
fused_decode_kernel(const __nv_bfloat16* __restrict__ wq, const __nv_bfloat16* __restrict__ kc, const __nv_bfloat16* __restrict__ x,
                    Scratch* __restrict__ scr, const __nv_bfloat16* __restrict__ vc, const __nv_bfloat16* __restrict__ wo,
                    const __nv_bfloat16* __restrict__ wg, const __nv_bfloat16* __restrict__ wu, const __nv_bfloat16* __restrict__ wd,
                    __nv_bfloat16* __restrict__ out) {
    extern __shared__ __align__(128) unsigned char smem[];
    const uint32_t sb = (uint32_t)__cvta_generic_to_shared(smem);
    const int tid = threadIdx.x, lane = tid & 31;
    const int cta = blockIdx.x;
    const uint32_t full0 = sb + SM_BAR, done0 = full0 + NBAR * 8;
    const uint32_t t0 = time_ns();
    if (tid < 224) {
        const int row = (tid >> 5) * 64 + (lane >> 2);
        const char* src = reinterpret_cast<const char*>(wq) + (uint32_t)(row * (QCOLS * 2) + cta * 64 + (lane & 3) * 16);
        const uint32_t dst = sb + SM_STRIP + row * 64 + ((lane & 3) ^ (lane >> 3)) * 16;
#pragma unroll
        for (int i = 0; i < 8; i++) cp_async16_strip(dst + i * 512, src + i * (8 * QCOLS * 2));
    }
    const int warp = __shfl_sync(0xffffffffu, tid >> 5, 0);
    const int hkv = cta >> 4, j = cta & 15, bat = j >> 3, sp = j & 7;
    const int g = lane >> 2, t = lane & 3;

    if (warp < 8) {
        if (tid == 224) load_x(sb, x, &scr->epoch[cta * 8]);
        __syncthreads();
        mbar_wait(full0 + B_X * 8);
        const uint32_t epoch = *reinterpret_cast<const uint32_t*>(smem + SM_X + 1792);
        const uint32_t tag = pin((epoch + 1) & 1);
        uint32_t* qdst = reinterpret_cast<uint32_t*>(scr->q) + (hkv * 2 + (t & 1)) * 512 + j * 32 + warp * 16 + g + 8 * (t >> 1);
        if (warp == 7) {
            layernorm(smem, lane);
            bar_arrive(BAR_LN, 256);
        } else {
            asm volatile("cp.async.wait_all;" ::: "memory");
            bar_sync(BAR_LN, 256);
            strip_partial(sb, SM_STRIP, smem, warp, lane);
        }
        bar_sync(BAR_CONS, 256);
        if (warp < 2) {
            st_pub1(qdst, (pack_bf(0.f, strip_sum(smem, tid)) & 0xffff0000u) | tag);
        } else if (warp >= 4) {
            const int i = tid - 128;
            const uint4* qp = scr->q + (hkv * 2 + bat) * 128 + i;
            wait_until(t0, Q_T);
            uint4 v;
            int it = 0;
            do {
                v = ld_poll4(qp);
                if (++it > SPIN_LIMIT) __trap();
            } while (warp_bad(bad4(v, tag)));
            *reinterpret_cast<uint2*>(smem + SM_Q + (i >> 6) * 528 + (i & 63) * 8) =
                make_uint2(__byte_perm(v.x, v.y, 0x7632), __byte_perm(v.z, v.w, 0x7632));
        }
        bar_sync(BAR_CONS, 256);
        if (tid == 96) scr->epoch[cta * 8] = epoch + 1;
        {
            uint32_t qf[8][4];
#pragma unroll
            for (int k2 = 0; k2 < 8; k2++) ldsm4(sb + SM_Q + (lane & 1) * 528 + k2 * 64 + (lane >> 3) * 16, qf[k2]);
            const int mt = warp & 1;
            const uint32_t aoff = (16 * mt + (lane & 15)) * 512 + ((lane >> 4) ^ (lane & 7)) * 16;
            float* sc = reinterpret_cast<float*>(smem + SM_S) + (t & 1) * 520 + (g >> 1) * 8 + (2 * mt + (t >> 1)) * 2 + (g & 1);
#pragma unroll 1
            for (int k = warp >> 1; k < 16; k += 4) {
                const int s = S_K + k;
                mbar_wait(full0 + s * 8);
                const uint32_t base = sb + SM_RING + (s >= NS ? s - NS : s) * SLOT + aoff;
                float c0[4] = {0.f, 0.f, 0.f, 0.f}, c1[4] = {0.f, 0.f, 0.f, 0.f};
#pragma unroll
                for (int k2 = 0; k2 < 8; k2++) {
                    uint32_t a0[4], a1[4];
                    ldsm4((base ^ ((k2 & 1) * 64)) + (k2 >> 1) * 128, a0);
                    ldsm4((base ^ ((k2 & 1) * 64 + 32)) + (k2 >> 1) * 128, a1);
                    mma16816(c0, a0, qf[k2][0], qf[k2][1]);
                    mma16816(c1, a1, qf[k2][2], qf[k2][3]);
                }
                __syncwarp();
                if (lane == 0) mbar_arrive(done0 + s * 8, 4);
                sc[k * 32] = rbf(sel4(c0, t) + sel4(c1, t));
            }
        }
        bar_sync(BAR_CONS, 256);
        {
            constexpr float C = SCALE_LOG2E;
            const float* sc = reinterpret_cast<const float*>(smem + SM_S);
            float* stat = reinterpret_cast<float*>(smem + SM_STAT);
            const float2 s0 = *reinterpret_cast<const float2*>(sc + 2 * tid);
            const float2 s1 = *reinterpret_cast<const float2*>(sc + 520 + 2 * tid);
            float m0 = fmaxf(s0.x, s0.y), m1 = fmaxf(s1.x, s1.y);
#pragma unroll
            for (int o = 16; o > 0; o >>= 1) {
                m0 = fmaxf(m0, __shfl_xor_sync(0xffffffffu, m0, o));
                m1 = fmaxf(m1, __shfl_xor_sync(0xffffffffu, m1, o));
            }
            if (lane == 0) *reinterpret_cast<float2*>(stat + warp * 2) = make_float2(m0, m1);
            bar_sync(BAR_CONS, 256);
#pragma unroll
            for (int w = 0; w < 8; w++) {
                const float2 mm = *reinterpret_cast<const float2*>(stat + w * 2);
                m0 = fmaxf(m0, mm.x); m1 = fmaxf(m1, mm.y);
            }
            const float p00 = ex2((s0.x - m0) * C), p01 = ex2((s0.y - m0) * C);
            const float p10 = ex2((s1.x - m1) * C), p11 = ex2((s1.y - m1) * C);
            uint32_t* ps = reinterpret_cast<uint32_t*>(smem + SM_P);
            ps[tid] = pack_bf(p00, p01);
            ps[272 + tid] = pack_bf(p10, p11);
            float l0 = p00 + p01, l1 = p10 + p11;
#pragma unroll
            for (int o = 16; o > 0; o >>= 1) {
                l0 += __shfl_xor_sync(0xffffffffu, l0, o);
                l1 += __shfl_xor_sync(0xffffffffu, l1, o);
            }
            if (lane == 0) *reinterpret_cast<float2*>(stat + 16 + warp * 2) = make_float2(l0, l1);
            bar_sync(BAR_CONS, 256);
            if (tid < 4) {
                float l = 0.f;
#pragma unroll
                for (int w = 0; w < 8; w++) l += stat[16 + w * 2 + (tid & 1)];
                st_pub2(scr->ml + cta * 4 + tid, tagf((tid & 1) ? m1 : m0, tag), tagf(l, tag));
            }
        }
        float wgt[2] = {0.f, 0.f};
        {
            float o0[4] = {0.f, 0.f, 0.f, 0.f}, o1[4] = {0.f, 0.f, 0.f, 0.f};
            float o2[4] = {0.f, 0.f, 0.f, 0.f}, o3[4] = {0.f, 0.f, 0.f, 0.f};
            const uint32_t aoff = ((lane & 7) + (lane >> 4) * 8) * 512 + ((warp * 4 + ((lane >> 3) & 1) * 2) ^ (lane & 7)) * 16;
            const uint4* ps = reinterpret_cast<const uint4*>(smem + SM_P + (g & 1) * 272 * 4) + t;
            uint32_t* dst = reinterpret_cast<uint32_t*>(scr->part) + ((size_t)(hkv * 16 + (t & 1) * 8 + warp) * 16 + j) * 32 +
                            (4 * (g & 3) + (t & 2) + (g >> 2)) * 2;
#pragma unroll
            for (int k = 0; k < 16; k++) {
                const uint4 pa = ps[k * 4];
                mbar_wait(full0 + (S_V + k) * 8);
                uint32_t a[4][4];
#pragma unroll
                for (int i = 0; i < 4; i++) ldsm4t(sb + (aoff ^ ((i & 1) * 16)) + slot_of(S_V + k) + (i >> 1) * 8192, a[i]);
                mma16816(o0, a[0], pa.x, pa.y);
                mma16816(o1, a[1], pa.x, pa.y);
                mma16816(o2, a[2], pa.z, pa.w);
                mma16816(o3, a[3], pa.z, pa.w);
                if (S_V + k + NS < NSTAGE + 3) {
                    __syncwarp();
                    if (lane == 0) mbar_arrive(done0 + (S_V + k) * 8, 1);
                }
                if (k == FFN_ST && warp < 7) {
                    strip_partial(sb, SM_STRIP, smem, warp, lane);
                    bar_arrive(BAR_FF, 256);
                }
                if (k == FFN_ST && warp == 7) {
                    const uint2* mlp = scr->ml + (hkv * 16 + g) * 4 + (j >> 3);
                    uint2 a, b;
                    int it = 0;
                    do {
                        a = ld_poll2(mlp); b = ld_poll2(mlp + 32);
                        if (++it > SPIN_LIMIT) __trap();
                    } while (warp_bad(bad2(a.x, a.y, tag) | bad2(b.x, b.y, tag)));
                    float m[2] = {bf_hi(a.x), bf_hi(b.x)};
                    float l[2] = {__uint_as_float(a.y), __uint_as_float(b.y)};
#pragma unroll
                    for (int bb = 0; bb < 2; bb++) {
                        float M = m[bb];
                        M = fmaxf(M, __shfl_xor_sync(0xffffffffu, M, 4));
                        M = fmaxf(M, __shfl_xor_sync(0xffffffffu, M, 8));
                        M = fmaxf(M, __shfl_xor_sync(0xffffffffu, M, 16));
                        const float e = ex2((m[bb] - M) * SCALE_LOG2E);
                        float L = e * l[bb];
                        L += __shfl_xor_sync(0xffffffffu, L, 4);
                        L += __shfl_xor_sync(0xffffffffu, L, 8);
                        L += __shfl_xor_sync(0xffffffffu, L, 16);
                        wgt[bb] = __fdividef(e, L);
                    }
                    bar_sync(BAR_FF, 256);
                    float ga = rbf(strip_sum(smem, lane));
                    ga *= (ga > 0.f ? 1.f : 0.f);
                    const float hv = ga * rbf(strip_sum(smem, 32 + lane));
                    const uint32_t w = pack_bf(hv, __shfl_xor_sync(0xffffffffu, hv, 2));
                    if (!(t & 2)) reinterpret_cast<uint32_t*>(smem + SM_H)[(t & 1) * 8 + (g & 3) * 2 + (g >> 2)] = w;
                    bar_arrive(BAR_H, 256);
                }
                if (k == PRE_ST) st_pub2(dst, tag ^ 1, tag ^ 1);
            }
            const float v0 = sel4(o0, t) + sel4(o2, t), v1 = sel4(o1, t) + sel4(o3, t);
            st_pub2(dst, tagf(v0, tag), tagf(v1, tag));
        }
        if (warp == 7) {
            const uint4* pp = pin(scr->part + (size_t)cta * 128 + lane);
            const uint32_t obaddr = pin(sb + SM_OB + (lane >> 4) * 64 + (lane & 7) * 8 + ((lane >> 3) & 1) * 4), ll = pin(lane);
            float w[4];
#pragma unroll
            for (int i = 0; i < 4; i++) w[i] = __shfl_sync(0xffffffffu, wgt[i >> 1], ((i & 1) * 4 + (lane >> 3)) * 4);
            wait_until(time_base(sb, 2), E2_T);
            float f[2][4];
            poll4(f, pp, tag, w);
            const bool h16 = ll & 16, h8 = ll & 8;
            float r4[4], r2[2];
#pragma unroll
            for (int e = 0; e < 4; e++) r4[e] = (h16 ? f[1][e] : f[0][e]) + __shfl_xor_sync(0xffffffffu, h16 ? f[0][e] : f[1][e], 16);
#pragma unroll
            for (int e = 0; e < 2; e++) r2[e] = (h8 ? r4[2 + e] : r4[e]) + __shfl_xor_sync(0xffffffffu, h8 ? r4[e] : r4[2 + e], 8);
            sts32(obaddr, pack_bf(r2[0], r2[1]));
            bar_arrive(BAR_OB, 256);
        } else if (warp < 4 && (cta & 1) == 0 && cta < 2 * NRED) {
            const uint4* op = pin(scr->outp + (size_t)(cta >> 1) * (NCTA * 4) + warp * 128 + lane);
            const int oidx = (t & 1) * D_MODEL + hkv * 64 + (lane >> 3) * 16 + (j >> 1) + (t >> 1) * 8;
            const float xv = __bfloat162float(reinterpret_cast<const __nv_bfloat16*>(smem + SM_X)[oidx]);
            __nv_bfloat16* optr = pin(out + oidx);
            const uint32_t red = pin(sb + SM_S + tid * 4), ll = pin(lane);
            float r2[2], rcv[2];
            const bool h8 = ll & 8;
            wait_until(time_base(sb, 3), E3_T);
            poll4_sum(r2, rcv, op, tag, ll & 16);
            r2[0] += rcv[0]; r2[1] += rcv[1];
            float r = (h8 ? r2[1] : r2[0]) + __shfl_xor_sync(0xffffffffu, h8 ? r2[0] : r2[1], 8);
            r += __shfl_xor_sync(0xffffffffu, r, 4);
            if (warp != 0) {
                sts32(red, __float_as_uint(r));
                bar_arrive(BAR_FIN, 128);
            } else {
                bar_sync(BAR_FIN, 128);
                r = ((xv + r) + lds32(red + 128)) + (lds32(red + 256) + lds32(red + 384));
                asm volatile("st.global.u16 [%0], %1;" :: "l"(optr), "h"(__bfloat16_as_ushort(__float2bfloat16_rn(r))) : "memory");
            }
        }
    } else if (warp < 15) {
        const int pt = tid - 256, pw = warp - 8;
        const char* pdn = reinterpret_cast<const char*>(wd) + (size_t)cta * 14336 + (lane >> 3) * 896 + pw * 128 + (lane & 7) * 16;
        const char* pwo = reinterpret_cast<const char*>(wo) + (size_t)cta * 28672 + (lane >> 3) * 896 + pw * 128 + (lane & 7) * 16;
        if (pw < 4) {
            if (lane == 0) {
#pragma unroll
                for (int i = 0; i < 9; i++) {
                    if (pw * 9 + i != B_X) mbar_init(full0 + (pw * 9 + i) * 8, NPT);
                    mbar_init(done0 + (pw * 9 + i) * 8, 8);
                }
            }
            Prod p;
            const size_t kvoff = ((size_t)(bat * 8 + hkv) * SK + (SK - WIN)) * DH * 2 + sp * SLOT + pt * 16;
            p.sb = sb;
            p.kvdst = (sb + pt * 16) ^ (pw * 16);
            p.sdst = sb + SM_STRIP + (pt >> 2) * 64 + ((pt & 3) ^ ((pt >> 3) & 3)) * 16;
            p.k = reinterpret_cast<const char*>(kc) + kvoff;
            p.v = reinterpret_cast<const char*>(vc) + kvoff;
            p.gu = ((pt & 2) ? wu : wg) + cta * 16 + (pt & 1) * 8 + (size_t)(pt >> 2) * FF;
            p.ffn = cta < NFFN;
            __syncthreads();
            produce<0>(p);
        } else {
            __syncthreads();
        }
        mbar_wait(full0 + B_X * 8);
        const uint32_t tag = pin((*reinterpret_cast<const uint32_t*>(smem + SM_X + 1792) + 1) & 1);
        if (pw == 4 && (cta & 3) == 0) {
#pragma unroll 1
            for (int i = 0; i < 4; i++) {
                uint32_t sum = 0;
#pragma unroll
                for (int k = 0; k < NM; k++) {
                    mbar_wait(full0 + (MEND - NM + 1 + k + 6 * i) * 8);
                    sum += time_ns() - t0;
                }
                if (lane < 4) st_pub2(&scr->prog[i * 128 + cta + lane], ((t0 + sum / NM) & ~1u) | tag, (t0 & ~1u) | tag);
            }
        }
        mbar_wait(done0 + (NSTAGE + 2 - NS) * 8);
        const uint32_t ta = LATE_T, td = LATE_DT;
        uint4* odst = scr->outp + ((size_t)(pt >> 2) * NCTA + cta) * 4 + t;
        st_pub4(odst, make_uint4(tag ^ 1, tag ^ 1, tag ^ 1, tag ^ 1));
        const uint32_t fdst = (sb + pw * 2048 + lane * 16) ^ ((lane >> 3) * 16);
        wait_clock(sb, 1, ta);
        if (cta < NFFN) fetch16(fdst + slot_of(NSTAGE), pdn);
        asm volatile("cp.async.commit_group;" ::: "memory");
        wait_clock(sb, 1, ta + td);
        fetch16(fdst + slot_of(NSTAGE + 1), pwo);
        asm volatile("cp.async.commit_group;" ::: "memory");
        wait_clock(sb, 1, ta + 2 * td);
        fetch16(fdst + slot_of(NSTAGE + 2), pwo + 14336);
        asm volatile("cp.async.commit_group;" ::: "memory");
        bar_sync(BAR_H, 256);
        const uint2 h = *reinterpret_cast<const uint2*>(smem + SM_H + (g & 1) * 32 + t * 8);
        float c[4][4];
#pragma unroll
        for (int m = 0; m < 4; m++)
#pragma unroll
            for (int e = 0; e < 4; e++) c[m][e] = 0.f;
        const int r7 = ((lane & 7) >> 1) + 4 * (lane >> 4);
        const uint32_t aoff = sb + pw * 2048 + (r7 + 8 * (lane & 1)) * 128 + (((lane >> 3) & 1) ^ r7 ^ ((lane & 1) << 2)) * 16;
        const uint32_t obaddr = pin(sb + SM_OB + (g & 1) * 64 + t * 16), tt = pin(t);
        uint32_t a0[4][4], a1[4][4];
        frag16<2, slot_of(NSTAGE)>(a0, aoff);
        if (cta < NFFN) {
#pragma unroll
            for (int m = 0; m < 4; m++) mma16816(c[m], a0[m], h.x, h.y);
        }
        frag16<1, slot_of(NSTAGE + 1)>(a1, aoff);
        bar_sync(BAR_OB, 256);
        const uint4 ob = lds128(obaddr);
#pragma unroll
        for (int m = 0; m < 4; m++) mma16816(c[m], a1[m], ob.x, ob.y);
        frag16<0, slot_of(NSTAGE + 2)>(a0, aoff);
#pragma unroll
        for (int m = 0; m < 4; m++) mma16816(c[m], a0[m], ob.z, ob.w);
        uint4 r;
        r.x = tagf(sel4(c[0], tt), tag); r.y = tagf(sel4(c[1], tt), tag);
        r.z = tagf(sel4(c[2], tt), tag); r.w = tagf(sel4(c[3], tt), tag);
        st_pub4(odst, r);
    } else if (warp == 15) {
        if (lane < 4) reinterpret_cast<uint32_t*>(smem + SM_T0)[lane] = t0;
        __syncthreads();
        mbar_wait(full0 + B_X * 8);
        const uint32_t tag = (*reinterpret_cast<const uint32_t*>(smem + SM_X + 1792) + 1) & 1;
#pragma unroll 1
        for (int i = 0; i < 4; i++) {
            mbar_wait(full0 + (MEND + 2 + 6 * i) * 8);
            uint2 v;
            int it = 0;
            do {
                v = ld_poll2(&scr->prog[i * 128 + lane * 4]);
                if (++it > SPIN_LIMIT) __trap();
            } while (warp_bad(bad2(v.x, v.y, tag)));
            const int nom = i == 0 ? M_NOM0 : i == 1 ? M_NOM1 : i == 2 ? M_NOM2 : M_NOM3;
            int base = (__reduce_add_sync(0xffffffffu, min(max((int)(v.x - t0), 0), 1 << 20)) >> 5) - nom;
            const int start = __reduce_add_sync(0xffffffffu, min(max((int)(v.y - t0), -(1 << 20)), 1 << 20)) >> 5;
            base = start + max(min(base - start, 2 * (base - start - DEAD)), 0);
            const int ahead = (lane == 0 ? nom : lane == 1 ? LATE_T : lane == 2 ? E2_T : E3_T - 150) - nom;
            const float rate = fminf(fmaxf(__fdividef((float)(base - start), (float)(nom - 500)), -0.01f), 0.045f);
            if (lane < 4) sts32(sb + SM_T0 + 4 * lane, t0 + base + (int)(rate * (float)ahead));
        }
    }
}

}

extern "C" void kernel_launch(void* const* d_in, const int* in_sizes, int n_in, void* d_out, int out_size) {
    (void)in_sizes; (void)n_in; (void)out_size;
    static Scratch* scr = nullptr;
    if (!scr) {
        cudaFuncSetAttribute(fused_decode_kernel, cudaFuncAttributeMaxDynamicSharedMemorySize, SM_TOTAL);
        cudaGetSymbolAddress(reinterpret_cast<void**>(&scr), g_scratch);
    }
    typedef const __nv_bfloat16* P;
    fused_decode_kernel<<<NCTA, NTHREADS, SM_TOTAL>>>((P)d_in[3], (P)d_in[1], (P)d_in[0], scr, (P)d_in[2], (P)d_in[4],
                                                      (P)d_in[6], (P)d_in[7], (P)d_in[8], (__nv_bfloat16*)d_out);
}
```

```cpp
#include <cuda_runtime.h>
#include <cuda_bf16.h>
#include <stdint.h>

namespace {

constexpr int PACE_DT = 636;
constexpr int PACE_LEAD = 350;
constexpr int LATE_T = 22400;
constexpr int LATE_DT = 400;
constexpr int Q_T = 4000;
constexpr int E2_T = 24050;
constexpr int E3_T = 24830;
constexpr int M_NOM0 = 5250;
constexpr int M_NOM1 = 9230;
constexpr int M_NOM2 = 13560;
constexpr int M_NOM3 = 17725;
constexpr int DEAD = 100;
constexpr int NM = 4;
constexpr int MEND = 6;
constexpr int NSLOT = 11;

constexpr int D_MODEL = 448;
constexpr int SK      = 32768;
constexpr int WIN     = 4096;
constexpr int DH      = 256;
constexpr int QCOLS   = 4096;
constexpr int FF      = 1792;
constexpr int NCTA    = 128;
constexpr int NFFN    = 112;
constexpr int NRED    = 56;
constexpr int NPT     = 128;
constexpr int NTHREADS = 512;

constexpr int NS     = NSLOT;
constexpr int SLOT   = 16384;
constexpr int XROW   = 912;
constexpr int S_K = 0, S_V = 16, NSTAGE = 32;
constexpr int S_GU   = NS;
constexpr int FFN_ST = 10;
constexpr int PRE_ST = 12;
constexpr int NBAR   = 36;
constexpr int B_X = NSTAGE;

constexpr int SM_RING  = 0;
constexpr int SM_STRIP = SM_RING + NS * SLOT;
constexpr int SM_S    = SM_STRIP + 448 * 64;
constexpr int SM_P    = SM_S + 2 * 520 * 4;
constexpr int SM_Q    = SM_P + 2 * 272 * 4;
constexpr int SM_XN   = SM_Q + 2 * 264 * 2;
constexpr int SM_X    = SM_XN + 2 * XROW;
constexpr int SM_RED  = SM_X + 1792 + 32;
constexpr int SM_STAT = SM_RED + 7 * 64 * 4;
constexpr int SM_OB   = SM_STAT + 2 * 8 * 2 * 4;
constexpr int SM_H    = SM_OB + 2 * 16 * 4;
constexpr int SM_T0   = SM_H + 2 * 8 * 4;
constexpr int SM_BAR  = SM_T0 + 16;
constexpr int SM_TOTAL = SM_BAR + 2 * NBAR * 8;
static_assert(SM_Q % 16 == 0 && SM_XN % 16 == 0 && SM_X % 16 == 0 && SM_OB % 16 == 0 && SM_P % 16 == 0 && SM_T0 % 16 == 0, "align");
static_assert(S_GU + 13 <= S_V + FFN_ST, "the gate/up strip lands with stage S_GU + 13");
static_assert(2 * NS >= 16, "K stage -> slot mapping");

constexpr int SPIN_LIMIT = 1 << 22;
constexpr float SCALE_LOG2E = 0.0625f * 1.4426950408889634f;

struct __align__(1024) Scratch {
    uint4    part[NCTA * 2 * 8 * 8];
    uint4    outp[NRED * NCTA * 4];
    uint4    q[8 * 2 * 128];
    uint2    ml[NCTA * 4];
    uint2    prog[4 * 32 * 4];
    unsigned epoch[NCTA * 8];
};
__device__ Scratch g_scratch;

__device__ __forceinline__ void mbar_init(uint32_t bar, uint32_t cnt) {
    asm volatile("mbarrier.init.shared::cta.b64 [%0], %1;" :: "r"(bar), "r"(cnt) : "memory");
}
__device__ __forceinline__ void mbar_arrive(uint32_t bar, uint32_t cnt) {
    asm volatile("mbarrier.arrive.shared::cta.b64 _, [%0], %1;" :: "r"(bar), "r"(cnt) : "memory");
}
__device__ __forceinline__ uint32_t time_ns() { uint32_t t; asm volatile("mov.u32 %0, %globaltimer_lo;" : "=r"(t)); return t; }
__device__ __forceinline__ void wait_until(uint32_t t0, uint32_t dt) { while (time_ns() - t0 < dt) {} }
__device__ __forceinline__ void mbar_wait(uint32_t bar) {
    asm volatile("{\n.reg .pred p;\nWAIT_LOOP:\nmbarrier.try_wait.parity.shared::cta.b64 p, [%0], 0;\n@!p bra WAIT_LOOP;\n}" :: "r"(bar) : "memory");
}
__device__ __forceinline__ void cp_async16_strip(uint32_t dst, const void* src) {
    asm volatile("cp.async.cg.shared.global.L2::128B [%0], [%1], 16;" :: "r"(dst), "l"(src) : "memory");
}
__device__ __forceinline__ void cp_async16_stream(uint32_t dst, const void* src) {
    asm volatile("{\n.reg .b64 pol;\ncreatepolicy.fractional.L2::evict_first.b64 pol, 1.0;\n"
                 "cp.async.cg.shared.global.L2::cache_hint [%0], [%1], 16, pol;\n}" :: "r"(dst), "l"(src) : "memory");
}
__device__ __forceinline__ void cp_async_arrive(uint32_t bar) {
    asm volatile("cp.async.mbarrier.arrive.noinc.shared::cta.b64 [%0];" :: "r"(bar) : "memory");
}
__device__ __forceinline__ void bar_sync(int id, int n)   { asm volatile("bar.sync %0, %1;" :: "r"(id), "r"(n) : "memory"); }
__device__ __forceinline__ void bar_arrive(int id, int n) { asm volatile("bar.arrive %0, %1;" :: "r"(id), "r"(n) : "memory"); }

__device__ __forceinline__ uint2 ld_poll2(const void* p) {
    uint2 v;
    asm volatile("ld.relaxed.gpu.global.v2.u32 {%0,%1}, [%2];" : "=r"(v.x), "=r"(v.y) : "l"(p) : "memory");
    return v;
}
__device__ __forceinline__ uint4 ld_poll4(const void* p) {
    uint4 v;
    asm volatile("ld.relaxed.gpu.global.v4.u32 {%0,%1,%2,%3}, [%4];" : "=r"(v.x), "=r"(v.y), "=r"(v.z), "=r"(v.w) : "l"(p) : "memory");
    return v;
}
__device__ __forceinline__ void st_pub64(void* p, uint32_t a, uint32_t b) {
    asm volatile("{\n.reg .b64 d;\nmov.b64 d, {%1,%2};\nst.relaxed.gpu.global.b64 [%0], d;\n}" :: "l"(p), "r"(a), "r"(b) : "memory");
}
__device__ __forceinline__ void st_pub2x64(void* p, uint32_t a, uint32_t b, uint32_t c, uint32_t d) {
    asm volatile("{\n.reg .b64 d, e;\nmov.b64 d, {%1,%2};\nmov.b64 e, {%3,%4};\nst.relaxed.gpu.global.v2.b64 [%0], {d,e};\n}"
                 :: "l"(p), "r"(a), "r"(b), "r"(c), "r"(d) : "memory");
}
__device__ __forceinline__ void st_pub2(void* p, uint32_t a, uint32_t b) {
    asm volatile("st.relaxed.gpu.global.v2.u32 [%0], {%1,%2};" :: "l"(p), "r"(a), "r"(b) : "memory");
}
__device__ __forceinline__ void st_pub1(void* p, uint32_t a) {
    asm volatile("st.relaxed.gpu.global.u32 [%0], %1;" :: "l"(p), "r"(a) : "memory");
}
__device__ __forceinline__ uint32_t tagf(float v, uint32_t tag) {
    uint32_t r;
    asm("lop3.b32 %0, %1, 0xfffffffe, %2, 0xEA;" : "=r"(r) : "r"(__float_as_uint(v)), "r"(tag));
    return r;
}
__device__ __forceinline__ uint32_t pin(uint32_t v) {
    uint32_t r;
    asm volatile("shfl.sync.bfly.b32 %0, %1, 0, 0x1f, 0xffffffff;" : "=r"(r) : "r"(v));
    return r;
}
template <class T>
__device__ __forceinline__ T* pin(T* p) {
    const uint64_t u = reinterpret_cast<uint64_t>(p);
    return reinterpret_cast<T*>(((uint64_t)pin((uint32_t)(u >> 32)) << 32) | pin((uint32_t)u));
}
__device__ __forceinline__ void sts32(uint32_t addr, uint32_t v) { asm volatile("st.shared.u32 [%0], %1;" :: "r"(addr), "r"(v) : "memory"); }
__device__ __forceinline__ float lds32(uint32_t addr) { float v; asm volatile("ld.shared.f32 %0, [%1];" : "=f"(v) : "r"(addr) : "memory"); return v; }
__device__ __forceinline__ uint4 lds128(uint32_t addr) {
    uint4 v;
    asm volatile("ld.shared.v4.u32 {%0,%1,%2,%3}, [%4];" : "=r"(v.x), "=r"(v.y), "=r"(v.z), "=r"(v.w) : "r"(addr) : "memory");
    return v;
}
__device__ __forceinline__ uint32_t bad2(uint32_t a, uint32_t b, uint32_t tag) {
    uint32_t r;
    asm("lop3.b32 %0, %1, %2, %3, 0x7E;" : "=r"(r) : "r"(a), "r"(b), "r"(tag));
    return r;
}
__device__ __forceinline__ uint32_t bad4(const uint4& v, uint32_t tag) { return bad2(v.x, v.y, tag) | bad2(v.z, v.w, tag); }
__device__ __forceinline__ bool warp_bad(uint32_t bad) { return __any_sync(0xffffffffu, bad & 1u); }

#define POLL_HEAD(P, T, N)                                                                                        \
    ".reg .pred p0, p1, p2, p3, q;\n"                                                                             \
    ".reg .b32 a, m, it, y<16>;\n"                                                                                \
    ".reg .b64 d<8>;\n"                                                                                           \
    "setp.eq.u32 p0, 0, 0;\nsetp.eq.u32 p1, 0, 0;\nsetp.eq.u32 p2, 0, 0;\nsetp.eq.u32 p3, 0, 0;\n"                \
    "mov.u32 it, " N ";\n"                                                                                        \
    "POLL_LOOP:\n"                                                                                                \
    "@p0 ld.relaxed.gpu.global.v2.b64 {d0,d1}, [" P "];\n"                                                        \
    "@p1 ld.relaxed.gpu.global.v2.b64 {d2,d3}, [" P "+512];\n"                                                    \
    "@p2 ld.relaxed.gpu.global.v2.b64 {d4,d5}, [" P "+1024];\n"                                                   \
    "@p3 ld.relaxed.gpu.global.v2.b64 {d6,d7}, [" P "+1536];\n"                                                   \
    "sub.u32 it, it, 1;\n"                                                                                        \
    "min.u32 m, it, 1;\n"                                                        \
    "mov.b64 {y0,y1}, d0;\nmov.b64 {y2,y3}, d1;\nmov.b64 {y4,y5}, d2;\nmov.b64 {y6,y7}, d3;\n"                    \
    "mov.b64 {y8,y9}, d4;\nmov.b64 {y10,y11}, d5;\nmov.b64 {y12,y13}, d6;\nmov.b64 {y14,y15}, d7;\n"              \
    "xor.b32 y0, y0, " T ";\nxor.b32 y2, y2, " T ";\nlop3.b32 a, y0, y2, m, 0xA8;\nsetp.ne.u32 p0, a, 0;\n"       \
    "xor.b32 y4, y4, " T ";\nxor.b32 y6, y6, " T ";\nlop3.b32 a, y4, y6, m, 0xA8;\nsetp.ne.u32 p1, a, 0;\n"       \
    "xor.b32 y8, y8, " T ";\nxor.b32 y10, y10, " T ";\nlop3.b32 a, y8, y10, m, 0xA8;\nsetp.ne.u32 p2, a, 0;\n"    \
    "xor.b32 y12, y12, " T ";\nxor.b32 y14, y14, " T ";\nlop3.b32 a, y12, y14, m, 0xA8;\nsetp.ne.u32 p3, a, 0;\n" \
    "or.pred q, p0, p1;\nor.pred q, q, p2;\nor.pred q, q, p3;\nvote.sync.any.pred q, q, 0xffffffff;\n"
#define POLL_TAIL "@q bra POLL_LOOP;\n"

__device__ __forceinline__ void poll4(float (&f)[2][4], const uint4* p, uint32_t tag, const float (&w)[4]) {
    asm volatile("{\n" POLL_HEAD("%8", "%9", "%14") POLL_TAIL
                 "mul.f32 %0, y0, %10;\nmul.f32 %1, y1, %10;\nmul.f32 %2, y2, %10;\nmul.f32 %3, y3, %10;\n"
                 "mul.f32 %4, y8, %12;\nmul.f32 %5, y9, %12;\nmul.f32 %6, y10, %12;\nmul.f32 %7, y11, %12;\n"
                 "fma.rn.f32 %0, y4, %11, %0;\nfma.rn.f32 %1, y5, %11, %1;\nfma.rn.f32 %2, y6, %11, %2;\nfma.rn.f32 %3, y7, %11, %3;\n"
                 "fma.rn.f32 %4, y12, %13, %4;\nfma.rn.f32 %5, y13, %13, %5;\nfma.rn.f32 %6, y14, %13, %6;\nfma.rn.f32 %7, y15, %13, %7;\n"
                 "}"
                 : "=&f"(f[0][0]), "=&f"(f[0][1]), "=&f"(f[0][2]), "=&f"(f[0][3]), "=&f"(f[1][0]), "=&f"(f[1][1]), "=&f"(f[1][2]), "=&f"(f[1][3])
                 : "l"(p), "r"(tag), "f"(w[0]), "f"(w[1]), "f"(w[2]), "f"(w[3]), "n"(SPIN_LIMIT) : "memory");
}
__device__ __forceinline__ void poll4_sum(float (&keep)[2], float (&recv)[2], const uint4* p, uint32_t tag, uint32_t hi) {
    asm volatile("{\n.reg .pred h;\n.reg .f32 s<8>;\nsetp.ne.u32 h, %6, 0;\n" POLL_HEAD("%4", "%5", "%7")
                 "add.f32 s0, y0, y4;\nadd.f32 s1, y1, y5;\nadd.f32 s2, y2, y6;\nadd.f32 s3, y3, y7;\n"
                 "add.f32 s4, y8, y12;\nadd.f32 s5, y9, y13;\nadd.f32 s6, y10, y14;\nadd.f32 s7, y11, y15;\n"
                 "add.f32 s0, s0, s4;\nadd.f32 s1, s1, s5;\nadd.f32 s2, s2, s6;\nadd.f32 s3, s3, s7;\n"
                 "selp.f32 s4, s0, s2, h;\nselp.f32 s5, s1, s3, h;\nselp.f32 %0, s2, s0, h;\nselp.f32 %1, s3, s1, h;\n"
                 "shfl.sync.bfly.b32 %2, s4, 16, 0x1f, 0xffffffff;\nshfl.sync.bfly.b32 %3, s5, 16, 0x1f, 0xffffffff;\n"
                 POLL_TAIL "}"
                 : "=&f"(keep[0]), "=&f"(keep[1]), "=&f"(recv[0]), "=&f"(recv[1])
                 : "l"(p), "r"(tag), "r"(hi), "n"(SPIN_LIMIT) : "memory");
}

__device__ __forceinline__ void ldsm4(uint32_t addr, uint32_t (&a)[4]) {
    asm volatile("ldmatrix.sync.aligned.m8n8.x4.shared.b16 {%0,%1,%2,%3}, [%4];" : "=r"(a[0]), "=r"(a[1]), "=r"(a[2]), "=r"(a[3]) : "r"(addr) : "memory");
}
__device__ __forceinline__ void ldsm4t(uint32_t addr, uint32_t (&a)[4]) {
    asm volatile("ldmatrix.sync.aligned.m8n8.x4.trans.shared.b16 {%0,%1,%2,%3}, [%4];" : "=r"(a[0]), "=r"(a[1]), "=r"(a[2]), "=r"(a[3]) : "r"(addr) : "memory");
}
__device__ __forceinline__ void mma16816(float (&c)[4], const uint32_t (&a)[4], uint32_t b0, uint32_t b1) {
    asm volatile("mma.sync.aligned.m16n8k16.row.col.f32.bf16.bf16.f32 {%0,%1,%2,%3}, {%4,%5,%6,%7}, {%8,%9}, {%0,%1,%2,%3};"
                 : "+f"(c[0]), "+f"(c[1]), "+f"(c[2]), "+f"(c[3]) : "r"(a[0]), "r"(a[1]), "r"(a[2]), "r"(a[3]), "r"(b0), "r"(b1));
}
__device__ __forceinline__ float bf_lo(uint32_t u) { return __uint_as_float(u << 16); }
__device__ __forceinline__ float bf_hi(uint32_t u) { return __uint_as_float(u & 0xffff0000u); }
__device__ __forceinline__ float rbf(float v) { return __bfloat162float(__float2bfloat16_rn(v)); }
__device__ __forceinline__ uint32_t pack_bf(float lo, float hi) {
    uint32_t r;
    asm("cvt.rn.bf16x2.f32 %0, %1, %2;" : "=r"(r) : "f"(hi), "f"(lo));
    return r;
}
__device__ __forceinline__ float sel4(const float (&c)[4], int t) {
    float a = (t & 1) ? c[1] : c[0];
    float b = (t & 1) ? c[3] : c[2];
    return (t & 2) ? b : a;
}
__device__ __forceinline__ float ex2(float x) { float y; asm("ex2.approx.ftz.f32 %0, %1;" : "=f"(y) : "f"(x)); return y; }
__device__ __forceinline__ float sqrt_approx(float x) { float y; asm("sqrt.approx.f32 %0, %1;" : "=f"(y) : "f"(x)); return y; }

__host__ __device__ constexpr uint32_t slot_of(int s) { return SM_RING + (s % NS) * SLOT; }

__device__ __forceinline__ void layernorm(unsigned char* smem, int lane) {
    uint32_t xs[2][7];
#pragma unroll
    for (int b = 0; b < 2; b++)
#pragma unroll
        for (int i = 0; i < 7; i++) xs[b][i] = reinterpret_cast<const uint32_t*>(smem + SM_X)[b * (D_MODEL / 2) + i * 32 + lane];
#pragma unroll
    for (int b = 0; b < 2; b++) {
        float sum = 0.f;
#pragma unroll
        for (int i = 0; i < 7; i++) sum += bf_lo(xs[b][i]) + bf_hi(xs[b][i]);
#pragma unroll
        for (int o = 16; o > 0; o >>= 1) sum += __shfl_xor_sync(0xffffffffu, sum, o);
        const float mean = sum * (1.0f / D_MODEL);
        float sq = 0.f;
#pragma unroll
        for (int i = 0; i < 7; i++) {
            const float d0 = bf_lo(xs[b][i]) - mean, d1 = bf_hi(xs[b][i]) - mean;
            sq = fmaf(d0, d0, fmaf(d1, d1, sq));
        }
#pragma unroll
        for (int o = 16; o > 0; o >>= 1) sq += __shfl_xor_sync(0xffffffffu, sq, o);
        const float mb = rbf(mean);
        const float sd = rbf(sqrt_approx(rbf(rbf(sq * (1.0f / D_MODEL)) + 1e-5f)));
#pragma unroll
        for (int i = 0; i < 7; i++)
            reinterpret_cast<uint32_t*>(smem + SM_XN + b * XROW)[i * 32 + lane] =
                pack_bf(__fdividef(rbf(bf_lo(xs[b][i]) - mb), sd), __fdividef(rbf(bf_hi(xs[b][i]) - mb), sd));
    }
}

__device__ __forceinline__ void strip_partial(uint32_t sb, uint32_t strip, unsigned char* smem, int warp, int lane) {
    float c[2][2][4];
#pragma unroll
    for (int n = 0; n < 2; n++)
#pragma unroll
        for (int e = 0; e < 4; e++) c[n][0][e] = c[n][1][e] = 0.f;
    const uint32_t ba = sb + SM_XN + (lane & 1) * XROW + (lane >> 3) * 16 + warp * 128;
    const uint32_t aa = sb + strip + (warp * 64 + (lane & 7) + (lane >> 4) * 8) * 64 + (((lane >> 3) & 1) ^ ((lane & 7) >> 1)) * 16;
#pragma unroll
    for (int k2 = 0; k2 < 2; k2++) {
        uint32_t b[4];
        ldsm4(ba + k2 * 64, b);
#pragma unroll
        for (int n = 0; n < 2; n++) {
            uint32_t a0[4], a1[4];
            ldsm4t((aa ^ (n * 32)) + k2 * 2048, a0);
            ldsm4t((aa ^ (n * 32)) + k2 * 2048 + 1024, a1);
            mma16816(c[n][0], a0, b[0], b[1]);
            mma16816(c[n][1], a1, b[2], b[3]);
        }
    }
    float* red = reinterpret_cast<float*>(smem + SM_RED) + warp * 64 + lane;
#pragma unroll
    for (int n = 0; n < 2; n++) red[n * 32] = sel4(c[n][0], lane & 3) + sel4(c[n][1], lane & 3);
}
__device__ __forceinline__ float strip_sum(const unsigned char* smem, int idx) {
    const float* red = reinterpret_cast<const float*>(smem + SM_RED) + idx;
    return ((red[0] + red[64]) + (red[128] + red[192])) + ((red[256] + red[320]) + red[384]);
}

__device__ __forceinline__ uint32_t time_base(uint32_t sb, int i) {
    uint32_t t;
    asm volatile("ld.volatile.shared.u32 %0, [%1];" : "=r"(t) : "r"(sb + SM_T0 + 4 * i) : "memory");
    return t;
}
__device__ __forceinline__ void wait_clock(uint32_t sb, int i, uint32_t dt) { while (time_ns() - time_base(sb, i) < dt) {} }

struct Prod {
    uint32_t sb, kvdst, sdst;
    const char *k, *v;
    const __nv_bfloat16* gu;
    bool ffn;
};
__host__ __device__ constexpr int bytes_before(int s) { return 28672 + s * 16384 + (s <= S_GU ? 0 : s < S_GU + 14 ? s - S_GU : 14) * 1792; }
__host__ __device__ constexpr int issue_time(int s) {
    return (int)((long long)bytes_before(s) * PACE_DT / 16384) - PACE_LEAD;
}

template <int S>
__device__ __forceinline__ void produce(Prod& p) {
    if constexpr (S < NSTAGE) {
        if constexpr (S >= NS) mbar_wait(p.sb + SM_BAR + (NBAR + S - NS) * 8);
        wait_clock(p.sb, 0, issue_time(S));
        const char* src = (S < S_V ? p.k : p.v) + (S & 15) * (8 * SLOT);
#pragma unroll
        for (int i = 0; i < 8; i++) cp_async16_stream((p.kvdst ^ ((i & 1) * 64)) + slot_of(S) + i * 2048, src + i * 2048);
        if constexpr (S >= S_GU && S < S_GU + 14) {
            if (p.ffn) cp_async16_strip(p.sdst + (S - S_GU) * 2048, p.gu + (size_t)(S - S_GU) * 32 * FF);
        }
        cp_async_arrive(p.sb + SM_BAR + S * 8);
        produce<S + 1>(p);
    }
}

__device__ __forceinline__ void fetch16(uint32_t dst, const char* src) {
#pragma unroll
    for (int i = 0; i < 4; i++)
        asm volatile("cp.async.cg.shared.global [%0], [%1], 16;" :: "r"((dst ^ (((i & 1) ^ (i >> 1)) * 64)) + i * 512), "l"(src + i * (4 * 896)) : "memory");
}
template <int PENDING, int OFF>
__device__ __forceinline__ void frag16(uint32_t (&a)[4][4], uint32_t addr) {
    asm volatile("cp.async.wait_group %0;" :: "n"(PENDING) : "memory");
    __syncwarp();
#pragma unroll
    for (int m = 0; m < 4; m++) ldsm4t((addr ^ (m * 32)) + OFF, a[m]);
}

__device__ __forceinline__ void load_x(uint32_t sb, const void* x, const void* epoch) {
    const uint32_t full0 = sb + SM_BAR;
    mbar_init(full0 + B_X * 8, 1);
    asm volatile("fence.mbarrier_init.release.cluster;" ::: "memory");
    asm volatile("mbarrier.arrive.expect_tx.shared::cta.b64 _, [%0], %1;" :: "r"(full0 + B_X * 8), "r"(1792 + 16) : "memory");
    asm volatile("cp.async.bulk.shared::cluster.global.mbarrier::complete_tx::bytes [%0], [%1], %2, [%3];"
                 :: "r"(sb + SM_X), "l"(x), "r"(1792), "r"(full0 + B_X * 8) : "memory");
    asm volatile("cp.async.bulk.shared::cluster.global.mbarrier::complete_tx::bytes [%0], [%1], %2, [%3];"
                 :: "r"(sb + SM_X + 1792), "l"(epoch), "r"(16), "r"(full0 + B_X * 8) : "memory");
}

enum { BAR_OB = 1, BAR_CONS = 2, BAR_LN = 3, BAR_FF = 4, BAR_FIN = 5, BAR_H = 6 };

__global__ void __launch_bounds__(NTHREADS, 1)
fused_decode_kernel(const __nv_bfloat16* __restrict__ wq, const __nv_bfloat16* __restrict__ kc, const __nv_bfloat16* __restrict__ x,
                    Scratch* __restrict__ scr, const __nv_bfloat16* __restrict__ vc, const __nv_bfloat16* __restrict__ wo,
                    const __nv_bfloat16* __restrict__ wg, const __nv_bfloat16* __restrict__ wu, const __nv_bfloat16* __restrict__ wd,
                    __nv_bfloat16* __restrict__ out) {
    extern __shared__ __align__(128) unsigned char smem[];
    const uint32_t sb = (uint32_t)__cvta_generic_to_shared(smem);
    const int tid = threadIdx.x, lane = tid & 31;
    const int cta = blockIdx.x;
    const uint32_t full0 = sb + SM_BAR, done0 = full0 + NBAR * 8;
    const uint32_t t0 = time_ns();
    if (tid < 224) {
        const int row = (tid >> 5) * 64 + (lane >> 2);
        const char* src = reinterpret_cast<const char*>(wq) + (uint32_t)(row * (QCOLS * 2) + cta * 64 + (lane & 3) * 16);
        const uint32_t dst = sb + SM_STRIP + row * 64 + ((lane & 3) ^ (lane >> 3)) * 16;
#pragma unroll
        for (int i = 0; i < 8; i++) cp_async16_strip(dst + i * 512, src + i * (8 * QCOLS * 2));
    }
    const int warp = __shfl_sync(0xffffffffu, tid >> 5, 0);
    const int hkv = cta >> 4, j = cta & 15, bat = j >> 3, sp = j & 7;
    const int g = lane >> 2, t = lane & 3;

    if (warp < 8) {
        if (tid == 224) load_x(sb, x, &scr->epoch[cta * 8]);
        __syncthreads();
        mbar_wait(full0 + B_X * 8);
        const uint32_t epoch = *reinterpret_cast<const uint32_t*>(smem + SM_X + 1792);
        const uint32_t tag = pin((epoch + 1) & 1);
        uint32_t* qdst = reinterpret_cast<uint32_t*>(scr->q) + (hkv * 2 + (t & 1)) * 512 + j * 32 + warp * 16 + g + 8 * (t >> 1);
        if (warp == 7) {
            layernorm(smem, lane);
            bar_arrive(BAR_LN, 256);
        } else {
            asm volatile("cp.async.wait_all;" ::: "memory");
            bar_sync(BAR_LN, 256);
            strip_partial(sb, SM_STRIP, smem, warp, lane);
        }
        bar_sync(BAR_CONS, 256);
        if (warp < 2) {
            st_pub1(qdst, (pack_bf(0.f, strip_sum(smem, tid)) & 0xffff0000u) | tag);
        } else if (warp >= 4) {
            const int i = tid - 128;
            const uint4* qp = scr->q + (hkv * 2 + bat) * 128 + i;
            wait_until(t0, Q_T);
            uint4 v;
            int it = 0;
            do {
                v = ld_poll4(qp);
                if (++it > SPIN_LIMIT) __trap();
            } while (warp_bad(bad4(v, tag)));
            *reinterpret_cast<uint2*>(smem + SM_Q + (i >> 6) * 528 + (i & 63) * 8) =
                make_uint2(__byte_perm(v.x, v.y, 0x7632), __byte_perm(v.z, v.w, 0x7632));
        }
        bar_sync(BAR_CONS, 256);
        if (tid == 96) scr->epoch[cta * 8] = epoch + 1;
        {
            uint32_t qf[8][4];
#pragma unroll
            for (int k2 = 0; k2 < 8; k2++) ldsm4(sb + SM_Q + (lane & 1) * 528 + k2 * 64 + (lane >> 3) * 16, qf[k2]);
            const int mt = warp & 1;
            const uint32_t aoff = (16 * mt + (lane & 15)) * 512 + ((lane >> 4) ^ (lane & 7)) * 16;
            float* sc = reinterpret_cast<float*>(smem + SM_S) + (t & 1) * 520 + (g >> 1) * 8 + (2 * mt + (t >> 1)) * 2 + (g & 1);
#pragma unroll 1
            for (int k = warp >> 1; k < 16; k += 4) {
                const int s = S_K + k;
                mbar_wait(full0 + s * 8);
                const uint32_t base = sb + SM_RING + (s >= NS ? s - NS : s) * SLOT + aoff;
                float c0[4] = {0.f, 0.f, 0.f, 0.f}, c1[4] = {0.f, 0.f, 0.f, 0.f};
#pragma unroll
                for (int k2 = 0; k2 < 8; k2++) {
                    uint32_t a0[4], a1[4];
                    ldsm4((base ^ ((k2 & 1) * 64)) + (k2 >> 1) * 128, a0);
                    ldsm4((base ^ ((k2 & 1) * 64 + 32)) + (k2 >> 1) * 128, a1);
                    mma16816(c0, a0, qf[k2][0], qf[k2][1]);
                    mma16816(c1, a1, qf[k2][2], qf[k2][3]);
                }
                __syncwarp();
                if (lane == 0) mbar_arrive(done0 + s * 8, 4);
                sc[k * 32] = rbf(sel4(c0, t) + sel4(c1, t));
            }
        }
        bar_sync(BAR_CONS, 256);
        {
            constexpr float C = SCALE_LOG2E;
            const float* sc = reinterpret_cast<const float*>(smem + SM_S);
            float* stat = reinterpret_cast<float*>(smem + SM_STAT);
            const float2 s0 = *reinterpret_cast<const float2*>(sc + 2 * tid);
            const float2 s1 = *reinterpret_cast<const float2*>(sc + 520 + 2 * tid);
            float m0 = fmaxf(s0.x, s0.y), m1 = fmaxf(s1.x, s1.y);
#pragma unroll
            for (int o = 16; o > 0; o >>= 1) {
                m0 = fmaxf(m0, __shfl_xor_sync(0xffffffffu, m0, o));
                m1 = fmaxf(m1, __shfl_xor_sync(0xffffffffu, m1, o));
            }
            if (lane == 0) *reinterpret_cast<float2*>(stat + warp * 2) = make_float2(m0, m1);
            bar_sync(BAR_CONS, 256);
#pragma unroll
            for (int w = 0; w < 8; w++) {
                const float2 mm = *reinterpret_cast<const float2*>(stat + w * 2);
                m0 = fmaxf(m0, mm.x); m1 = fmaxf(m1, mm.y);
            }
            const float p00 = ex2((s0.x - m0) * C), p01 = ex2((s0.y - m0) * C);
            const float p10 = ex2((s1.x - m1) * C), p11 = ex2((s1.y - m1) * C);
            uint32_t* ps = reinterpret_cast<uint32_t*>(smem + SM_P);
            ps[tid] = pack_bf(p00, p01);
            ps[272 + tid] = pack_bf(p10, p11);
            float l0 = p00 + p01, l1 = p10 + p11;
#pragma unroll
            for (int o = 16; o > 0; o >>= 1) {
                l0 += __shfl_xor_sync(0xffffffffu, l0, o);
                l1 += __shfl_xor_sync(0xffffffffu, l1, o);
            }
            if (lane == 0) *reinterpret_cast<float2*>(stat + 16 + warp * 2) = make_float2(l0, l1);
            bar_sync(BAR_CONS, 256);
            if (tid < 4) {
                float l = 0.f;
#pragma unroll
                for (int w = 0; w < 8; w++) l += stat[16 + w * 2 + (tid & 1)];
                st_pub2(scr->ml + cta * 4 + tid, tagf((tid & 1) ? m1 : m0, tag), tagf(l, tag));
            }
        }
        float wgt[2] = {0.f, 0.f};
        {
            float o0[4] = {0.f, 0.f, 0.f, 0.f}, o1[4] = {0.f, 0.f, 0.f, 0.f};
            float o2[4] = {0.f, 0.f, 0.f, 0.f}, o3[4] = {0.f, 0.f, 0.f, 0.f};
            const uint32_t aoff = ((lane & 7) + (lane >> 4) * 8) * 512 + ((warp * 4 + ((lane >> 3) & 1) * 2) ^ (lane & 7)) * 16;
            const uint4* ps = reinterpret_cast<const uint4*>(smem + SM_P + (g & 1) * 272 * 4) + t;
            uint32_t* dst = reinterpret_cast<uint32_t*>(scr->part) + ((size_t)(hkv * 16 + (t & 1) * 8 + warp) * 16 + j) * 32 +
                            (4 * (g & 3) + (t & 2) + (g >> 2)) * 2;
#pragma unroll
            for (int k = 0; k < 16; k++) {
                const uint4 pa = ps[k * 4];
                mbar_wait(full0 + (S_V + k) * 8);
                uint32_t a[4][4];
#pragma unroll
                for (int i = 0; i < 4; i++) ldsm4t(sb + (aoff ^ ((i & 1) * 16)) + slot_of(S_V + k) + (i >> 1) * 8192, a[i]);
                mma16816(o0, a[0], pa.x, pa.y);
                mma16816(o1, a[1], pa.x, pa.y);
                mma16816(o2, a[2], pa.z, pa.w);
                mma16816(o3, a[3], pa.z, pa.w);
                if (S_V + k + NS < NSTAGE + 3) {
                    __syncwarp();
                    if (lane == 0) mbar_arrive(done0 + (S_V + k) * 8, 1);
                }
                if (k == FFN_ST && warp < 7) {
                    strip_partial(sb, SM_STRIP, smem, warp, lane);
                    bar_arrive(BAR_FF, 256);
                }
                if (k == FFN_ST && warp == 7) {
                    const uint2* mlp = scr->ml + (hkv * 16 + g) * 4 + (j >> 3);
                    uint2 a, b;
                    int it = 0;
                    do {
                        a = ld_poll2(mlp); b = ld_poll2(mlp + 32);
                        if (++it > SPIN_LIMIT) __trap();
                    } while (warp_bad(bad2(a.x, a.y, tag) | bad2(b.x, b.y, tag)));
                    float m[2] = {bf_hi(a.x), bf_hi(b.x)};
                    float l[2] = {__uint_as_float(a.y ^ tag), __uint_as_float(b.y ^ tag)};
#pragma unroll
                    for (int bb = 0; bb < 2; bb++) {
                        float M = m[bb];
                        M = fmaxf(M, __shfl_xor_sync(0xffffffffu, M, 4));
                        M = fmaxf(M, __shfl_xor_sync(0xffffffffu, M, 8));
                        M = fmaxf(M, __shfl_xor_sync(0xffffffffu, M, 16));
                        const float e = ex2((m[bb] - M) * SCALE_LOG2E);
                        float L = e * l[bb];
                        L += __shfl_xor_sync(0xffffffffu, L, 4);
                        L += __shfl_xor_sync(0xffffffffu, L, 8);
                        L += __shfl_xor_sync(0xffffffffu, L, 16);
                        wgt[bb] = __fdividef(e, L);
                    }
                    bar_sync(BAR_FF, 256);
                    float ga = rbf(strip_sum(smem, lane));
                    ga *= (ga > 0.f ? 1.f : 0.f);
                    const float hv = ga * rbf(strip_sum(smem, 32 + lane));
                    const uint32_t w = pack_bf(hv, __shfl_xor_sync(0xffffffffu, hv, 2));
                    if (!(t & 2)) reinterpret_cast<uint32_t*>(smem + SM_H)[(t & 1) * 8 + (g & 3) * 2 + (g >> 2)] = w;
                    bar_arrive(BAR_H, 256);
                }
                if (k == PRE_ST) st_pub64(dst, tag ^ 1, 0);
            }
            const float v0 = sel4(o0, t) + sel4(o2, t), v1 = sel4(o1, t) + sel4(o3, t);
            st_pub64(dst, tagf(v0, tag), __float_as_uint(v1));
        }
        if (warp == 7) {
            const uint4* pp = pin(scr->part + (size_t)cta * 128 + lane);
            const uint32_t obaddr = pin(sb + SM_OB + (lane >> 4) * 64 + (lane & 7) * 8 + ((lane >> 3) & 1) * 4), ll = pin(lane);
            float w[4];
#pragma unroll
            for (int i = 0; i < 4; i++) w[i] = __shfl_sync(0xffffffffu, wgt[i >> 1], ((i & 1) * 4 + (lane >> 3)) * 4);
            wait_until(time_base(sb, 2), E2_T);
            float f[2][4];
            poll4(f, pp, tag, w);
            const bool h16 = ll & 16, h8 = ll & 8;
            float r4[4], r2[2];
#pragma unroll
            for (int e = 0; e < 4; e++) r4[e] = (h16 ? f[1][e] : f[0][e]) + __shfl_xor_sync(0xffffffffu, h16 ? f[0][e] : f[1][e], 16);
#pragma unroll
            for (int e = 0; e < 2; e++) r2[e] = (h8 ? r4[2 + e] : r4[e]) + __shfl_xor_sync(0xffffffffu, h8 ? r4[e] : r4[2 + e], 8);
            sts32(obaddr, pack_bf(r2[0], r2[1]));
            bar_arrive(BAR_OB, 256);
        } else if (warp < 4 && (cta & 1) == 0 && cta < 2 * NRED) {
            const uint4* op = pin(scr->outp + (size_t)(cta >> 1) * (NCTA * 4) + warp * 128 + lane);
            const int oidx = (t & 1) * D_MODEL + hkv * 64 + (lane >> 3) * 16 + (j >> 1) + (t >> 1) * 8;
            const float xv = __bfloat162float(reinterpret_cast<const __nv_bfloat16*>(smem + SM_X)[oidx]);
            __nv_bfloat16* optr = pin(out + oidx);
            const uint32_t red = pin(sb + SM_S + tid * 4), ll = pin(lane);
            float r2[2], rcv[2];
            const bool h8 = ll & 8;
            wait_until(time_base(sb, 3), E3_T);
            poll4_sum(r2, rcv, op, tag, ll & 16);
            r2[0] += rcv[0]; r2[1] += rcv[1];
            float r = (h8 ? r2[1] : r2[0]) + __shfl_xor_sync(0xffffffffu, h8 ? r2[0] : r2[1], 8);
            r += __shfl_xor_sync(0xffffffffu, r, 4);
            if (warp != 0) {
                sts32(red, __float_as_uint(r));
                bar_arrive(BAR_FIN, 128);
            } else {
                bar_sync(BAR_FIN, 128);
                r = ((xv + r) + lds32(red + 128)) + (lds32(red + 256) + lds32(red + 384));
                asm volatile("st.global.u16 [%0], %1;" :: "l"(optr), "h"(__bfloat16_as_ushort(__float2bfloat16_rn(r))) : "memory");
            }
        }
    } else if (warp < 15) {
        const int pt = tid - 256, pw = warp - 8;
        const char* pdn = reinterpret_cast<const char*>(wd) + (size_t)cta * 14336 + (lane >> 3) * 896 + pw * 128 + (lane & 7) * 16;
        const char* pwo = reinterpret_cast<const char*>(wo) + (size_t)cta * 28672 + (lane >> 3) * 896 + pw * 128 + (lane & 7) * 16;
        if (pw < 4) {
            if (lane == 0) {
#pragma unroll
                for (int i = 0; i < 9; i++) {
                    if (pw * 9 + i != B_X) mbar_init(full0 + (pw * 9 + i) * 8, NPT);
                    mbar_init(done0 + (pw * 9 + i) * 8, 8);
                }
            }
            Prod p;
            const size_t kvoff = ((size_t)(bat * 8 + hkv) * SK + (SK - WIN)) * DH * 2 + sp * SLOT + pt * 16;
            p.sb = sb;
            p.kvdst = (sb + pt * 16) ^ (pw * 16);
            p.sdst = sb + SM_STRIP + (pt >> 2) * 64 + ((pt & 3) ^ ((pt >> 3) & 3)) * 16;
            p.k = reinterpret_cast<const char*>(kc) + kvoff;
            p.v = reinterpret_cast<const char*>(vc) + kvoff;
            p.gu = ((pt & 2) ? wu : wg) + cta * 16 + (pt & 1) * 8 + (size_t)(pt >> 2) * FF;
            p.ffn = cta < NFFN;
            __syncthreads();
            produce<0>(p);
        } else {
            __syncthreads();
        }
        mbar_wait(full0 + B_X * 8);
        const uint32_t tag = pin((*reinterpret_cast<const uint32_t*>(smem + SM_X + 1792) + 1) & 1);
        if (pw == 4 && (cta & 3) == 0) {
#pragma unroll 1
            for (int i = 0; i < 4; i++) {
                uint32_t sum = 0;
#pragma unroll
                for (int k = 0; k < NM; k++) {
                    mbar_wait(full0 + (MEND - NM + 1 + k + 6 * i) * 8);
                    sum += time_ns() - t0;
                }
                if (lane < 4) st_pub2(&scr->prog[i * 128 + cta + lane], ((t0 + sum / NM) & ~1u) | tag, (t0 & ~1u) | tag);
            }
        }
        mbar_wait(done0 + (NSTAGE + 2 - NS) * 8);
        const uint32_t ta = LATE_T, td = LATE_DT;
        uint4* odst = scr->outp + ((size_t)(pt >> 2) * NCTA + cta) * 4 + t;
        st_pub2x64(odst, tag ^ 1, 0, tag ^ 1, 0);
        const uint32_t fdst = (sb + pw * 2048 + lane * 16) ^ ((lane >> 3) * 16);
        wait_clock(sb, 1, ta);
        if (cta < NFFN) fetch16(fdst + slot_of(NSTAGE), pdn);
        asm volatile("cp.async.commit_group;" ::: "memory");
        wait_clock(sb, 1, ta + td);
        fetch16(fdst + slot_of(NSTAGE + 1), pwo);
        asm volatile("cp.async.commit_group;" ::: "memory");
        wait_clock(sb, 1, ta + 2 * td);
        fetch16(fdst + slot_of(NSTAGE + 2), pwo + 14336);
        asm volatile("cp.async.commit_group;" ::: "memory");
        bar_sync(BAR_H, 256);
        const uint2 h = *reinterpret_cast<const uint2*>(smem + SM_H + (g & 1) * 32 + t * 8);
        float c[4][4];
#pragma unroll
        for (int m = 0; m < 4; m++)
#pragma unroll
            for (int e = 0; e < 4; e++) c[m][e] = 0.f;
        const int r7 = ((lane & 7) >> 1) + 4 * (lane >> 4);
        const uint32_t aoff = sb + pw * 2048 + (r7 + 8 * (lane & 1)) * 128 + (((lane >> 3) & 1) ^ r7 ^ ((lane & 1) << 2)) * 16;
        const uint32_t obaddr = pin(sb + SM_OB + (g & 1) * 64 + t * 16), tt = pin(t);
        uint32_t a0[4][4], a1[4][4];
        frag16<2, slot_of(NSTAGE)>(a0, aoff);
        if (cta < NFFN) {
#pragma unroll
            for (int m = 0; m < 4; m++) mma16816(c[m], a0[m], h.x, h.y);
        }
        frag16<1, slot_of(NSTAGE + 1)>(a1, aoff);
        bar_sync(BAR_OB, 256);
        const uint4 ob = lds128(obaddr);
#pragma unroll
        for (int m = 0; m < 4; m++) mma16816(c[m], a1[m], ob.x, ob.y);
        frag16<0, slot_of(NSTAGE + 2)>(a0, aoff);
#pragma unroll
        for (int m = 0; m < 4; m++) mma16816(c[m], a0[m], ob.z, ob.w);
        st_pub2x64(odst, tagf(sel4(c[0], tt), tag), __float_as_uint(sel4(c[1], tt)), tagf(sel4(c[2], tt), tag), __float_as_uint(sel4(c[3], tt)));
    } else if (warp == 15) {
        if (lane < 4) reinterpret_cast<uint32_t*>(smem + SM_T0)[lane] = t0;
        __syncthreads();
        mbar_wait(full0 + B_X * 8);
        const uint32_t tag = (*reinterpret_cast<const uint32_t*>(smem + SM_X + 1792) + 1) & 1;
#pragma unroll 1
        for (int i = 0; i < 4; i++) {
            mbar_wait(full0 + (MEND + 2 + 6 * i) * 8);
            uint2 v;
            int it = 0;
            do {
                v = ld_poll2(&scr->prog[i * 128 + lane * 4]);
                if (++it > SPIN_LIMIT) __trap();
            } while (warp_bad(bad2(v.x, v.y, tag)));
            const int nom = i == 0 ? M_NOM0 : i == 1 ? M_NOM1 : i == 2 ? M_NOM2 : M_NOM3;
            int base = (__reduce_add_sync(0xffffffffu, min(max((int)(v.x - t0), 0), 1 << 20)) >> 5) - nom;
            const int start = __reduce_add_sync(0xffffffffu, min(max((int)(v.y - t0), -(1 << 20)), 1 << 20)) >> 5;
            base = start + max(min(base - start, 2 * (base - start - DEAD)), 0);
            const int ahead = (lane == 0 ? nom : lane == 1 ? LATE_T : lane == 2 ? E2_T : E3_T - 150) - nom;
            const float rate = fminf(fmaxf(__fdividef((float)(base - start), (float)(nom - 500)), -0.01f), 0.045f);
            if (lane < 4) sts32(sb + SM_T0 + 4 * lane, t0 + base + (int)(rate * (float)ahead));
        }
    }
}

}

extern "C" void kernel_launch(void* const* d_in, const int* in_sizes, int n_in, void* d_out, int out_size) {
    (void)in_sizes; (void)n_in; (void)out_size;
    static Scratch* scr = nullptr;
    if (!scr) {
        cudaFuncSetAttribute(fused_decode_kernel, cudaFuncAttributeMaxDynamicSharedMemorySize, SM_TOTAL);
        cudaGetSymbolAddress(reinterpret_cast<void**>(&scr), g_scratch);
    }
    typedef const __nv_bfloat16* P;
    fused_decode_kernel<<<NCTA, NTHREADS, SM_TOTAL>>>((P)d_in[3], (P)d_in[1], (P)d_in[0], scr, (P)d_in[2], (P)d_in[4],
                                                      (P)d_in[6], (P)d_in[7], (P)d_in[8], (__nv_bfloat16*)d_out);
}
```

```cpp
#include <cuda_runtime.h>
#include <cuda_bf16.h>
#include <stdint.h>

namespace {

constexpr int PACE_DT = 640;
constexpr int PACE_LEAD = 350;
constexpr int LATE_T = 22370;
constexpr int LATE_DT = 400;
constexpr int Q_T = 4000;
constexpr int E2_T = 24090;
constexpr int E3_T = 24830;
constexpr int M_NOM0 = 4595;
constexpr int M_NOM1 = 8450;
constexpr int M_NOM2 = 12800;
constexpr int M_NOM3 = 17010;
constexpr int DEAD = 100;
constexpr int NM = 4;
constexpr int MEND = 5;
constexpr int MGAP = 3;
constexpr int NSLOT = 11;

constexpr int D_MODEL = 448;
constexpr int SK      = 32768;
constexpr int WIN     = 4096;
constexpr int DH      = 256;
constexpr int QCOLS   = 4096;
constexpr int FF      = 1792;
constexpr int NCTA    = 128;
constexpr int NFFN    = 112;
constexpr int NRED    = 56;
constexpr int NPT     = 128;
constexpr int NTHREADS = 512;

constexpr int NS     = NSLOT;
constexpr int SLOT   = 16384;
constexpr int XROW   = 912;
constexpr int S_K = 0, S_V = 16, NSTAGE = 32;
constexpr int S_GU   = NS;
constexpr int FFN_AT = 8;
constexpr int FFN_ST = FFN_AT;
constexpr int HID_AT = 11;
constexpr int HID_ST = HID_AT;
constexpr int PRE_ST = 12;
constexpr int NBAR   = 36;
constexpr int B_X = NSTAGE;

constexpr int SM_RING  = 0;
constexpr int SM_STRIP = SM_RING + NS * SLOT;
constexpr int SM_S    = SM_STRIP + 448 * 64;
constexpr int SM_P    = SM_S + 2 * 520 * 4;
constexpr int SM_Q    = SM_P + 2 * 272 * 4;
constexpr int SM_XN   = SM_Q + 2 * 264 * 2;
constexpr int SM_X    = SM_XN + 2 * XROW;
constexpr int SM_RED  = SM_X + 1792 + 32;
constexpr int SM_STAT = SM_RED + 7 * 64 * 4;
constexpr int SM_OB   = SM_STAT + 2 * 8 * 2 * 4;
constexpr int SM_H    = SM_OB + 2 * 16 * 4;
constexpr int SM_T0   = SM_H + 2 * 8 * 4;
constexpr int SM_BAR  = SM_T0 + 16;
constexpr int SM_TOTAL = SM_BAR + 2 * NBAR * 8;
static_assert(SM_Q % 16 == 0 && SM_XN % 16 == 0 && SM_X % 16 == 0 && SM_OB % 16 == 0 && SM_P % 16 == 0 && SM_T0 % 16 == 0, "align");
static_assert(S_GU + 13 <= S_V + FFN_ST, "the gate/up strip lands with stage S_GU + 13");
static_assert(2 * NS >= 16, "K stage -> slot mapping");

constexpr int SPIN_LIMIT = 1 << 22;
constexpr float SCALE_LOG2E = 0.0625f * 1.4426950408889634f;

struct __align__(1024) Scratch {
    uint4    part[NCTA * 2 * 8 * 8];
    uint4    outp[NRED * NCTA * 4];
    uint4    q[8 * 2 * 128];
    unsigned gu[NCTA * 32];
    uint2    ml[NCTA * 4];
    uint2    prog[4 * 32 * 4];
    unsigned epoch[NCTA * 8];
};
__device__ Scratch g_scratch;

__device__ __forceinline__ void mbar_init(uint32_t bar, uint32_t cnt) {
    asm volatile("mbarrier.init.shared::cta.b64 [%0], %1;" :: "r"(bar), "r"(cnt) : "memory");
}
__device__ __forceinline__ void mbar_arrive(uint32_t bar, uint32_t cnt) {
    asm volatile("mbarrier.arrive.shared::cta.b64 _, [%0], %1;" :: "r"(bar), "r"(cnt) : "memory");
}
__device__ __forceinline__ uint32_t time_ns() { uint32_t t; asm volatile("mov.u32 %0, %globaltimer_lo;" : "=r"(t)); return t; }
__device__ __forceinline__ void wait_until(uint32_t t0, uint32_t dt) { while (time_ns() - t0 < dt) {} }
__device__ __forceinline__ void mbar_wait(uint32_t bar) {
    asm volatile("{\n.reg .pred p;\nWAIT_LOOP:\nmbarrier.try_wait.parity.shared::cta.b64 p, [%0], 0;\n@!p bra WAIT_LOOP;\n}" :: "r"(bar) : "memory");
}
__device__ __forceinline__ void cp_async16_strip(uint32_t dst, const void* src) {
    asm volatile("cp.async.cg.shared.global.L2::128B [%0], [%1], 16;" :: "r"(dst), "l"(src) : "memory");
}
__device__ __forceinline__ void cp_async16_stream(uint32_t dst, const void* src) {
    asm volatile("{\n.reg .b64 pol;\ncreatepolicy.fractional.L2::evict_first.b64 pol, 1.0;\n"
                 "cp.async.cg.shared.global.L2::cache_hint [%0], [%1], 16, pol;\n}" :: "r"(dst), "l"(src) : "memory");
}
__device__ __forceinline__ void cp_async_arrive(uint32_t bar) {
    asm volatile("cp.async.mbarrier.arrive.noinc.shared::cta.b64 [%0];" :: "r"(bar) : "memory");
}
__device__ __forceinline__ void bar_sync(int id, int n)   { asm volatile("bar.sync %0, %1;" :: "r"(id), "r"(n) : "memory"); }
__device__ __forceinline__ void bar_arrive(int id, int n) { asm volatile("bar.arrive %0, %1;" :: "r"(id), "r"(n) : "memory"); }

__device__ __forceinline__ uint32_t ld_poll1(const void* p) {
    uint32_t v;
    asm volatile("ld.relaxed.gpu.global.u32 %0, [%1];" : "=r"(v) : "l"(p) : "memory");
    return v;
}
__device__ __forceinline__ uint2 ld_poll2(const void* p) {
    uint2 v;
    asm volatile("ld.relaxed.gpu.global.v2.u32 {%0,%1}, [%2];" : "=r"(v.x), "=r"(v.y) : "l"(p) : "memory");
    return v;
}
__device__ __forceinline__ uint4 ld_poll4(const void* p) {
    uint4 v;
    asm volatile("ld.relaxed.gpu.global.v4.u32 {%0,%1,%2,%3}, [%4];" : "=r"(v.x), "=r"(v.y), "=r"(v.z), "=r"(v.w) : "l"(p) : "memory");
    return v;
}
__device__ __forceinline__ void st_pub64(void* p, uint32_t a, uint32_t b) {
    asm volatile("{\n.reg .b64 d;\nmov.b64 d, {%1,%2};\nst.relaxed.gpu.global.b64 [%0], d;\n}" :: "l"(p), "r"(a), "r"(b) : "memory");
}
__device__ __forceinline__ void st_pub2x64(void* p, uint32_t a, uint32_t b, uint32_t c, uint32_t d) {
    asm volatile("{\n.reg .b64 d, e;\nmov.b64 d, {%1,%2};\nmov.b64 e, {%3,%4};\nst.relaxed.gpu.global.v2.b64 [%0], {d,e};\n}"
                 :: "l"(p), "r"(a), "r"(b), "r"(c), "r"(d) : "memory");
}
__device__ __forceinline__ void st_pub2(void* p, uint32_t a, uint32_t b) {
    asm volatile("st.relaxed.gpu.global.v2.u32 [%0], {%1,%2};" :: "l"(p), "r"(a), "r"(b) : "memory");
}
__device__ __forceinline__ void st_pub1(void* p, uint32_t a) {
    asm volatile("st.relaxed.gpu.global.u32 [%0], %1;" :: "l"(p), "r"(a) : "memory");
}
__device__ __forceinline__ uint32_t tagf(float v, uint32_t tag) {
    uint32_t r;
    asm("lop3.b32 %0, %1, 0xfffffffe, %2, 0xEA;" : "=r"(r) : "r"(__float_as_uint(v)), "r"(tag));
    return r;
}
__device__ __forceinline__ uint32_t pin(uint32_t v) {
    uint32_t r;
    asm volatile("shfl.sync.bfly.b32 %0, %1, 0, 0x1f, 0xffffffff;" : "=r"(r) : "r"(v));
    return r;
}
template <class T>
__device__ __forceinline__ T* pin(T* p) {
    const uint64_t u = reinterpret_cast<uint64_t>(p);
    return reinterpret_cast<T*>(((uint64_t)pin((uint32_t)(u >> 32)) << 32) | pin((uint32_t)u));
}
__device__ __forceinline__ void sts32(uint32_t addr, uint32_t v) { asm volatile("st.shared.u32 [%0], %1;" :: "r"(addr), "r"(v) : "memory"); }
__device__ __forceinline__ float lds32(uint32_t addr) { float v; asm volatile("ld.shared.f32 %0, [%1];" : "=f"(v) : "r"(addr) : "memory"); return v; }
__device__ __forceinline__ uint4 lds128(uint32_t addr) {
    uint4 v;
    asm volatile("ld.shared.v4.u32 {%0,%1,%2,%3}, [%4];" : "=r"(v.x), "=r"(v.y), "=r"(v.z), "=r"(v.w) : "r"(addr) : "memory");
    return v;
}
__device__ __forceinline__ uint32_t bad2(uint32_t a, uint32_t b, uint32_t tag) {
    uint32_t r;
    asm("lop3.b32 %0, %1, %2, %3, 0x7E;" : "=r"(r) : "r"(a), "r"(b), "r"(tag));
    return r;
}
__device__ __forceinline__ uint32_t bad4(const uint4& v, uint32_t tag) { return bad2(v.x, v.y, tag) | bad2(v.z, v.w, tag); }
__device__ __forceinline__ bool warp_bad(uint32_t bad) { return __any_sync(0xffffffffu, bad & 1u); }

#define POLL_HEAD(P, T, N)                                                                                        \
    ".reg .pred p0, p1, p2, p3, q;\n"                                                                             \
    ".reg .b32 a, m, it, y<16>;\n"                                                                                \
    ".reg .b64 d<8>;\n"                                                                                           \
    "setp.eq.u32 p0, 0, 0;\nsetp.eq.u32 p1, 0, 0;\nsetp.eq.u32 p2, 0, 0;\nsetp.eq.u32 p3, 0, 0;\n"                \
    "mov.u32 it, " N ";\n"                                                                                        \
    "POLL_LOOP:\n"                                                                                                \
    "@p0 ld.relaxed.gpu.global.v2.b64 {d0,d1}, [" P "];\n"                                                        \
    "@p1 ld.relaxed.gpu.global.v2.b64 {d2,d3}, [" P "+512];\n"                                                    \
    "@p2 ld.relaxed.gpu.global.v2.b64 {d4,d5}, [" P "+1024];\n"                                                   \
    "@p3 ld.relaxed.gpu.global.v2.b64 {d6,d7}, [" P "+1536];\n"                                                   \
    "sub.u32 it, it, 1;\n"                                                                                        \
    "min.u32 m, it, 1;\n"                                                        \
    "mov.b64 {y0,y1}, d0;\nmov.b64 {y2,y3}, d1;\nmov.b64 {y4,y5}, d2;\nmov.b64 {y6,y7}, d3;\n"                    \
    "mov.b64 {y8,y9}, d4;\nmov.b64 {y10,y11}, d5;\nmov.b64 {y12,y13}, d6;\nmov.b64 {y14,y15}, d7;\n"              \
    "xor.b32 y0, y0, " T ";\nxor.b32 y2, y2, " T ";\nlop3.b32 a, y0, y2, m, 0xA8;\nsetp.ne.u32 p0, a, 0;\n"       \
    "xor.b32 y4, y4, " T ";\nxor.b32 y6, y6, " T ";\nlop3.b32 a, y4, y6, m, 0xA8;\nsetp.ne.u32 p1, a, 0;\n"       \
    "xor.b32 y8, y8, " T ";\nxor.b32 y10, y10, " T ";\nlop3.b32 a, y8, y10, m, 0xA8;\nsetp.ne.u32 p2, a, 0;\n"    \
    "xor.b32 y12, y12, " T ";\nxor.b32 y14, y14, " T ";\nlop3.b32 a, y12, y14, m, 0xA8;\nsetp.ne.u32 p3, a, 0;\n" \
    "or.pred q, p0, p1;\nor.pred q, q, p2;\nor.pred q, q, p3;\nvote.sync.any.pred q, q, 0xffffffff;\n"
#define POLL_TAIL "@q bra POLL_LOOP;\n"

__device__ __forceinline__ void poll4(float (&f)[2][4], const uint4* p, uint32_t tag, const float (&w)[4]) {
    asm volatile("{\n" POLL_HEAD("%8", "%9", "%14") POLL_TAIL
                 "mul.f32 %0, y0, %10;\nmul.f32 %1, y1, %10;\nmul.f32 %2, y2, %10;\nmul.f32 %3, y3, %10;\n"
                 "mul.f32 %4, y8, %12;\nmul.f32 %5, y9, %12;\nmul.f32 %6, y10, %12;\nmul.f32 %7, y11, %12;\n"
                 "fma.rn.f32 %0, y4, %11, %0;\nfma.rn.f32 %1, y5, %11, %1;\nfma.rn.f32 %2, y6, %11, %2;\nfma.rn.f32 %3, y7, %11, %3;\n"
                 "fma.rn.f32 %4, y12, %13, %4;\nfma.rn.f32 %5, y13, %13, %5;\nfma.rn.f32 %6, y14, %13, %6;\nfma.rn.f32 %7, y15, %13, %7;\n"
                 "}"
                 : "=&f"(f[0][0]), "=&f"(f[0][1]), "=&f"(f[0][2]), "=&f"(f[0][3]), "=&f"(f[1][0]), "=&f"(f[1][1]), "=&f"(f[1][2]), "=&f"(f[1][3])
                 : "l"(p), "r"(tag), "f"(w[0]), "f"(w[1]), "f"(w[2]), "f"(w[3]), "n"(SPIN_LIMIT) : "memory");
}
__device__ __forceinline__ void poll4_sum(float (&keep)[2], float (&recv)[2], const uint4* p, uint32_t tag, uint32_t hi) {
    asm volatile("{\n.reg .pred h;\n.reg .f32 s<8>;\nsetp.ne.u32 h, %6, 0;\n" POLL_HEAD("%4", "%5", "%7")
                 "add.f32 s0, y0, y4;\nadd.f32 s1, y1, y5;\nadd.f32 s2, y2, y6;\nadd.f32 s3, y3, y7;\n"
                 "add.f32 s4, y8, y12;\nadd.f32 s5, y9, y13;\nadd.f32 s6, y10, y14;\nadd.f32 s7, y11, y15;\n"
                 "add.f32 s0, s0, s4;\nadd.f32 s1, s1, s5;\nadd.f32 s2, s2, s6;\nadd.f32 s3, s3, s7;\n"
                 "selp.f32 s4, s0, s2, h;\nselp.f32 s5, s1, s3, h;\nselp.f32 %0, s2, s0, h;\nselp.f32 %1, s3, s1, h;\n"
                 "shfl.sync.bfly.b32 %2, s4, 16, 0x1f, 0xffffffff;\nshfl.sync.bfly.b32 %3, s5, 16, 0x1f, 0xffffffff;\n"
                 POLL_TAIL "}"
                 : "=&f"(keep[0]), "=&f"(keep[1]), "=&f"(recv[0]), "=&f"(recv[1])
                 : "l"(p), "r"(tag), "r"(hi), "n"(SPIN_LIMIT) : "memory");
}

__device__ __forceinline__ void ldsm4(uint32_t addr, uint32_t (&a)[4]) {
    asm volatile("ldmatrix.sync.aligned.m8n8.x4.shared.b16 {%0,%1,%2,%3}, [%4];" : "=r"(a[0]), "=r"(a[1]), "=r"(a[2]), "=r"(a[3]) : "r"(addr) : "memory");
}
__device__ __forceinline__ void ldsm4t(uint32_t addr, uint32_t (&a)[4]) {
    asm volatile("ldmatrix.sync.aligned.m8n8.x4.trans.shared.b16 {%0,%1,%2,%3}, [%4];" : "=r"(a[0]), "=r"(a[1]), "=r"(a[2]), "=r"(a[3]) : "r"(addr) : "memory");
}
__device__ __forceinline__ void mma16816(float (&c)[4], const uint32_t (&a)[4], uint32_t b0, uint32_t b1) {
    asm volatile("mma.sync.aligned.m16n8k16.row.col.f32.bf16.bf16.f32 {%0,%1,%2,%3}, {%4,%5,%6,%7}, {%8,%9}, {%0,%1,%2,%3};"
                 : "+f"(c[0]), "+f"(c[1]), "+f"(c[2]), "+f"(c[3]) : "r"(a[0]), "r"(a[1]), "r"(a[2]), "r"(a[3]), "r"(b0), "r"(b1));
}
__device__ __forceinline__ float bf_lo(uint32_t u) { return __uint_as_float(u << 16); }
__device__ __forceinline__ float bf_hi(uint32_t u) { return __uint_as_float(u & 0xffff0000u); }
__device__ __forceinline__ float rbf(float v) { return __bfloat162float(__float2bfloat16_rn(v)); }
__device__ __forceinline__ uint32_t pack_bf(float lo, float hi) {
    uint32_t r;
    asm("cvt.rn.bf16x2.f32 %0, %1, %2;" : "=r"(r) : "f"(hi), "f"(lo));
    return r;
}
__device__ __forceinline__ float sel4(const float (&c)[4], int t) {
    float a = (t & 1) ? c[1] : c[0];
    float b = (t & 1) ? c[3] : c[2];
    return (t & 2) ? b : a;
}
__device__ __forceinline__ float ex2(float x) { float y; asm("ex2.approx.ftz.f32 %0, %1;" : "=f"(y) : "f"(x)); return y; }
__device__ __forceinline__ float sqrt_approx(float x) { float y; asm("sqrt.approx.f32 %0, %1;" : "=f"(y) : "f"(x)); return y; }

__host__ __device__ constexpr uint32_t slot_of(int s) { return SM_RING + (s % NS) * SLOT; }

__device__ __forceinline__ void layernorm(unsigned char* smem, int lane) {
    uint32_t xs[2][7];
#pragma unroll
    for (int b = 0; b < 2; b++)
#pragma unroll
        for (int i = 0; i < 7; i++) xs[b][i] = reinterpret_cast<const uint32_t*>(smem + SM_X)[b * (D_MODEL / 2) + i * 32 + lane];
#pragma unroll
    for (int b = 0; b < 2; b++) {
        float sum = 0.f;
#pragma unroll
        for (int i = 0; i < 7; i++) sum += bf_lo(xs[b][i]) + bf_hi(xs[b][i]);
#pragma unroll
        for (int o = 16; o > 0; o >>= 1) sum += __shfl_xor_sync(0xffffffffu, sum, o);
        const float mean = sum * (1.0f / D_MODEL);
        float sq = 0.f;
#pragma unroll
        for (int i = 0; i < 7; i++) {
            const float d0 = bf_lo(xs[b][i]) - mean, d1 = bf_hi(xs[b][i]) - mean;
            sq = fmaf(d0, d0, fmaf(d1, d1, sq));
        }
#pragma unroll
        for (int o = 16; o > 0; o >>= 1) sq += __shfl_xor_sync(0xffffffffu, sq, o);
        const float mb = rbf(mean);
        const float sd = rbf(sqrt_approx(rbf(rbf(sq * (1.0f / D_MODEL)) + 1e-5f)));
#pragma unroll
        for (int i = 0; i < 7; i++)
            reinterpret_cast<uint32_t*>(smem + SM_XN + b * XROW)[i * 32 + lane] =
                pack_bf(__fdividef(rbf(bf_lo(xs[b][i]) - mb), sd), __fdividef(rbf(bf_hi(xs[b][i]) - mb), sd));
    }
}

__device__ __forceinline__ void strip_partial(uint32_t sb, uint32_t strip, unsigned char* smem, int warp, int lane) {
    float c[2][2][4];
#pragma unroll
    for (int n = 0; n < 2; n++)
#pragma unroll
        for (int e = 0; e < 4; e++) c[n][0][e] = c[n][1][e] = 0.f;
    const uint32_t ba = sb + SM_XN + (lane & 1) * XROW + (lane >> 3) * 16 + warp * 128;
    const uint32_t aa = sb + strip + (warp * 64 + (lane & 7) + (lane >> 4) * 8) * 64 + (((lane >> 3) & 1) ^ ((lane & 7) >> 1)) * 16;
#pragma unroll
    for (int k2 = 0; k2 < 2; k2++) {
        uint32_t b[4];
        ldsm4(ba + k2 * 64, b);
#pragma unroll
        for (int n = 0; n < 2; n++) {
            uint32_t a0[4], a1[4];
            ldsm4t((aa ^ (n * 32)) + k2 * 2048, a0);
            ldsm4t((aa ^ (n * 32)) + k2 * 2048 + 1024, a1);
            mma16816(c[n][0], a0, b[0], b[1]);
            mma16816(c[n][1], a1, b[2], b[3]);
        }
    }
    float* red = reinterpret_cast<float*>(smem + SM_RED) + warp * 64 + lane;
#pragma unroll
    for (int n = 0; n < 2; n++) red[n * 32] = sel4(c[n][0], lane & 3) + sel4(c[n][1], lane & 3);
}
__device__ __forceinline__ float strip_sum(const unsigned char* smem, int idx) {
    const float* red = reinterpret_cast<const float*>(smem + SM_RED) + idx;
    return ((red[0] + red[64]) + (red[128] + red[192])) + ((red[256] + red[320]) + red[384]);
}

__device__ __forceinline__ uint32_t time_base(uint32_t sb, int i) {
    uint32_t t;
    asm volatile("ld.volatile.shared.u32 %0, [%1];" : "=r"(t) : "r"(sb + SM_T0 + 4 * i) : "memory");
    return t;
}
__device__ __forceinline__ void wait_clock(uint32_t sb, int i, uint32_t dt) { while (time_ns() - time_base(sb, i) < dt) {} }

struct Prod {
    uint32_t sb, kvdst, sdst;
    const char *k, *v;
    const __nv_bfloat16* gu;
    bool ffn;
};
__host__ __device__ constexpr int bytes_before(int s) { return 28672 + s * 16384 + (s <= S_GU ? 0 : s < S_GU + 14 ? s - S_GU : 14) * 1792; }
__host__ __device__ constexpr int issue_time(int s) {
    return (int)((long long)bytes_before(s) * PACE_DT / 16384) - PACE_LEAD;
}

template <int S>
__device__ __forceinline__ void produce(Prod& p) {
    if constexpr (S < NSTAGE) {
        if constexpr (S >= NS) mbar_wait(p.sb + SM_BAR + (NBAR + S - NS) * 8);
        wait_clock(p.sb, 0, issue_time(S));
        const char* src = (S < S_V ? p.k : p.v) + (S & 15) * (8 * SLOT);
#pragma unroll
        for (int i = 0; i < 8; i++) cp_async16_stream((p.kvdst ^ ((i & 1) * 64)) + slot_of(S) + i * 2048, src + i * 2048);
        if constexpr (S >= S_GU && S < S_GU + 14) {
            if (p.ffn) cp_async16_strip(p.sdst + (S - S_GU) * 2048, p.gu + (size_t)(S - S_GU) * 32 * FF);
        }
        cp_async_arrive(p.sb + SM_BAR + S * 8);
        produce<S + 1>(p);
    }
}

__device__ __forceinline__ void fetch16(uint32_t dst, const char* src) {
#pragma unroll
    for (int i = 0; i < 4; i++)
        asm volatile("cp.async.cg.shared.global [%0], [%1], 16;" :: "r"((dst ^ (((i & 1) ^ (i >> 1)) * 64)) + i * 512), "l"(src + i * (4 * 896)) : "memory");
}
template <int PENDING, int OFF>
__device__ __forceinline__ void frag16(uint32_t (&a)[4][4], uint32_t addr) {
    asm volatile("cp.async.wait_group %0;" :: "n"(PENDING) : "memory");
    __syncwarp();
#pragma unroll
    for (int m = 0; m < 4; m++) ldsm4t((addr ^ (m * 32)) + OFF, a[m]);
}

__device__ __forceinline__ void load_x(uint32_t sb, const void* x, const void* epoch) {
    const uint32_t full0 = sb + SM_BAR;
    mbar_init(full0 + B_X * 8, 1);
    asm volatile("fence.mbarrier_init.release.cluster;" ::: "memory");
    asm volatile("mbarrier.arrive.expect_tx.shared::cta.b64 _, [%0], %1;" :: "r"(full0 + B_X * 8), "r"(1792 + 16) : "memory");
    asm volatile("cp.async.bulk.shared::cluster.global.mbarrier::complete_tx::bytes [%0], [%1], %2, [%3];"
                 :: "r"(sb + SM_X), "l"(x), "r"(1792), "r"(full0 + B_X * 8) : "memory");
    asm volatile("cp.async.bulk.shared::cluster.global.mbarrier::complete_tx::bytes [%0], [%1], %2, [%3];"
                 :: "r"(sb + SM_X + 1792), "l"(epoch), "r"(16), "r"(full0 + B_X * 8) : "memory");
}

enum { BAR_OB = 1, BAR_CONS = 2, BAR_LN = 3, BAR_FF = 4, BAR_FIN = 5, BAR_H = 6 };

__global__ void __launch_bounds__(NTHREADS, 1)
fused_decode_kernel(const __nv_bfloat16* __restrict__ wq, const __nv_bfloat16* __restrict__ kc, const __nv_bfloat16* __restrict__ x,
                    Scratch* __restrict__ scr, const __nv_bfloat16* __restrict__ vc, const __nv_bfloat16* __restrict__ wo,
                    const __nv_bfloat16* __restrict__ wg, const __nv_bfloat16* __restrict__ wu, const __nv_bfloat16* __restrict__ wd,
                    __nv_bfloat16* __restrict__ out) {
    extern __shared__ __align__(128) unsigned char smem[];
    const uint32_t sb = (uint32_t)__cvta_generic_to_shared(smem);
    const int tid = threadIdx.x, lane = tid & 31;
    const int cta = blockIdx.x;
    const uint32_t full0 = sb + SM_BAR, done0 = full0 + NBAR * 8;
    const uint32_t t0 = time_ns();
    if (tid < 224) {
        const int row = (tid >> 5) * 64 + (lane >> 2);
        const char* src = reinterpret_cast<const char*>(wq) + (uint32_t)(row * (QCOLS * 2) + cta * 64 + (lane & 3) * 16);
        const uint32_t dst = sb + SM_STRIP + row * 64 + ((lane & 3) ^ (lane >> 3)) * 16;
#pragma unroll
        for (int i = 0; i < 8; i++) cp_async16_strip(dst + i * 512, src + i * (8 * QCOLS * 2));
    }
    const int warp = __shfl_sync(0xffffffffu, tid >> 5, 0);
    const int hkv = cta >> 4, j = cta & 15, bat = j >> 3, sp = j & 7;
    const int g = lane >> 2, t = lane & 3;

    if (warp < 8) {
        if (tid == 224) load_x(sb, x, &scr->epoch[cta * 8]);
        __syncthreads();
        mbar_wait(full0 + B_X * 8);
        const uint32_t epoch = *reinterpret_cast<const uint32_t*>(smem + SM_X + 1792);
        const uint32_t tag = pin((epoch + 1) & 1);
        uint32_t* qdst = reinterpret_cast<uint32_t*>(scr->q) + (hkv * 2 + (t & 1)) * 512 + j * 32 + warp * 16 + g + 8 * (t >> 1);
        if (warp == 7) {
            layernorm(smem, lane);
            bar_arrive(BAR_LN, 256);
        } else {
            asm volatile("cp.async.wait_all;" ::: "memory");
            bar_sync(BAR_LN, 256);
            strip_partial(sb, SM_STRIP, smem, warp, lane);
        }
        bar_sync(BAR_CONS, 256);
        if (warp < 2) {
            st_pub1(qdst, (pack_bf(0.f, strip_sum(smem, tid)) & 0xffff0000u) | tag);
        } else if (warp >= 4) {
            const int i = tid - 128;
            const uint4* qp = scr->q + (hkv * 2 + bat) * 128 + i;
            wait_until(t0, Q_T);
            uint4 v;
            int it = 0;
            do {
                v = ld_poll4(qp);
                if (++it > SPIN_LIMIT) __trap();
            } while (warp_bad(bad4(v, tag)));
            *reinterpret_cast<uint2*>(smem + SM_Q + (i >> 6) * 528 + (i & 63) * 8) =
                make_uint2(__byte_perm(v.x, v.y, 0x7632), __byte_perm(v.z, v.w, 0x7632));
        }
        bar_sync(BAR_CONS, 256);
        if (tid == 96) scr->epoch[cta * 8] = epoch + 1;
        {
            uint32_t qf[8][4];
#pragma unroll
            for (int k2 = 0; k2 < 8; k2++) ldsm4(sb + SM_Q + (lane & 1) * 528 + k2 * 64 + (lane >> 3) * 16, qf[k2]);
            const int mt = warp & 1;
            const uint32_t aoff = (16 * mt + (lane & 15)) * 512 + ((lane >> 4) ^ (lane & 7)) * 16;
            float* sc = reinterpret_cast<float*>(smem + SM_S) + (t & 1) * 520 + (g >> 1) * 8 + (2 * mt + (t >> 1)) * 2 + (g & 1);
#pragma unroll 1
            for (int k = warp >> 1; k < 16; k += 4) {
                const int s = S_K + k;
                mbar_wait(full0 + s * 8);
                const uint32_t base = sb + SM_RING + (s >= NS ? s - NS : s) * SLOT + aoff;
                float c0[4] = {0.f, 0.f, 0.f, 0.f}, c1[4] = {0.f, 0.f, 0.f, 0.f};
#pragma unroll
                for (int k2 = 0; k2 < 8; k2++) {
                    uint32_t a0[4], a1[4];
                    ldsm4((base ^ ((k2 & 1) * 64)) + (k2 >> 1) * 128, a0);
                    ldsm4((base ^ ((k2 & 1) * 64 + 32)) + (k2 >> 1) * 128, a1);
                    mma16816(c0, a0, qf[k2][0], qf[k2][1]);
                    mma16816(c1, a1, qf[k2][2], qf[k2][3]);
                }
                __syncwarp();
                if (lane == 0) mbar_arrive(done0 + s * 8, 4);
                sc[k * 32] = rbf(sel4(c0, t) + sel4(c1, t));
            }
        }
        bar_sync(BAR_CONS, 256);
        {
            constexpr float C = SCALE_LOG2E;
            const float* sc = reinterpret_cast<const float*>(smem + SM_S);
            float* stat = reinterpret_cast<float*>(smem + SM_STAT);
            const float2 s0 = *reinterpret_cast<const float2*>(sc + 2 * tid);
            const float2 s1 = *reinterpret_cast<const float2*>(sc + 520 + 2 * tid);
            float m0 = fmaxf(s0.x, s0.y), m1 = fmaxf(s1.x, s1.y);
#pragma unroll
            for (int o = 16; o > 0; o >>= 1) {
                m0 = fmaxf(m0, __shfl_xor_sync(0xffffffffu, m0, o));
                m1 = fmaxf(m1, __shfl_xor_sync(0xffffffffu, m1, o));
            }
            if (lane == 0) *reinterpret_cast<float2*>(stat + warp * 2) = make_float2(m0, m1);
            bar_sync(BAR_CONS, 256);
#pragma unroll
            for (int w = 0; w < 8; w++) {
                const float2 mm = *reinterpret_cast<const float2*>(stat + w * 2);
                m0 = fmaxf(m0, mm.x); m1 = fmaxf(m1, mm.y);
            }
            const float p00 = ex2((s0.x - m0) * C), p01 = ex2((s0.y - m0) * C);
            const float p10 = ex2((s1.x - m1) * C), p11 = ex2((s1.y - m1) * C);
            uint32_t* ps = reinterpret_cast<uint32_t*>(smem + SM_P);
            ps[tid] = pack_bf(p00, p01);
            ps[272 + tid] = pack_bf(p10, p11);
            float l0 = p00 + p01, l1 = p10 + p11;
#pragma unroll
            for (int o = 16; o > 0; o >>= 1) {
                l0 += __shfl_xor_sync(0xffffffffu, l0, o);
                l1 += __shfl_xor_sync(0xffffffffu, l1, o);
            }
            if (lane == 0) *reinterpret_cast<float2*>(stat + 16 + warp * 2) = make_float2(l0, l1);
            bar_sync(BAR_CONS, 256);
            if (tid < 4) {
                float l = 0.f;
#pragma unroll
                for (int w = 0; w < 8; w++) l += stat[16 + w * 2 + (tid & 1)];
                st_pub2(scr->ml + cta * 4 + tid, tagf((tid & 1) ? m1 : m0, tag), tagf(l, tag));
            }
        }
        float wgt[2] = {0.f, 0.f}, own = 0.f;
        {
            float o0[4] = {0.f, 0.f, 0.f, 0.f}, o1[4] = {0.f, 0.f, 0.f, 0.f};
            float o2[4] = {0.f, 0.f, 0.f, 0.f}, o3[4] = {0.f, 0.f, 0.f, 0.f};
            const uint32_t aoff = ((lane & 7) + (lane >> 4) * 8) * 512 + ((warp * 4 + ((lane >> 3) & 1) * 2) ^ (lane & 7)) * 16;
            const uint4* ps = reinterpret_cast<const uint4*>(smem + SM_P + (g & 1) * 272 * 4) + t;
            uint32_t* dst = reinterpret_cast<uint32_t*>(scr->part) + ((size_t)(hkv * 16 + (t & 1) * 8 + warp) * 16 + j) * 32 +
                            (4 * (g & 3) + (t & 2) + (g >> 2)) * 2;
#pragma unroll
            for (int k = 0; k < 16; k++) {
                const uint4 pa = ps[k * 4];
                mbar_wait(full0 + (S_V + k) * 8);
                uint32_t a[4][4];
#pragma unroll
                for (int i = 0; i < 4; i++) ldsm4t(sb + (aoff ^ ((i & 1) * 16)) + slot_of(S_V + k) + (i >> 1) * 8192, a[i]);
                mma16816(o0, a[0], pa.x, pa.y);
                mma16816(o1, a[1], pa.x, pa.y);
                mma16816(o2, a[2], pa.z, pa.w);
                mma16816(o3, a[3], pa.z, pa.w);
                if (S_V + k + NS < NSTAGE + 3) {
                    __syncwarp();
                    if (lane == 0) mbar_arrive(done0 + (S_V + k) * 8, 1);
                }
                if (k == FFN_ST && warp < 7) {
                    strip_partial(sb, SM_STRIP, smem, warp, lane);
                    bar_arrive(BAR_FF, 256);
                }
                if (k == FFN_ST && warp == 7) {
                    bar_sync(BAR_FF, 256);
                    own = rbf(strip_sum(smem, (cta & 1) * 32 + lane));
                    st_pub1(scr->gu + (cta ^ 1) * 32 + lane, (pack_bf(0.f, strip_sum(smem, (~cta & 1) * 32 + lane)) & 0xffff0000u) | tag);
                }
                if (k == HID_ST && warp == 7) {
                    const uint2* mlp = scr->ml + (hkv * 16 + g) * 4 + (j >> 3);
                    uint2 a, b;
                    uint32_t other;
                    int it = 0;
                    do {
                        a = ld_poll2(mlp); b = ld_poll2(mlp + 32); other = ld_poll1(scr->gu + cta * 32 + lane);
                        if (++it > SPIN_LIMIT) __trap();
                    } while (warp_bad(bad2(a.x, a.y, tag) | bad2(b.x, b.y, tag) | (other ^ tag)));
                    float m[2] = {bf_hi(a.x), bf_hi(b.x)};
                    float l[2] = {__uint_as_float(a.y ^ tag), __uint_as_float(b.y ^ tag)};
#pragma unroll
                    for (int bb = 0; bb < 2; bb++) {
                        float M = m[bb];
                        M = fmaxf(M, __shfl_xor_sync(0xffffffffu, M, 4));
                        M = fmaxf(M, __shfl_xor_sync(0xffffffffu, M, 8));
                        M = fmaxf(M, __shfl_xor_sync(0xffffffffu, M, 16));
                        const float e = ex2((m[bb] - M) * SCALE_LOG2E);
                        float L = e * l[bb];
                        L += __shfl_xor_sync(0xffffffffu, L, 4);
                        L += __shfl_xor_sync(0xffffffffu, L, 8);
                        L += __shfl_xor_sync(0xffffffffu, L, 16);
                        wgt[bb] = __fdividef(e, L);
                    }
                    float ga = (cta & 1) ? bf_hi(other) : own;
                    ga *= (ga > 0.f ? 1.f : 0.f);
                    const float hv = ga * ((cta & 1) ? own : bf_hi(other));
                    const uint32_t w = pack_bf(hv, __shfl_xor_sync(0xffffffffu, hv, 2));
                    if (!(t & 2)) reinterpret_cast<uint32_t*>(smem + SM_H)[(t & 1) * 8 + (g & 3) * 2 + (g >> 2)] = w;
                    bar_arrive(BAR_H, 256);
                }
                if (k == PRE_ST) st_pub64(dst, tag ^ 1, 0);
            }
            const float v0 = sel4(o0, t) + sel4(o2, t), v1 = sel4(o1, t) + sel4(o3, t);
            st_pub64(dst, tagf(v0, tag), __float_as_uint(v1));
        }
        if (warp == 7) {
            const uint4* pp = pin(scr->part + (size_t)cta * 128 + lane);
            const uint32_t obaddr = pin(sb + SM_OB + (lane >> 4) * 64 + (lane & 7) * 8 + ((lane >> 3) & 1) * 4), ll = pin(lane);
            float w[4];
#pragma unroll
            for (int i = 0; i < 4; i++) w[i] = __shfl_sync(0xffffffffu, wgt[i >> 1], ((i & 1) * 4 + (lane >> 3)) * 4);
            wait_until(time_base(sb, 2), E2_T);
            float f[2][4];
            poll4(f, pp, tag, w);
            const bool h16 = ll & 16, h8 = ll & 8;
            float r4[4], r2[2];
#pragma unroll
            for (int e = 0; e < 4; e++) r4[e] = (h16 ? f[1][e] : f[0][e]) + __shfl_xor_sync(0xffffffffu, h16 ? f[0][e] : f[1][e], 16);
#pragma unroll
            for (int e = 0; e < 2; e++) r2[e] = (h8 ? r4[2 + e] : r4[e]) + __shfl_xor_sync(0xffffffffu, h8 ? r4[e] : r4[2 + e], 8);
            sts32(obaddr, pack_bf(r2[0], r2[1]));
            bar_arrive(BAR_OB, 256);
        } else if (warp < 4 && (cta & 1) == 0 && cta < 2 * NRED) {
            const uint4* op = pin(scr->outp + (size_t)(cta >> 1) * (NCTA * 4) + warp * 128 + lane);
            const int oidx = (t & 1) * D_MODEL + hkv * 64 + (lane >> 3) * 16 + (j >> 1) + (t >> 1) * 8;
            const float xv = __bfloat162float(reinterpret_cast<const __nv_bfloat16*>(smem + SM_X)[oidx]);
            __nv_bfloat16* optr = pin(out + oidx);
            const uint32_t red = pin(sb + SM_S + tid * 4), ll = pin(lane);
            float r2[2], rcv[2];
            const bool h8 = ll & 8;
            wait_until(time_base(sb, 3), E3_T);
            poll4_sum(r2, rcv, op, tag, ll & 16);
            r2[0] += rcv[0]; r2[1] += rcv[1];
            float r = (h8 ? r2[1] : r2[0]) + __shfl_xor_sync(0xffffffffu, h8 ? r2[0] : r2[1], 8);
            r += __shfl_xor_sync(0xffffffffu, r, 4);
            if (warp != 0) {
                sts32(red, __float_as_uint(r));
                bar_arrive(BAR_FIN, 128);
            } else {
                bar_sync(BAR_FIN, 128);
                r = ((xv + r) + lds32(red + 128)) + (lds32(red + 256) + lds32(red + 384));
                asm volatile("st.global.u16 [%0], %1;" :: "l"(optr), "h"(__bfloat16_as_ushort(__float2bfloat16_rn(r))) : "memory");
            }
        }
    } else if (warp < 15) {
        const int pt = tid - 256, pw = warp - 8;
        const char* pdn = reinterpret_cast<const char*>(wd) + (size_t)cta * 14336 + (lane >> 3) * 896 + pw * 128 + (lane & 7) * 16;
        const char* pwo = reinterpret_cast<const char*>(wo) + (size_t)cta * 28672 + (lane >> 3) * 896 + pw * 128 + (lane & 7) * 16;
        if (pw < 4) {
            if (lane == 0) {
#pragma unroll
                for (int i = 0; i < 9; i++) {
                    if (pw * 9 + i != B_X) mbar_init(full0 + (pw * 9 + i) * 8, NPT);
                    mbar_init(done0 + (pw * 9 + i) * 8, 8);
                }
            }
            Prod p;
            const size_t kvoff = ((size_t)(bat * 8 + hkv) * SK + (SK - WIN)) * DH * 2 + sp * SLOT + pt * 16;
            p.sb = sb;
            p.kvdst = (sb + pt * 16) ^ (pw * 16);
            p.sdst = sb + SM_STRIP + (pt >> 2) * 64 + ((pt & 3) ^ ((pt >> 3) & 3)) * 16;
            p.k = reinterpret_cast<const char*>(kc) + kvoff;
            p.v = reinterpret_cast<const char*>(vc) + kvoff;
            p.gu = ((cta & 1) ? wu : wg) + (cta >> 1) * 32 + (pt & 3) * 8 + (size_t)(pt >> 2) * FF;
            p.ffn = cta < NFFN;
            __syncthreads();
            produce<0>(p);
        } else {
            __syncthreads();
        }
        mbar_wait(full0 + B_X * 8);
        const uint32_t tag = pin((*reinterpret_cast<const uint32_t*>(smem + SM_X + 1792) + 1) & 1);
        if (pw == 4 && (cta & 3) == 0) {
#pragma unroll 1
            for (int i = 0; i < 4; i++) {
                uint32_t sum = 0;
#pragma unroll
                for (int k = 0; k < NM; k++) {
                    mbar_wait(full0 + (MEND - NM + 1 + k + 6 * i) * 8);
                    sum += time_ns() - t0;
                }
                if (lane < 4) st_pub2(&scr->prog[i * 128 + cta + lane], ((t0 + sum / NM) & ~1u) | tag, (t0 & ~1u) | tag);
            }
        }
        mbar_wait(done0 + (NSTAGE + 2 - NS) * 8);
        const uint32_t ta = LATE_T, td = LATE_DT;
        uint4* odst = scr->outp + ((size_t)(pt >> 2) * NCTA + cta) * 4 + t;
        st_pub2x64(odst, tag ^ 1, 0, tag ^ 1, 0);
        const uint32_t fdst = (sb + pw * 2048 + lane * 16) ^ ((lane >> 3) * 16);
        wait_clock(sb, 1, ta);
        if (cta < NFFN) fetch16(fdst + slot_of(NSTAGE), pdn);
        asm volatile("cp.async.commit_group;" ::: "memory");
        wait_clock(sb, 1, ta + td);
        fetch16(fdst + slot_of(NSTAGE + 1), pwo);
        asm volatile("cp.async.commit_group;" ::: "memory");
        wait_clock(sb, 1, ta + 2 * td);
        fetch16(fdst + slot_of(NSTAGE + 2), pwo + 14336);
        asm volatile("cp.async.commit_group;" ::: "memory");
        bar_sync(BAR_H, 256);
        const uint2 h = *reinterpret_cast<const uint2*>(smem + SM_H + (g & 1) * 32 + t * 8);
        float c[4][4];
#pragma unroll
        for (int m = 0; m < 4; m++)
#pragma unroll
            for (int e = 0; e < 4; e++) c[m][e] = 0.f;
        const int r7 = ((lane & 7) >> 1) + 4 * (lane >> 4);
        const uint32_t aoff = sb + pw * 2048 + (r7 + 8 * (lane & 1)) * 128 + (((lane >> 3) & 1) ^ r7 ^ ((lane & 1) << 2)) * 16;
        const uint32_t obaddr = pin(sb + SM_OB + (g & 1) * 64 + t * 16), tt = pin(t);
        uint32_t a0[4][4], a1[4][4];
        frag16<2, slot_of(NSTAGE)>(a0, aoff);
        if (cta < NFFN) {
#pragma unroll
            for (int m = 0; m < 4; m++) mma16816(c[m], a0[m], h.x, h.y);
        }
        frag16<1, slot_of(NSTAGE + 1)>(a1, aoff);
        bar_sync(BAR_OB, 256);
        const uint4 ob = lds128(obaddr);
#pragma unroll
        for (int m = 0; m < 4; m++) mma16816(c[m], a1[m], ob.x, ob.y);
        frag16<0, slot_of(NSTAGE + 2)>(a0, aoff);
#pragma unroll
        for (int m = 0; m < 4; m++) mma16816(c[m], a0[m], ob.z, ob.w);
        st_pub2x64(odst, tagf(sel4(c[0], tt), tag), __float_as_uint(sel4(c[1], tt)), tagf(sel4(c[2], tt), tag), __float_as_uint(sel4(c[3], tt)));
    } else if (warp == 15) {
        if (lane < 4) reinterpret_cast<uint32_t*>(smem + SM_T0)[lane] = t0;
        __syncthreads();
        mbar_wait(full0 + B_X * 8);
        const uint32_t tag = (*reinterpret_cast<const uint32_t*>(smem + SM_X + 1792) + 1) & 1;
#pragma unroll 1
        for (int i = 0; i < 4; i++) {
            mbar_wait(full0 + (MEND + MGAP + 6 * i) * 8);
            uint2 v;
            int it = 0;
            do {
                v = ld_poll2(&scr->prog[i * 128 + lane * 4]);
                if (++it > SPIN_LIMIT) __trap();
            } while (warp_bad(bad2(v.x, v.y, tag)));
            const int nom = i == 0 ? M_NOM0 : i == 1 ? M_NOM1 : i == 2 ? M_NOM2 : M_NOM3;
            int base = (__reduce_add_sync(0xffffffffu, min(max((int)(v.x - t0), 0), 1 << 20)) >> 5) - nom;
            const int start = __reduce_add_sync(0xffffffffu, min(max((int)(v.y - t0), -(1 << 20)), 1 << 20)) >> 5;
            base = start + max(min(base - start, 2 * (base - start - DEAD)), 0);
            const int ahead = (lane == 0 ? nom : lane == 1 ? LATE_T : lane == 2 ? E2_T : E3_T - 150) - nom;
            const float rate = fminf(fmaxf(__fdividef((float)(base - start), (float)(nom - 500)), -0.01f), 0.045f);
            if (lane < 4) sts32(sb + SM_T0 + 4 * lane, t0 + base + (int)(rate * (float)ahead));
        }
    }
}

}

extern "C" void kernel_launch(void* const* d_in, const int* in_sizes, int n_in, void* d_out, int out_size) {
    (void)in_sizes; (void)n_in; (void)out_size;
    static Scratch* scr = nullptr;
    if (!scr) {
        cudaFuncSetAttribute(fused_decode_kernel, cudaFuncAttributeMaxDynamicSharedMemorySize, SM_TOTAL);
        cudaGetSymbolAddress(reinterpret_cast<void**>(&scr), g_scratch);
    }
    typedef const __nv_bfloat16* P;
    fused_decode_kernel<<<NCTA, NTHREADS, SM_TOTAL>>>((P)d_in[3], (P)d_in[1], (P)d_in[0], scr, (P)d_in[2], (P)d_in[4],
                                                      (P)d_in[6], (P)d_in[7], (P)d_in[8], (__nv_bfloat16*)d_out);
}
```

```cpp
#include <cuda_runtime.h>
#include <cuda_bf16.h>
#include <stdint.h>

namespace {

constexpr int PACE_DT = 640;
constexpr int PACE_LEAD = 350;
constexpr int LATE_T = 22370;
constexpr int LATE_DT = 400;
constexpr int Q_T = 4000;
constexpr int E2_T = 24090;
constexpr int E3_T = 24830;
constexpr int M_NOM0 = 4595;
constexpr int M_NOM1 = 8450;
constexpr int M_NOM2 = 12800;
constexpr int M_NOM3 = 17010;
constexpr int DEAD = 100;
constexpr int NM = 4;
constexpr int MEND = 5;
constexpr int MGAP = 3;
constexpr int NSLOT = 11;

constexpr int D_MODEL = 448;
constexpr int SK      = 32768;
constexpr int WIN     = 4096;
constexpr int DH      = 256;
constexpr int QCOLS   = 4096;
constexpr int FF      = 1792;
constexpr int NCTA    = 128;
constexpr int NFFN    = 112;
constexpr int NRED    = 56;
constexpr int NPT     = 128;
constexpr int NTHREADS = 512;

constexpr int NS     = NSLOT;
constexpr int SLOT   = 16384;
constexpr int XROW   = 912;
constexpr int S_K = 0, S_V = 16, NSTAGE = 32;
constexpr int S_GU   = NS;
constexpr int FFN_ST = 8;
constexpr int HID_ST = 11;
constexpr int PRE_ST = 12;
constexpr int NBAR   = 36;
constexpr int B_X = NSTAGE;

constexpr int SM_RING  = 0;
constexpr int SM_STRIP = SM_RING + NS * SLOT;
constexpr int SM_S    = SM_STRIP + 448 * 64;
constexpr int SM_P    = SM_S + 2 * 520 * 4;
constexpr int SM_Q    = SM_P + 2 * 272 * 4;
constexpr int SM_XN   = SM_Q + 2 * 264 * 2;
constexpr int SM_X    = SM_XN + 2 * XROW;
constexpr int SM_RED  = SM_X + 1792 + 32;
constexpr int SM_STAT = SM_RED + 7 * 64 * 4;
constexpr int SM_OB   = SM_STAT + 2 * 8 * 2 * 4;
constexpr int SM_H    = SM_OB + 2 * 16 * 4;
constexpr int SM_T0   = SM_H + 2 * 8 * 4;
constexpr int SM_BAR  = SM_T0 + 16;
constexpr int SM_TOTAL = SM_BAR + 2 * NBAR * 8;
static_assert(SM_Q % 16 == 0 && SM_XN % 16 == 0 && SM_X % 16 == 0 && SM_OB % 16 == 0 && SM_P % 16 == 0 && SM_T0 % 16 == 0, "align");
static_assert(S_GU + 13 <= S_V + FFN_ST, "the gate/up strip lands with stage S_GU + 13");
static_assert(2 * NS >= 16, "K stage -> slot mapping");

constexpr int SPIN_LIMIT = 1 << 22;
constexpr float SCALE_LOG2E = 0.0625f * 1.4426950408889634f;

struct __align__(1024) Scratch {
    uint4    part[NCTA * 2 * 8 * 8];
    uint4    outp[NRED * NCTA * 4];
    uint4    q[8 * 2 * 128];
    unsigned gu[NCTA * 32];
    uint2    ml[NCTA * 4];
    uint2    prog[4 * 32 * 4];
    unsigned epoch[NCTA * 8];
};
__device__ Scratch g_scratch;

__device__ __forceinline__ void mbar_init(uint32_t bar, uint32_t cnt) {
    asm volatile("mbarrier.init.shared::cta.b64 [%0], %1;" :: "r"(bar), "r"(cnt) : "memory");
}
__device__ __forceinline__ void mbar_arrive(uint32_t bar, uint32_t cnt) {
    asm volatile("mbarrier.arrive.shared::cta.b64 _, [%0], %1;" :: "r"(bar), "r"(cnt) : "memory");
}
template <bool SCALED>
struct Clock {
    uint32_t scale;
    __device__ __forceinline__ uint32_t now() const {
        if constexpr (SCALED) {
            uint64_t t;
            asm volatile("mov.u64 %0, %globaltimer;" : "=l"(t));
            return (uint32_t)((t * scale) >> 6);
        } else {
            uint32_t t;
            asm volatile("mov.u32 %0, %globaltimer_lo;" : "=r"(t));
            return t;
        }
    }
    __device__ __forceinline__ static uint32_t base(uint32_t sb, int i) {
        uint32_t t;
        asm volatile("ld.volatile.shared.u32 %0, [%1];" : "=r"(t) : "r"(sb + SM_T0 + 4 * i) : "memory");
        return t;
    }
    __device__ __forceinline__ void wait_until(uint32_t t0, uint32_t dt) const { while (now() - t0 < dt) {} }
    __device__ __forceinline__ void wait_base(uint32_t sb, int i, uint32_t dt) const { while (now() - base(sb, i) < dt) {} }
};
__device__ __forceinline__ void mbar_wait(uint32_t bar) {
    asm volatile("{\n.reg .pred p;\nWAIT_LOOP:\nmbarrier.try_wait.parity.shared::cta.b64 p, [%0], 0;\n@!p bra WAIT_LOOP;\n}" :: "r"(bar) : "memory");
}
__device__ __forceinline__ void cp_async16_strip(uint32_t dst, const void* src) {
    asm volatile("cp.async.cg.shared.global.L2::128B [%0], [%1], 16;" :: "r"(dst), "l"(src) : "memory");
}
__device__ __forceinline__ void cp_async16_stream(uint32_t dst, const void* src) {
    asm volatile("{\n.reg .b64 pol;\ncreatepolicy.fractional.L2::evict_first.b64 pol, 1.0;\n"
                 "cp.async.cg.shared.global.L2::cache_hint [%0], [%1], 16, pol;\n}" :: "r"(dst), "l"(src) : "memory");
}
__device__ __forceinline__ void cp_async_arrive(uint32_t bar) {
    asm volatile("cp.async.mbarrier.arrive.noinc.shared::cta.b64 [%0];" :: "r"(bar) : "memory");
}
__device__ __forceinline__ void bar_sync(int id, int n)   { asm volatile("bar.sync %0, %1;" :: "r"(id), "r"(n) : "memory"); }
__device__ __forceinline__ void bar_arrive(int id, int n) { asm volatile("bar.arrive %0, %1;" :: "r"(id), "r"(n) : "memory"); }

__device__ __forceinline__ uint32_t ld_poll1(const void* p) {
    uint32_t v;
    asm volatile("ld.relaxed.gpu.global.u32 %0, [%1];" : "=r"(v) : "l"(p) : "memory");
    return v;
}
__device__ __forceinline__ uint2 ld_poll2(const void* p) {
    uint2 v;
    asm volatile("ld.relaxed.gpu.global.v2.u32 {%0,%1}, [%2];" : "=r"(v.x), "=r"(v.y) : "l"(p) : "memory");
    return v;
}
__device__ __forceinline__ uint4 ld_poll4(const void* p) {
    uint4 v;
    asm volatile("ld.relaxed.gpu.global.v4.u32 {%0,%1,%2,%3}, [%4];" : "=r"(v.x), "=r"(v.y), "=r"(v.z), "=r"(v.w) : "l"(p) : "memory");
    return v;
}
__device__ __forceinline__ void st_pub64(void* p, uint32_t a, uint32_t b) {
    asm volatile("{\n.reg .b64 d;\nmov.b64 d, {%1,%2};\nst.relaxed.gpu.global.b64 [%0], d;\n}" :: "l"(p), "r"(a), "r"(b) : "memory");
}
__device__ __forceinline__ void st_pub2x64(void* p, uint32_t a, uint32_t b, uint32_t c, uint32_t d) {
    asm volatile("{\n.reg .b64 d, e;\nmov.b64 d, {%1,%2};\nmov.b64 e, {%3,%4};\nst.relaxed.gpu.global.v2.b64 [%0], {d,e};\n}"
                 :: "l"(p), "r"(a), "r"(b), "r"(c), "r"(d) : "memory");
}
__device__ __forceinline__ void st_pub2(void* p, uint32_t a, uint32_t b) {
    asm volatile("st.relaxed.gpu.global.v2.u32 [%0], {%1,%2};" :: "l"(p), "r"(a), "r"(b) : "memory");
}
__device__ __forceinline__ void st_pub1(void* p, uint32_t a) {
    asm volatile("st.relaxed.gpu.global.u32 [%0], %1;" :: "l"(p), "r"(a) : "memory");
}
__device__ __forceinline__ uint32_t tagf(float v, uint32_t tag) {
    uint32_t r;
    asm("lop3.b32 %0, %1, 0xfffffffe, %2, 0xEA;" : "=r"(r) : "r"(__float_as_uint(v)), "r"(tag));
    return r;
}
__device__ __forceinline__ uint32_t pin(uint32_t v) {
    uint32_t r;
    asm volatile("shfl.sync.bfly.b32 %0, %1, 0, 0x1f, 0xffffffff;" : "=r"(r) : "r"(v));
    return r;
}
template <class T>
__device__ __forceinline__ T* pin(T* p) {
    const uint64_t u = reinterpret_cast<uint64_t>(p);
    return reinterpret_cast<T*>(((uint64_t)pin((uint32_t)(u >> 32)) << 32) | pin((uint32_t)u));
}
__device__ __forceinline__ void sts32(uint32_t addr, uint32_t v) { asm volatile("st.shared.u32 [%0], %1;" :: "r"(addr), "r"(v) : "memory"); }
__device__ __forceinline__ float lds32(uint32_t addr) { float v; asm volatile("ld.shared.f32 %0, [%1];" : "=f"(v) : "r"(addr) : "memory"); return v; }
__device__ __forceinline__ uint4 lds128(uint32_t addr) {
    uint4 v;
    asm volatile("ld.shared.v4.u32 {%0,%1,%2,%3}, [%4];" : "=r"(v.x), "=r"(v.y), "=r"(v.z), "=r"(v.w) : "r"(addr) : "memory");
    return v;
}
__device__ __forceinline__ uint32_t bad2(uint32_t a, uint32_t b, uint32_t tag) {
    uint32_t r;
    asm("lop3.b32 %0, %1, %2, %3, 0x7E;" : "=r"(r) : "r"(a), "r"(b), "r"(tag));
    return r;
}
__device__ __forceinline__ uint32_t bad4(const uint4& v, uint32_t tag) { return bad2(v.x, v.y, tag) | bad2(v.z, v.w, tag); }
__device__ __forceinline__ bool warp_bad(uint32_t bad) { return __any_sync(0xffffffffu, bad & 1u); }

#define POLL_HEAD(P, T, N)                                                                                        \
    ".reg .pred p0, p1, p2, p3, q;\n"                                                                             \
    ".reg .b32 a, m, it, y<16>;\n"                                                                                \
    ".reg .b64 d<8>;\n"                                                                                           \
    "setp.eq.u32 p0, 0, 0;\nsetp.eq.u32 p1, 0, 0;\nsetp.eq.u32 p2, 0, 0;\nsetp.eq.u32 p3, 0, 0;\n"                \
    "mov.u32 it, " N ";\n"                                                                                        \
    "POLL_LOOP:\n"                                                                                                \
    "@p0 ld.relaxed.gpu.global.v2.b64 {d0,d1}, [" P "];\n"                                                        \
    "@p1 ld.relaxed.gpu.global.v2.b64 {d2,d3}, [" P "+512];\n"                                                    \
    "@p2 ld.relaxed.gpu.global.v2.b64 {d4,d5}, [" P "+1024];\n"                                                   \
    "@p3 ld.relaxed.gpu.global.v2.b64 {d6,d7}, [" P "+1536];\n"                                                   \
    "sub.u32 it, it, 1;\n"                                                                                        \
    "min.u32 m, it, 1;\n"                                                        \
    "mov.b64 {y0,y1}, d0;\nmov.b64 {y2,y3}, d1;\nmov.b64 {y4,y5}, d2;\nmov.b64 {y6,y7}, d3;\n"                    \
    "mov.b64 {y8,y9}, d4;\nmov.b64 {y10,y11}, d5;\nmov.b64 {y12,y13}, d6;\nmov.b64 {y14,y15}, d7;\n"              \
    "xor.b32 y0, y0, " T ";\nxor.b32 y2, y2, " T ";\nlop3.b32 a, y0, y2, m, 0xA8;\nsetp.ne.u32 p0, a, 0;\n"       \
    "xor.b32 y4, y4, " T ";\nxor.b32 y6, y6, " T ";\nlop3.b32 a, y4, y6, m, 0xA8;\nsetp.ne.u32 p1, a, 0;\n"       \
    "xor.b32 y8, y8, " T ";\nxor.b32 y10, y10, " T ";\nlop3.b32 a, y8, y10, m, 0xA8;\nsetp.ne.u32 p2, a, 0;\n"    \
    "xor.b32 y12, y12, " T ";\nxor.b32 y14, y14, " T ";\nlop3.b32 a, y12, y14, m, 0xA8;\nsetp.ne.u32 p3, a, 0;\n" \
    "or.pred q, p0, p1;\nor.pred q, q, p2;\nor.pred q, q, p3;\nvote.sync.any.pred q, q, 0xffffffff;\n"
#define POLL_TAIL "@q bra POLL_LOOP;\n"

__device__ __forceinline__ void poll4(float (&f)[2][4], const uint4* p, uint32_t tag, const float (&w)[4]) {
    asm volatile("{\n" POLL_HEAD("%8", "%9", "%14") POLL_TAIL
                 "mul.f32 %0, y0, %10;\nmul.f32 %1, y1, %10;\nmul.f32 %2, y2, %10;\nmul.f32 %3, y3, %10;\n"
                 "mul.f32 %4, y8, %12;\nmul.f32 %5, y9, %12;\nmul.f32 %6, y10, %12;\nmul.f32 %7, y11, %12;\n"
                 "fma.rn.f32 %0, y4, %11, %0;\nfma.rn.f32 %1, y5, %11, %1;\nfma.rn.f32 %2, y6, %11, %2;\nfma.rn.f32 %3, y7, %11, %3;\n"
                 "fma.rn.f32 %4, y12, %13, %4;\nfma.rn.f32 %5, y13, %13, %5;\nfma.rn.f32 %6, y14, %13, %6;\nfma.rn.f32 %7, y15, %13, %7;\n"
                 "}"
                 : "=&f"(f[0][0]), "=&f"(f[0][1]), "=&f"(f[0][2]), "=&f"(f[0][3]), "=&f"(f[1][0]), "=&f"(f[1][1]), "=&f"(f[1][2]), "=&f"(f[1][3])
                 : "l"(p), "r"(tag), "f"(w[0]), "f"(w[1]), "f"(w[2]), "f"(w[3]), "n"(SPIN_LIMIT) : "memory");
}
__device__ __forceinline__ void poll4_sum(float (&keep)[2], float (&recv)[2], const uint4* p, uint32_t tag, uint32_t hi) {
    asm volatile("{\n.reg .pred h;\n.reg .f32 s<8>;\nsetp.ne.u32 h, %6, 0;\n" POLL_HEAD("%4", "%5", "%7")
                 "add.f32 s0, y0, y4;\nadd.f32 s1, y1, y5;\nadd.f32 s2, y2, y6;\nadd.f32 s3, y3, y7;\n"
                 "add.f32 s4, y8, y12;\nadd.f32 s5, y9, y13;\nadd.f32 s6, y10, y14;\nadd.f32 s7, y11, y15;\n"
                 "add.f32 s0, s0, s4;\nadd.f32 s1, s1, s5;\nadd.f32 s2, s2, s6;\nadd.f32 s3, s3, s7;\n"
                 "selp.f32 s4, s0, s2, h;\nselp.f32 s5, s1, s3, h;\nselp.f32 %0, s2, s0, h;\nselp.f32 %1, s3, s1, h;\n"
                 "shfl.sync.bfly.b32 %2, s4, 16, 0x1f, 0xffffffff;\nshfl.sync.bfly.b32 %3, s5, 16, 0x1f, 0xffffffff;\n"
                 POLL_TAIL "}"
                 : "=&f"(keep[0]), "=&f"(keep[1]), "=&f"(recv[0]), "=&f"(recv[1])
                 : "l"(p), "r"(tag), "r"(hi), "n"(SPIN_LIMIT) : "memory");
}

__device__ __forceinline__ void ldsm4(uint32_t addr, uint32_t (&a)[4]) {
    asm volatile("ldmatrix.sync.aligned.m8n8.x4.shared.b16 {%0,%1,%2,%3}, [%4];" : "=r"(a[0]), "=r"(a[1]), "=r"(a[2]), "=r"(a[3]) : "r"(addr) : "memory");
}
__device__ __forceinline__ void ldsm4t(uint32_t addr, uint32_t (&a)[4]) {
    asm volatile("ldmatrix.sync.aligned.m8n8.x4.trans.shared.b16 {%0,%1,%2,%3}, [%4];" : "=r"(a[0]), "=r"(a[1]), "=r"(a[2]), "=r"(a[3]) : "r"(addr) : "memory");
}
__device__ __forceinline__ void mma16816(float (&c)[4], const uint32_t (&a)[4], uint32_t b0, uint32_t b1) {
    asm volatile("mma.sync.aligned.m16n8k16.row.col.f32.bf16.bf16.f32 {%0,%1,%2,%3}, {%4,%5,%6,%7}, {%8,%9}, {%0,%1,%2,%3};"
                 : "+f"(c[0]), "+f"(c[1]), "+f"(c[2]), "+f"(c[3]) : "r"(a[0]), "r"(a[1]), "r"(a[2]), "r"(a[3]), "r"(b0), "r"(b1));
}
__device__ __forceinline__ float bf_lo(uint32_t u) { return __uint_as_float(u << 16); }
__device__ __forceinline__ float bf_hi(uint32_t u) { return __uint_as_float(u & 0xffff0000u); }
__device__ __forceinline__ float rbf(float v) { return __bfloat162float(__float2bfloat16_rn(v)); }
__device__ __forceinline__ uint32_t pack_bf(float lo, float hi) {
    uint32_t r;
    asm("cvt.rn.bf16x2.f32 %0, %1, %2;" : "=r"(r) : "f"(hi), "f"(lo));
    return r;
}
__device__ __forceinline__ float sel4(const float (&c)[4], int t) {
    float a = (t & 1) ? c[1] : c[0];
    float b = (t & 1) ? c[3] : c[2];
    return (t & 2) ? b : a;
}
__device__ __forceinline__ float ex2(float x) { float y; asm("ex2.approx.ftz.f32 %0, %1;" : "=f"(y) : "f"(x)); return y; }
__device__ __forceinline__ float sqrt_approx(float x) { float y; asm("sqrt.approx.f32 %0, %1;" : "=f"(y) : "f"(x)); return y; }

__host__ __device__ constexpr uint32_t slot_of(int s) { return SM_RING + (s % NS) * SLOT; }

__device__ __forceinline__ void layernorm(unsigned char* smem, int lane) {
    uint32_t xs[2][7];
#pragma unroll
    for (int b = 0; b < 2; b++)
#pragma unroll
        for (int i = 0; i < 7; i++) xs[b][i] = reinterpret_cast<const uint32_t*>(smem + SM_X)[b * (D_MODEL / 2) + i * 32 + lane];
#pragma unroll
    for (int b = 0; b < 2; b++) {
        float sum = 0.f;
#pragma unroll
        for (int i = 0; i < 7; i++) sum += bf_lo(xs[b][i]) + bf_hi(xs[b][i]);
#pragma unroll
        for (int o = 16; o > 0; o >>= 1) sum += __shfl_xor_sync(0xffffffffu, sum, o);
        const float mean = sum * (1.0f / D_MODEL);
        float sq = 0.f;
#pragma unroll
        for (int i = 0; i < 7; i++) {
            const float d0 = bf_lo(xs[b][i]) - mean, d1 = bf_hi(xs[b][i]) - mean;
            sq = fmaf(d0, d0, fmaf(d1, d1, sq));
        }
#pragma unroll
        for (int o = 16; o > 0; o >>= 1) sq += __shfl_xor_sync(0xffffffffu, sq, o);
        const float mb = rbf(mean);
        const float sd = rbf(sqrt_approx(rbf(rbf(sq * (1.0f / D_MODEL)) + 1e-5f)));
#pragma unroll
        for (int i = 0; i < 7; i++)
            reinterpret_cast<uint32_t*>(smem + SM_XN + b * XROW)[i * 32 + lane] =
                pack_bf(__fdividef(rbf(bf_lo(xs[b][i]) - mb), sd), __fdividef(rbf(bf_hi(xs[b][i]) - mb), sd));
    }
}

__device__ __forceinline__ void strip_partial(uint32_t sb, uint32_t strip, unsigned char* smem, int warp, int lane) {
    float c[2][2][4];
#pragma unroll
    for (int n = 0; n < 2; n++)
#pragma unroll
        for (int e = 0; e < 4; e++) c[n][0][e] = c[n][1][e] = 0.f;
    const uint32_t ba = sb + SM_XN + (lane & 1) * XROW + (lane >> 3) * 16 + warp * 128;
    const uint32_t aa = sb + strip + (warp * 64 + (lane & 7) + (lane >> 4) * 8) * 64 + (((lane >> 3) & 1) ^ ((lane & 7) >> 1)) * 16;
#pragma unroll
    for (int k2 = 0; k2 < 2; k2++) {
        uint32_t b[4];
        ldsm4(ba + k2 * 64, b);
#pragma unroll
        for (int n = 0; n < 2; n++) {
            uint32_t a0[4], a1[4];
            ldsm4t((aa ^ (n * 32)) + k2 * 2048, a0);
            ldsm4t((aa ^ (n * 32)) + k2 * 2048 + 1024, a1);
            mma16816(c[n][0], a0, b[0], b[1]);
            mma16816(c[n][1], a1, b[2], b[3]);
        }
    }
    float* red = reinterpret_cast<float*>(smem + SM_RED) + warp * 64 + lane;
#pragma unroll
    for (int n = 0; n < 2; n++) red[n * 32] = sel4(c[n][0], lane & 3) + sel4(c[n][1], lane & 3);
}
__device__ __forceinline__ float strip_sum(const unsigned char* smem, int idx) {
    const float* red = reinterpret_cast<const float*>(smem + SM_RED) + idx;
    return ((red[0] + red[64]) + (red[128] + red[192])) + ((red[256] + red[320]) + red[384]);
}

struct Prod {
    uint32_t sb, kvdst, sdst;
    const char *k, *v;
    const __nv_bfloat16* gu;
    bool ffn;
};
__host__ __device__ constexpr int bytes_before(int s) { return 28672 + s * 16384 + (s <= S_GU ? 0 : s < S_GU + 14 ? s - S_GU : 14) * 1792; }
__host__ __device__ constexpr int issue_time(int s) {
    return (int)((long long)bytes_before(s) * PACE_DT / 16384) - PACE_LEAD;
}

template <int S, class CLK>
__device__ __forceinline__ void produce(Prod& p, const CLK& clk) {
    if constexpr (S < NSTAGE) {
        if constexpr (S >= NS) mbar_wait(p.sb + SM_BAR + (NBAR + S - NS) * 8);
        clk.wait_base(p.sb, 0, issue_time(S));
        const char* src = (S < S_V ? p.k : p.v) + (S & 15) * (8 * SLOT);
#pragma unroll
        for (int i = 0; i < 8; i++) cp_async16_stream((p.kvdst ^ ((i & 1) * 64)) + slot_of(S) + i * 2048, src + i * 2048);
        if constexpr (S >= S_GU && S < S_GU + 14) {
            if (p.ffn) cp_async16_strip(p.sdst + (S - S_GU) * 2048, p.gu + (size_t)(S - S_GU) * 32 * FF);
        }
        cp_async_arrive(p.sb + SM_BAR + S * 8);
        produce<S + 1>(p, clk);
    }
}

__device__ __forceinline__ void fetch16(uint32_t dst, const char* src) {
#pragma unroll
    for (int i = 0; i < 4; i++)
        asm volatile("cp.async.cg.shared.global [%0], [%1], 16;" :: "r"((dst ^ (((i & 1) ^ (i >> 1)) * 64)) + i * 512), "l"(src + i * (4 * 896)) : "memory");
}
template <int PENDING, int OFF>
__device__ __forceinline__ void frag16(uint32_t (&a)[4][4], uint32_t addr) {
    asm volatile("cp.async.wait_group %0;" :: "n"(PENDING) : "memory");
    __syncwarp();
#pragma unroll
    for (int m = 0; m < 4; m++) ldsm4t((addr ^ (m * 32)) + OFF, a[m]);
}

__device__ __forceinline__ void load_x(uint32_t sb, const void* x, const void* epoch) {
    const uint32_t full0 = sb + SM_BAR;
    mbar_init(full0 + B_X * 8, 1);
    asm volatile("fence.mbarrier_init.release.cluster;" ::: "memory");
    asm volatile("mbarrier.arrive.expect_tx.shared::cta.b64 _, [%0], %1;" :: "r"(full0 + B_X * 8), "r"(1792 + 16) : "memory");
    asm volatile("cp.async.bulk.shared::cluster.global.mbarrier::complete_tx::bytes [%0], [%1], %2, [%3];"
                 :: "r"(sb + SM_X), "l"(x), "r"(1792), "r"(full0 + B_X * 8) : "memory");
    asm volatile("cp.async.bulk.shared::cluster.global.mbarrier::complete_tx::bytes [%0], [%1], %2, [%3];"
                 :: "r"(sb + SM_X + 1792), "l"(epoch), "r"(16), "r"(full0 + B_X * 8) : "memory");
}

enum { BAR_OB = 1, BAR_CONS = 2, BAR_LN = 3, BAR_FF = 4, BAR_FIN = 5, BAR_H = 6 };

template <bool SCALED>
__global__ void __launch_bounds__(NTHREADS, 1)
fused_decode_kernel(const __nv_bfloat16* __restrict__ wq, const __nv_bfloat16* __restrict__ kc, const __nv_bfloat16* __restrict__ x,
                    Scratch* __restrict__ scr, const __nv_bfloat16* __restrict__ vc, const __nv_bfloat16* __restrict__ wo,
                    const __nv_bfloat16* __restrict__ wg, const __nv_bfloat16* __restrict__ wu, const __nv_bfloat16* __restrict__ wd,
                    __nv_bfloat16* __restrict__ out, const Clock<SCALED> clk) {
    extern __shared__ __align__(128) unsigned char smem[];
    const uint32_t sb = (uint32_t)__cvta_generic_to_shared(smem);
    const int tid = threadIdx.x, lane = tid & 31;
    const int cta = blockIdx.x;
    const uint32_t full0 = sb + SM_BAR, done0 = full0 + NBAR * 8;
    const uint32_t t0 = clk.now();
    if (tid < 224) {
        const int row = (tid >> 5) * 64 + (lane >> 2);
        const char* src = reinterpret_cast<const char*>(wq) + (uint32_t)(row * (QCOLS * 2) + cta * 64 + (lane & 3) * 16);
        const uint32_t dst = sb + SM_STRIP + row * 64 + ((lane & 3) ^ (lane >> 3)) * 16;
#pragma unroll
        for (int i = 0; i < 8; i++) cp_async16_strip(dst + i * 512, src + i * (8 * QCOLS * 2));
    }
    const int warp = __shfl_sync(0xffffffffu, tid >> 5, 0);
    const int hkv = cta >> 4, j = cta & 15, bat = j >> 3, sp = j & 7;
    const int g = lane >> 2, t = lane & 3;

    if (warp < 8) {
        if (tid == 224) load_x(sb, x, &scr->epoch[cta * 8]);
        __syncthreads();
        mbar_wait(full0 + B_X * 8);
        const uint32_t epoch = *reinterpret_cast<const uint32_t*>(smem + SM_X + 1792);
        const uint32_t tag = pin((epoch + 1) & 1);
        uint32_t* qdst = reinterpret_cast<uint32_t*>(scr->q) + (hkv * 2 + (t & 1)) * 512 + j * 32 + warp * 16 + g + 8 * (t >> 1);
        if (warp == 7) {
            layernorm(smem, lane);
            bar_arrive(BAR_LN, 256);
        } else {
            asm volatile("cp.async.wait_all;" ::: "memory");
            bar_sync(BAR_LN, 256);
            strip_partial(sb, SM_STRIP, smem, warp, lane);
        }
        bar_sync(BAR_CONS, 256);
        if (warp < 2) {
            st_pub1(qdst, (pack_bf(0.f, strip_sum(smem, tid)) & 0xffff0000u) | tag);
        } else if (warp >= 4) {
            const int i = tid - 128;
            const uint4* qp = scr->q + (hkv * 2 + bat) * 128 + i;
            clk.wait_until(t0, Q_T);
            uint4 v;
            int it = 0;
            do {
                v = ld_poll4(qp);
                if (++it > SPIN_LIMIT) __trap();
            } while (warp_bad(bad4(v, tag)));
            *reinterpret_cast<uint2*>(smem + SM_Q + (i >> 6) * 528 + (i & 63) * 8) =
                make_uint2(__byte_perm(v.x, v.y, 0x7632), __byte_perm(v.z, v.w, 0x7632));
        }
        bar_sync(BAR_CONS, 256);
        if (tid == 96) scr->epoch[cta * 8] = epoch + 1;
        {
            uint32_t qf[8][4];
#pragma unroll
            for (int k2 = 0; k2 < 8; k2++) ldsm4(sb + SM_Q + (lane & 1) * 528 + k2 * 64 + (lane >> 3) * 16, qf[k2]);
            const int mt = warp & 1;
            const uint32_t aoff = (16 * mt + (lane & 15)) * 512 + ((lane >> 4) ^ (lane & 7)) * 16;
            float* sc = reinterpret_cast<float*>(smem + SM_S) + (t & 1) * 520 + (g >> 1) * 8 + (2 * mt + (t >> 1)) * 2 + (g & 1);
#pragma unroll 1
            for (int k = warp >> 1; k < 16; k += 4) {
                const int s = S_K + k;
                mbar_wait(full0 + s * 8);
                const uint32_t base = sb + SM_RING + (s >= NS ? s - NS : s) * SLOT + aoff;
                float c0[4] = {0.f, 0.f, 0.f, 0.f}, c1[4] = {0.f, 0.f, 0.f, 0.f};
#pragma unroll
                for (int k2 = 0; k2 < 8; k2++) {
                    uint32_t a0[4], a1[4];
                    ldsm4((base ^ ((k2 & 1) * 64)) + (k2 >> 1) * 128, a0);
                    ldsm4((base ^ ((k2 & 1) * 64 + 32)) + (k2 >> 1) * 128, a1);
                    mma16816(c0, a0, qf[k2][0], qf[k2][1]);
                    mma16816(c1, a1, qf[k2][2], qf[k2][3]);
                }
                __syncwarp();
                if (lane == 0) mbar_arrive(done0 + s * 8, 4);
                sc[k * 32] = rbf(sel4(c0, t) + sel4(c1, t));
            }
        }
        bar_sync(BAR_CONS, 256);
        {
            constexpr float C = SCALE_LOG2E;
            const float* sc = reinterpret_cast<const float*>(smem + SM_S);
            float* stat = reinterpret_cast<float*>(smem + SM_STAT);
            const float2 s0 = *reinterpret_cast<const float2*>(sc + 2 * tid);
            const float2 s1 = *reinterpret_cast<const float2*>(sc + 520 + 2 * tid);
            float m0 = fmaxf(s0.x, s0.y), m1 = fmaxf(s1.x, s1.y);
#pragma unroll
            for (int o = 16; o > 0; o >>= 1) {
                m0 = fmaxf(m0, __shfl_xor_sync(0xffffffffu, m0, o));
                m1 = fmaxf(m1, __shfl_xor_sync(0xffffffffu, m1, o));
            }
            if (lane == 0) *reinterpret_cast<float2*>(stat + warp * 2) = make_float2(m0, m1);
            bar_sync(BAR_CONS, 256);
#pragma unroll
            for (int w = 0; w < 8; w++) {
                const float2 mm = *reinterpret_cast<const float2*>(stat + w * 2);
                m0 = fmaxf(m0, mm.x); m1 = fmaxf(m1, mm.y);
            }
            const float p00 = ex2((s0.x - m0) * C), p01 = ex2((s0.y - m0) * C);
            const float p10 = ex2((s1.x - m1) * C), p11 = ex2((s1.y - m1) * C);
            uint32_t* ps = reinterpret_cast<uint32_t*>(smem + SM_P);
            ps[tid] = pack_bf(p00, p01);
            ps[272 + tid] = pack_bf(p10, p11);
            float l0 = p00 + p01, l1 = p10 + p11;
#pragma unroll
            for (int o = 16; o > 0; o >>= 1) {
                l0 += __shfl_xor_sync(0xffffffffu, l0, o);
                l1 += __shfl_xor_sync(0xffffffffu, l1, o);
            }
            if (lane == 0) *reinterpret_cast<float2*>(stat + 16 + warp * 2) = make_float2(l0, l1);
            bar_sync(BAR_CONS, 256);
            if (tid < 4) {
                float l = 0.f;
#pragma unroll
                for (int w = 0; w < 8; w++) l += stat[16 + w * 2 + (tid & 1)];
                st_pub2(scr->ml + cta * 4 + tid, tagf((tid & 1) ? m1 : m0, tag), tagf(l, tag));
            }
        }
        float wgt[2] = {0.f, 0.f}, own = 0.f;
        {
            float o0[4] = {0.f, 0.f, 0.f, 0.f}, o1[4] = {0.f, 0.f, 0.f, 0.f};
            float o2[4] = {0.f, 0.f, 0.f, 0.f}, o3[4] = {0.f, 0.f, 0.f, 0.f};
            const uint32_t aoff = ((lane & 7) + (lane >> 4) * 8) * 512 + ((warp * 4 + ((lane >> 3) & 1) * 2) ^ (lane & 7)) * 16;
            const uint4* ps = reinterpret_cast<const uint4*>(smem + SM_P + (g & 1) * 272 * 4) + t;
            uint32_t* dst = reinterpret_cast<uint32_t*>(scr->part) + ((size_t)(hkv * 16 + (t & 1) * 8 + warp) * 16 + j) * 32 +
                            (4 * (g & 3) + (t & 2) + (g >> 2)) * 2;
#pragma unroll
            for (int k = 0; k < 16; k++) {
                const uint4 pa = ps[k * 4];
                mbar_wait(full0 + (S_V + k) * 8);
                uint32_t a[4][4];
#pragma unroll
                for (int i = 0; i < 4; i++) ldsm4t(sb + (aoff ^ ((i & 1) * 16)) + slot_of(S_V + k) + (i >> 1) * 8192, a[i]);
                mma16816(o0, a[0], pa.x, pa.y);
                mma16816(o1, a[1], pa.x, pa.y);
                mma16816(o2, a[2], pa.z, pa.w);
                mma16816(o3, a[3], pa.z, pa.w);
                if (S_V + k + NS < NSTAGE + 3) {
                    __syncwarp();
                    if (lane == 0) mbar_arrive(done0 + (S_V + k) * 8, 1);
                }
                if (k == FFN_ST && warp < 7) {
                    strip_partial(sb, SM_STRIP, smem, warp, lane);
                    bar_arrive(BAR_FF, 256);
                }
                if (k == FFN_ST && warp == 7) {
                    bar_sync(BAR_FF, 256);
                    own = rbf(strip_sum(smem, (cta & 1) * 32 + lane));
                    st_pub1(scr->gu + (cta ^ 1) * 32 + lane, (pack_bf(0.f, strip_sum(smem, (~cta & 1) * 32 + lane)) & 0xffff0000u) | tag);
                }
                if (k == HID_ST && warp == 7) {
                    const uint2* mlp = scr->ml + (hkv * 16 + g) * 4 + (j >> 3);
                    uint2 a, b;
                    uint32_t other;
                    int it = 0;
                    do {
                        a = ld_poll2(mlp); b = ld_poll2(mlp + 32); other = ld_poll1(scr->gu + cta * 32 + lane);
                        if (++it > SPIN_LIMIT) __trap();
                    } while (warp_bad(bad2(a.x, a.y, tag) | bad2(b.x, b.y, tag) | (other ^ tag)));
                    float m[2] = {bf_hi(a.x), bf_hi(b.x)};
                    float l[2] = {__uint_as_float(a.y ^ tag), __uint_as_float(b.y ^ tag)};
#pragma unroll
                    for (int bb = 0; bb < 2; bb++) {
                        float M = m[bb];
                        M = fmaxf(M, __shfl_xor_sync(0xffffffffu, M, 4));
                        M = fmaxf(M, __shfl_xor_sync(0xffffffffu, M, 8));
                        M = fmaxf(M, __shfl_xor_sync(0xffffffffu, M, 16));
                        const float e = ex2((m[bb] - M) * SCALE_LOG2E);
                        float L = e * l[bb];
                        L += __shfl_xor_sync(0xffffffffu, L, 4);
                        L += __shfl_xor_sync(0xffffffffu, L, 8);
                        L += __shfl_xor_sync(0xffffffffu, L, 16);
                        wgt[bb] = __fdividef(e, L);
                    }
                    float ga = (cta & 1) ? bf_hi(other) : own;
                    ga *= (ga > 0.f ? 1.f : 0.f);
                    const float hv = ga * ((cta & 1) ? own : bf_hi(other));
                    const uint32_t w = pack_bf(hv, __shfl_xor_sync(0xffffffffu, hv, 2));
                    if (!(t & 2)) reinterpret_cast<uint32_t*>(smem + SM_H)[(t & 1) * 8 + (g & 3) * 2 + (g >> 2)] = w;
                    bar_arrive(BAR_H, 256);
                }
                if (k == PRE_ST) st_pub64(dst, tag ^ 1, 0);
            }
            const float v0 = sel4(o0, t) + sel4(o2, t), v1 = sel4(o1, t) + sel4(o3, t);
            st_pub64(dst, tagf(v0, tag), __float_as_uint(v1));
        }
        if (warp == 7) {
            const uint4* pp = pin(scr->part + (size_t)cta * 128 + lane);
            const uint32_t obaddr = pin(sb + SM_OB + (lane >> 4) * 64 + (lane & 7) * 8 + ((lane >> 3) & 1) * 4), ll = pin(lane);
            float w[4];
#pragma unroll
            for (int i = 0; i < 4; i++) w[i] = __shfl_sync(0xffffffffu, wgt[i >> 1], ((i & 1) * 4 + (lane >> 3)) * 4);
            clk.wait_until(clk.base(sb, 2), E2_T);
            float f[2][4];
            poll4(f, pp, tag, w);
            const bool h16 = ll & 16, h8 = ll & 8;
            float r4[4], r2[2];
#pragma unroll
            for (int e = 0; e < 4; e++) r4[e] = (h16 ? f[1][e] : f[0][e]) + __shfl_xor_sync(0xffffffffu, h16 ? f[0][e] : f[1][e], 16);
#pragma unroll
            for (int e = 0; e < 2; e++) r2[e] = (h8 ? r4[2 + e] : r4[e]) + __shfl_xor_sync(0xffffffffu, h8 ? r4[e] : r4[2 + e], 8);
            sts32(obaddr, pack_bf(r2[0], r2[1]));
            bar_arrive(BAR_OB, 256);
        } else if (warp < 4 && (cta & 1) == 0 && cta < 2 * NRED) {
            const uint4* op = pin(scr->outp + (size_t)(cta >> 1) * (NCTA * 4) + warp * 128 + lane);
            const int oidx = (t & 1) * D_MODEL + hkv * 64 + (lane >> 3) * 16 + (j >> 1) + (t >> 1) * 8;
            const float xv = __bfloat162float(reinterpret_cast<const __nv_bfloat16*>(smem + SM_X)[oidx]);
            __nv_bfloat16* optr = pin(out + oidx);
            const uint32_t red = pin(sb + SM_S + tid * 4), ll = pin(lane);
            float r2[2], rcv[2];
            const bool h8 = ll & 8;
            clk.wait_until(clk.base(sb, 3), E3_T);
            poll4_sum(r2, rcv, op, tag, ll & 16);
            r2[0] += rcv[0]; r2[1] += rcv[1];
            float r = (h8 ? r2[1] : r2[0]) + __shfl_xor_sync(0xffffffffu, h8 ? r2[0] : r2[1], 8);
            r += __shfl_xor_sync(0xffffffffu, r, 4);
            if (warp != 0) {
                sts32(red, __float_as_uint(r));
                bar_arrive(BAR_FIN, 128);
            } else {
                bar_sync(BAR_FIN, 128);
                r = ((xv + r) + lds32(red + 128)) + (lds32(red + 256) + lds32(red + 384));
                asm volatile("st.global.u16 [%0], %1;" :: "l"(optr), "h"(__bfloat16_as_ushort(__float2bfloat16_rn(r))) : "memory");
            }
        }
    } else if (warp < 15) {
        const int pt = tid - 256, pw = warp - 8;
        const char* pdn = reinterpret_cast<const char*>(wd) + (size_t)cta * 14336 + (lane >> 3) * 896 + pw * 128 + (lane & 7) * 16;
        const char* pwo = reinterpret_cast<const char*>(wo) + (size_t)cta * 28672 + (lane >> 3) * 896 + pw * 128 + (lane & 7) * 16;
        if (pw < 4) {
            if (lane == 0) {
#pragma unroll
                for (int i = 0; i < 9; i++) {
                    if (pw * 9 + i != B_X) mbar_init(full0 + (pw * 9 + i) * 8, NPT);
                    mbar_init(done0 + (pw * 9 + i) * 8, 8);
                }
            }
            Prod p;
            const size_t kvoff = ((size_t)(bat * 8 + hkv) * SK + (SK - WIN)) * DH * 2 + sp * SLOT + pt * 16;
            p.sb = sb;
            p.kvdst = (sb + pt * 16) ^ (pw * 16);
            p.sdst = sb + SM_STRIP + (pt >> 2) * 64 + ((pt & 3) ^ ((pt >> 3) & 3)) * 16;
            p.k = reinterpret_cast<const char*>(kc) + kvoff;
            p.v = reinterpret_cast<const char*>(vc) + kvoff;
            p.gu = ((cta & 1) ? wu : wg) + (cta >> 1) * 32 + (pt & 3) * 8 + (size_t)(pt >> 2) * FF;
            p.ffn = cta < NFFN;
            __syncthreads();
            produce<0>(p, clk);
        } else {
            __syncthreads();
        }
        mbar_wait(full0 + B_X * 8);
        const uint32_t tag = pin((*reinterpret_cast<const uint32_t*>(smem + SM_X + 1792) + 1) & 1);
        if (pw == 4 && (cta & 3) == 0) {
#pragma unroll 1
            for (int i = 0; i < 4; i++) {
                uint32_t sum = 0;
#pragma unroll
                for (int k = 0; k < NM; k++) {
                    mbar_wait(full0 + (MEND - NM + 1 + k + 6 * i) * 8);
                    sum += clk.now() - t0;
                }
                if (lane < 4) st_pub2(&scr->prog[i * 128 + cta + lane], ((t0 + sum / NM) & ~1u) | tag, (t0 & ~1u) | tag);
            }
        }
        mbar_wait(done0 + (NSTAGE + 2 - NS) * 8);
        const uint32_t ta = LATE_T, td = LATE_DT;
        uint4* odst = scr->outp + ((size_t)(pt >> 2) * NCTA + cta) * 4 + t;
        st_pub2x64(odst, tag ^ 1, 0, tag ^ 1, 0);
        const uint32_t fdst = (sb + pw * 2048 + lane * 16) ^ ((lane >> 3) * 16);
        clk.wait_base(sb, 1, ta);
        if (cta < NFFN) fetch16(fdst + slot_of(NSTAGE), pdn);
        asm volatile("cp.async.commit_group;" ::: "memory");
        clk.wait_base(sb, 1, ta + td);
        fetch16(fdst + slot_of(NSTAGE + 1), pwo);
        asm volatile("cp.async.commit_group;" ::: "memory");
        clk.wait_base(sb, 1, ta + 2 * td);
        fetch16(fdst + slot_of(NSTAGE + 2), pwo + 14336);
        asm volatile("cp.async.commit_group;" ::: "memory");
        bar_sync(BAR_H, 256);
        const uint2 h = *reinterpret_cast<const uint2*>(smem + SM_H + (g & 1) * 32 + t * 8);
        float c[4][4];
#pragma unroll
        for (int m = 0; m < 4; m++)
#pragma unroll
            for (int e = 0; e < 4; e++) c[m][e] = 0.f;
        const int r7 = ((lane & 7) >> 1) + 4 * (lane >> 4);
        const uint32_t aoff = sb + pw * 2048 + (r7 + 8 * (lane & 1)) * 128 + (((lane >> 3) & 1) ^ r7 ^ ((lane & 1) << 2)) * 16;
        const uint32_t obaddr = pin(sb + SM_OB + (g & 1) * 64 + t * 16), tt = pin(t);
        uint32_t a0[4][4], a1[4][4];
        frag16<2, slot_of(NSTAGE)>(a0, aoff);
        if (cta < NFFN) {
#pragma unroll
            for (int m = 0; m < 4; m++) mma16816(c[m], a0[m], h.x, h.y);
        }
        frag16<1, slot_of(NSTAGE + 1)>(a1, aoff);
        bar_sync(BAR_OB, 256);
        const uint4 ob = lds128(obaddr);
#pragma unroll
        for (int m = 0; m < 4; m++) mma16816(c[m], a1[m], ob.x, ob.y);
        frag16<0, slot_of(NSTAGE + 2)>(a0, aoff);
#pragma unroll
        for (int m = 0; m < 4; m++) mma16816(c[m], a0[m], ob.z, ob.w);
        st_pub2x64(odst, tagf(sel4(c[0], tt), tag), __float_as_uint(sel4(c[1], tt)), tagf(sel4(c[2], tt), tag), __float_as_uint(sel4(c[3], tt)));
    } else if (warp == 15) {
        if (lane < 4) reinterpret_cast<uint32_t*>(smem + SM_T0)[lane] = t0;
        __syncthreads();
        mbar_wait(full0 + B_X * 8);
        const uint32_t tag = (*reinterpret_cast<const uint32_t*>(smem + SM_X + 1792) + 1) & 1;
#pragma unroll 1
        for (int i = 0; i < 4; i++) {
            mbar_wait(full0 + (MEND + MGAP + 6 * i) * 8);
            uint2 v;
            int it = 0;
            do {
                v = ld_poll2(&scr->prog[i * 128 + lane * 4]);
                if (++it > SPIN_LIMIT) __trap();
            } while (warp_bad(bad2(v.x, v.y, tag)));
            const int nom = i == 0 ? M_NOM0 : i == 1 ? M_NOM1 : i == 2 ? M_NOM2 : M_NOM3;
            int base = (__reduce_add_sync(0xffffffffu, min(max((int)(v.x - t0), 0), 1 << 20)) >> 5) - nom;
            const int start = __reduce_add_sync(0xffffffffu, min(max((int)(v.y - t0), -(1 << 20)), 1 << 20)) >> 5;
            base = start + max(min(base - start, 2 * (base - start - DEAD)), 0);
            const int ahead = (lane == 0 ? nom : lane == 1 ? LATE_T : lane == 2 ? E2_T : E3_T - 150) - nom;
            const float rate = fminf(fmaxf(__fdividef((float)(base - start), (float)(nom - 500)), -0.01f), 0.045f);
            if (lane < 4) reinterpret_cast<volatile uint32_t*>(smem + SM_T0)[lane] = t0 + base + (int)(rate * (float)ahead);
        }
    }
}

}

extern "C" void kernel_launch(void* const* d_in, const int* in_sizes, int n_in, void* d_out, int out_size) {
    (void)in_sizes; (void)n_in; (void)out_size;
    static Scratch* scr = nullptr;
    static uint32_t scale = 64;
    if (!scr) {
        int dev = 0, khz = 0, bits = 0;
        cudaGetDevice(&dev);
        cudaDeviceGetAttribute(&khz, cudaDevAttrMemoryClockRate, dev);
        cudaDeviceGetAttribute(&bits, cudaDevAttrGlobalMemoryBusWidth, dev);
        if (khz > 0 && bits > 0) scale = (uint32_t)(64.0 * khz * bits / (2619000.0 * 5120.0) + 0.5);
        cudaFuncSetAttribute(fused_decode_kernel<false>, cudaFuncAttributeMaxDynamicSharedMemorySize, SM_TOTAL);
        cudaFuncSetAttribute(fused_decode_kernel<true>, cudaFuncAttributeMaxDynamicSharedMemorySize, SM_TOTAL);
        cudaGetSymbolAddress(reinterpret_cast<void**>(&scr), g_scratch);
    }
    typedef const __nv_bfloat16* P;
    if (scale == 64)
        fused_decode_kernel<false><<<NCTA, NTHREADS, SM_TOTAL>>>((P)d_in[3], (P)d_in[1], (P)d_in[0], scr, (P)d_in[2], (P)d_in[4], (P)d_in[6],
                                                                 (P)d_in[7], (P)d_in[8], (__nv_bfloat16*)d_out, Clock<false>{scale});
    else
        fused_decode_kernel<true><<<NCTA, NTHREADS, SM_TOTAL>>>((P)d_in[3], (P)d_in[1], (P)d_in[0], scr, (P)d_in[2], (P)d_in[4], (P)d_in[6],
                                                                (P)d_in[7], (P)d_in[8], (__nv_bfloat16*)d_out, Clock<true>{scale});
}
```

```cpp
#include <cuda_runtime.h>
#include <cuda_bf16.h>
#include <stdint.h>

namespace {

constexpr int PACE_DT = 640;
constexpr int PACE_LEAD = 350;
constexpr int LATE_T = 22370;
constexpr int LATE_DT = 400;
constexpr int Q_T = 4000;
constexpr int E2_T = 24090;
constexpr int E3_T = 24830;
constexpr int M_NOM0 = 4585;
constexpr int M_NOM1 = 8810;
constexpr int M_NOM2 = 13145;
constexpr int M_NOM3 = 17055;
constexpr int DEAD = 100;
constexpr int NM = 4;
constexpr int MEND = 5;
constexpr int MGAP = 3;
constexpr int NSLOT = 11;

constexpr int D_MODEL = 448;
constexpr int SK      = 32768;
constexpr int WIN     = 4096;
constexpr int DH      = 256;
constexpr int QCOLS   = 4096;
constexpr int FF      = 1792;
constexpr int NCTA    = 128;
constexpr int NFFN    = 112;
constexpr int NRED    = 56;
constexpr int NPT     = 128;
constexpr int NTHREADS = 512;

constexpr int NS     = NSLOT;
constexpr int SLOT   = 16384;
constexpr int XROW   = 912;
constexpr int S_K = 0, S_V = 16, NSTAGE = 32;
constexpr int S_GU   = 6;
constexpr int FFN_ST = S_GU - 3;
constexpr int HID_ST = S_GU;
constexpr int PRE_ST = 12;
constexpr int NBAR   = 36;
constexpr int B_X = NSTAGE, B_W = NBAR + NSTAGE;

constexpr int SM_RING  = 0;
constexpr int SM_STRIP = SM_RING + NS * SLOT;
constexpr int SM_S    = SM_STRIP + 448 * 64;
constexpr int SM_P    = SM_S + 2 * 520 * 4;
constexpr int SM_Q    = SM_P + 2 * 272 * 4;
constexpr int SM_XN   = SM_Q + 2 * 264 * 2;
constexpr int SM_X    = SM_XN + 2 * XROW;
constexpr int SM_RED  = SM_X + 1792 + 32;
constexpr int SM_STAT = SM_RED + 7 * 64 * 4;
constexpr int SM_OB   = SM_STAT + 2 * 8 * 2 * 4;
constexpr int SM_H    = SM_OB + 2 * 16 * 4;
constexpr int SM_T0   = SM_H + 2 * 8 * 4;
constexpr int SM_BAR  = SM_T0 + 16;
constexpr int SM_TOTAL = SM_BAR + 2 * NBAR * 8;
static_assert(SM_Q % 16 == 0 && SM_XN % 16 == 0 && SM_X % 16 == 0 && SM_OB % 16 == 0 && SM_P % 16 == 0 && SM_T0 % 16 == 0, "align");
static_assert(S_GU + 13 <= S_V + FFN_ST, "the gate/up strip lands with stage S_GU + 13");
static_assert(2 * NS >= 16, "K stage -> slot mapping");

constexpr int SPIN_LIMIT = 1 << 22;
constexpr float SCALE_LOG2E = 0.0625f * 1.4426950408889634f;

struct __align__(1024) Scratch {
    uint4    part[NCTA * 2 * 8 * 8];
    uint4    outp[NRED * NCTA * 4];
    uint4    q[8 * 2 * 128];
    unsigned gu[NCTA * 32];
    uint2    ml[NCTA * 4];
    uint2    prog[4 * 32 * 4];
    unsigned epoch[NCTA * 8];
};
__device__ Scratch g_scratch;

__device__ __forceinline__ void mbar_init(uint32_t bar, uint32_t cnt) {
    asm volatile("mbarrier.init.shared::cta.b64 [%0], %1;" :: "r"(bar), "r"(cnt) : "memory");
}
__device__ __forceinline__ void mbar_arrive(uint32_t bar, uint32_t cnt) {
    asm volatile("mbarrier.arrive.shared::cta.b64 _, [%0], %1;" :: "r"(bar), "r"(cnt) : "memory");
}
template <bool SCALED>
struct Clock {
    uint32_t scale;
    __device__ __forceinline__ uint32_t now() const {
        if constexpr (SCALED) {
            uint64_t t;
            asm volatile("mov.u64 %0, %globaltimer;" : "=l"(t));
            return (uint32_t)((t * scale) >> 6);
        } else {
            uint32_t t;
            asm volatile("mov.u32 %0, %globaltimer_lo;" : "=r"(t));
            return t;
        }
    }
    __device__ __forceinline__ static uint32_t base(uint32_t sb, int i) {
        uint32_t t;
        asm volatile("ld.volatile.shared.u32 %0, [%1];" : "=r"(t) : "r"(sb + SM_T0 + 4 * i) : "memory");
        return t;
    }
    __device__ __forceinline__ void wait_until(uint32_t t0, uint32_t dt) const { while (now() - t0 < dt) {} }
    __device__ __forceinline__ void wait_base(uint32_t sb, int i, uint32_t dt) const { while (now() - base(sb, i) < dt) {} }
};
__device__ __forceinline__ void mbar_wait(uint32_t bar) {
    asm volatile("{\n.reg .pred p;\nWAIT_LOOP:\nmbarrier.try_wait.parity.shared::cta.b64 p, [%0], 0;\n@!p bra WAIT_LOOP;\n}" :: "r"(bar) : "memory");
}
__device__ __forceinline__ void cp_async16_strip(uint32_t dst, const void* src) {
    asm volatile("cp.async.cg.shared.global.L2::128B [%0], [%1], 16;" :: "r"(dst), "l"(src) : "memory");
}
__device__ __forceinline__ void cp_async16_stream(uint32_t dst, const void* src) {
    asm volatile("{\n.reg .b64 pol;\ncreatepolicy.fractional.L2::evict_first.b64 pol, 1.0;\n"
                 "cp.async.cg.shared.global.L2::cache_hint [%0], [%1], 16, pol;\n}" :: "r"(dst), "l"(src) : "memory");
}
__device__ __forceinline__ void cp_async_arrive(uint32_t bar) {
    asm volatile("cp.async.mbarrier.arrive.noinc.shared::cta.b64 [%0];" :: "r"(bar) : "memory");
}
__device__ __forceinline__ void bar_sync(int id, int n)   { asm volatile("bar.sync %0, %1;" :: "r"(id), "r"(n) : "memory"); }
__device__ __forceinline__ void bar_arrive(int id, int n) { asm volatile("bar.arrive %0, %1;" :: "r"(id), "r"(n) : "memory"); }

__device__ __forceinline__ uint32_t ld_poll1(const void* p) {
    uint32_t v;
    asm volatile("ld.relaxed.gpu.global.u32 %0, [%1];" : "=r"(v) : "l"(p) : "memory");
    return v;
}
__device__ __forceinline__ uint2 ld_poll2(const void* p) {
    uint2 v;
    asm volatile("ld.relaxed.gpu.global.v2.u32 {%0,%1}, [%2];" : "=r"(v.x), "=r"(v.y) : "l"(p) : "memory");
    return v;
}
__device__ __forceinline__ uint4 ld_poll4(const void* p) {
    uint4 v;
    asm volatile("ld.relaxed.gpu.global.v4.u32 {%0,%1,%2,%3}, [%4];" : "=r"(v.x), "=r"(v.y), "=r"(v.z), "=r"(v.w) : "l"(p) : "memory");
    return v;
}
__device__ __forceinline__ void st_pub64(void* p, uint32_t a, uint32_t b) {
    asm volatile("{\n.reg .b64 d;\nmov.b64 d, {%1,%2};\nst.relaxed.gpu.global.b64 [%0], d;\n}" :: "l"(p), "r"(a), "r"(b) : "memory");
}
__device__ __forceinline__ void st_pub2x64(void* p, uint32_t a, uint32_t b, uint32_t c, uint32_t d) {
    asm volatile("{\n.reg .b64 d, e;\nmov.b64 d, {%1,%2};\nmov.b64 e, {%3,%4};\nst.relaxed.gpu.global.v2.b64 [%0], {d,e};\n}"
                 :: "l"(p), "r"(a), "r"(b), "r"(c), "r"(d) : "memory");
}
__device__ __forceinline__ void st_pub2(void* p, uint32_t a, uint32_t b) {
    asm volatile("st.relaxed.gpu.global.v2.u32 [%0], {%1,%2};" :: "l"(p), "r"(a), "r"(b) : "memory");
}
__device__ __forceinline__ void st_pub1(void* p, uint32_t a) {
    asm volatile("st.relaxed.gpu.global.u32 [%0], %1;" :: "l"(p), "r"(a) : "memory");
}
__device__ __forceinline__ uint32_t tagf(float v, uint32_t tag) {
    uint32_t r;
    asm("lop3.b32 %0, %1, 0xfffffffe, %2, 0xEA;" : "=r"(r) : "r"(__float_as_uint(v)), "r"(tag));
    return r;
}
__device__ __forceinline__ uint32_t pin(uint32_t v) {
    uint32_t r;
    asm volatile("shfl.sync.bfly.b32 %0, %1, 0, 0x1f, 0xffffffff;" : "=r"(r) : "r"(v));
    return r;
}
template <class T>
__device__ __forceinline__ T* pin(T* p) {
    const uint64_t u = reinterpret_cast<uint64_t>(p);
    return reinterpret_cast<T*>(((uint64_t)pin((uint32_t)(u >> 32)) << 32) | pin((uint32_t)u));
}
__device__ __forceinline__ void sts32(uint32_t addr, uint32_t v) { asm volatile("st.shared.u32 [%0], %1;" :: "r"(addr), "r"(v) : "memory"); }
__device__ __forceinline__ float lds32(uint32_t addr) { float v; asm volatile("ld.shared.f32 %0, [%1];" : "=f"(v) : "r"(addr) : "memory"); return v; }
__device__ __forceinline__ uint4 lds128(uint32_t addr) {
    uint4 v;
    asm volatile("ld.shared.v4.u32 {%0,%1,%2,%3}, [%4];" : "=r"(v.x), "=r"(v.y), "=r"(v.z), "=r"(v.w) : "r"(addr) : "memory");
    return v;
}
__device__ __forceinline__ uint32_t bad2(uint32_t a, uint32_t b, uint32_t tag) {
    uint32_t r;
    asm("lop3.b32 %0, %1, %2, %3, 0x7E;" : "=r"(r) : "r"(a), "r"(b), "r"(tag));
    return r;
}
__device__ __forceinline__ uint32_t bad4(const uint4& v, uint32_t tag) { return bad2(v.x, v.y, tag) | bad2(v.z, v.w, tag); }
__device__ __forceinline__ bool warp_bad(uint32_t bad) { return __any_sync(0xffffffffu, bad & 1u); }

#define POLL_HEAD(P, T, N)                                                                                        \
    ".reg .pred p0, p1, p2, p3, q;\n"                                                                             \
    ".reg .b32 a, m, it, y<16>;\n"                                                                                \
    ".reg .b64 d<8>;\n"                                                                                           \
    "setp.eq.u32 p0, 0, 0;\nsetp.eq.u32 p1, 0, 0;\nsetp.eq.u32 p2, 0, 0;\nsetp.eq.u32 p3, 0, 0;\n"                \
    "mov.u32 it, " N ";\n"                                                                                        \
    "POLL_LOOP:\n"                                                                                                \
    "@p0 ld.relaxed.gpu.global.v2.b64 {d0,d1}, [" P "];\n"                                                        \
    "@p1 ld.relaxed.gpu.global.v2.b64 {d2,d3}, [" P "+512];\n"                                                    \
    "@p2 ld.relaxed.gpu.global.v2.b64 {d4,d5}, [" P "+1024];\n"                                                   \
    "@p3 ld.relaxed.gpu.global.v2.b64 {d6,d7}, [" P "+1536];\n"                                                   \
    "sub.u32 it, it, 1;\n"                                                                                        \
    "min.u32 m, it, 1;\n"                                                        \
    "mov.b64 {y0,y1}, d0;\nmov.b64 {y2,y3}, d1;\nmov.b64 {y4,y5}, d2;\nmov.b64 {y6,y7}, d3;\n"                    \
    "mov.b64 {y8,y9}, d4;\nmov.b64 {y10,y11}, d5;\nmov.b64 {y12,y13}, d6;\nmov.b64 {y14,y15}, d7;\n"              \
    "xor.b32 y0, y0, " T ";\nxor.b32 y2, y2, " T ";\nlop3.b32 a, y0, y2, m, 0xA8;\nsetp.ne.u32 p0, a, 0;\n"       \
    "xor.b32 y4, y4, " T ";\nxor.b32 y6, y6, " T ";\nlop3.b32 a, y4, y6, m, 0xA8;\nsetp.ne.u32 p1, a, 0;\n"       \
    "xor.b32 y8, y8, " T ";\nxor.b32 y10, y10, " T ";\nlop3.b32 a, y8, y10, m, 0xA8;\nsetp.ne.u32 p2, a, 0;\n"    \
    "xor.b32 y12, y12, " T ";\nxor.b32 y14, y14, " T ";\nlop3.b32 a, y12, y14, m, 0xA8;\nsetp.ne.u32 p3, a, 0;\n" \
    "or.pred q, p0, p1;\nor.pred q, q, p2;\nor.pred q, q, p3;\nvote.sync.any.pred q, q, 0xffffffff;\n"
#define POLL_TAIL "@q bra POLL_LOOP;\n"

__device__ __forceinline__ void poll4(float (&f)[2][4], const uint4* p, uint32_t tag, const float (&w)[4]) {
    asm volatile("{\n" POLL_HEAD("%8", "%9", "%14") POLL_TAIL
                 "mul.f32 %0, y0, %10;\nmul.f32 %1, y1, %10;\nmul.f32 %2, y2, %10;\nmul.f32 %3, y3, %10;\n"
                 "mul.f32 %4, y8, %12;\nmul.f32 %5, y9, %12;\nmul.f32 %6, y10, %12;\nmul.f32 %7, y11, %12;\n"
                 "fma.rn.f32 %0, y4, %11, %0;\nfma.rn.f32 %1, y5, %11, %1;\nfma.rn.f32 %2, y6, %11, %2;\nfma.rn.f32 %3, y7, %11, %3;\n"
                 "fma.rn.f32 %4, y12, %13, %4;\nfma.rn.f32 %5, y13, %13, %5;\nfma.rn.f32 %6, y14, %13, %6;\nfma.rn.f32 %7, y15, %13, %7;\n"
                 "}"
                 : "=&f"(f[0][0]), "=&f"(f[0][1]), "=&f"(f[0][2]), "=&f"(f[0][3]), "=&f"(f[1][0]), "=&f"(f[1][1]), "=&f"(f[1][2]), "=&f"(f[1][3])
                 : "l"(p), "r"(tag), "f"(w[0]), "f"(w[1]), "f"(w[2]), "f"(w[3]), "n"(SPIN_LIMIT) : "memory");
}
__device__ __forceinline__ void poll4_sum(float (&keep)[2], float (&recv)[2], const uint4* p, uint32_t tag, uint32_t hi) {
    asm volatile("{\n.reg .pred h;\n.reg .f32 s<8>;\nsetp.ne.u32 h, %6, 0;\n" POLL_HEAD("%4", "%5", "%7")
                 "add.f32 s0, y0, y4;\nadd.f32 s1, y1, y5;\nadd.f32 s2, y2, y6;\nadd.f32 s3, y3, y7;\n"
                 "add.f32 s4, y8, y12;\nadd.f32 s5, y9, y13;\nadd.f32 s6, y10, y14;\nadd.f32 s7, y11, y15;\n"
                 "add.f32 s0, s0, s4;\nadd.f32 s1, s1, s5;\nadd.f32 s2, s2, s6;\nadd.f32 s3, s3, s7;\n"
                 "selp.f32 s4, s0, s2, h;\nselp.f32 s5, s1, s3, h;\nselp.f32 %0, s2, s0, h;\nselp.f32 %1, s3, s1, h;\n"
                 "shfl.sync.bfly.b32 %2, s4, 16, 0x1f, 0xffffffff;\nshfl.sync.bfly.b32 %3, s5, 16, 0x1f, 0xffffffff;\n"
                 POLL_TAIL "}"
                 : "=&f"(keep[0]), "=&f"(keep[1]), "=&f"(recv[0]), "=&f"(recv[1])
                 : "l"(p), "r"(tag), "r"(hi), "n"(SPIN_LIMIT) : "memory");
}

__device__ __forceinline__ void ldsm4(uint32_t addr, uint32_t (&a)[4]) {
    asm volatile("ldmatrix.sync.aligned.m8n8.x4.shared.b16 {%0,%1,%2,%3}, [%4];" : "=r"(a[0]), "=r"(a[1]), "=r"(a[2]), "=r"(a[3]) : "r"(addr) : "memory");
}
__device__ __forceinline__ void ldsm4t(uint32_t addr, uint32_t (&a)[4]) {
    asm volatile("ldmatrix.sync.aligned.m8n8.x4.trans.shared.b16 {%0,%1,%2,%3}, [%4];" : "=r"(a[0]), "=r"(a[1]), "=r"(a[2]), "=r"(a[3]) : "r"(addr) : "memory");
}
__device__ __forceinline__ void mma16816(float (&c)[4], const uint32_t (&a)[4], uint32_t b0, uint32_t b1) {
    asm volatile("mma.sync.aligned.m16n8k16.row.col.f32.bf16.bf16.f32 {%0,%1,%2,%3}, {%4,%5,%6,%7}, {%8,%9}, {%0,%1,%2,%3};"
                 : "+f"(c[0]), "+f"(c[1]), "+f"(c[2]), "+f"(c[3]) : "r"(a[0]), "r"(a[1]), "r"(a[2]), "r"(a[3]), "r"(b0), "r"(b1));
}
__device__ __forceinline__ float bf_lo(uint32_t u) { return __uint_as_float(u << 16); }
__device__ __forceinline__ float bf_hi(uint32_t u) { return __uint_as_float(u & 0xffff0000u); }
__device__ __forceinline__ float rbf(float v) { return __bfloat162float(__float2bfloat16_rn(v)); }
__device__ __forceinline__ uint32_t pack_bf(float lo, float hi) {
    uint32_t r;
    asm("cvt.rn.bf16x2.f32 %0, %1, %2;" : "=r"(r) : "f"(hi), "f"(lo));
    return r;
}
__device__ __forceinline__ float sel4(const float (&c)[4], int t) {
    float a = (t & 1) ? c[1] : c[0];
    float b = (t & 1) ? c[3] : c[2];
    return (t & 2) ? b : a;
}
__device__ __forceinline__ float ex2(float x) { float y; asm("ex2.approx.ftz.f32 %0, %1;" : "=f"(y) : "f"(x)); return y; }
__device__ __forceinline__ float sqrt_approx(float x) { float y; asm("sqrt.approx.f32 %0, %1;" : "=f"(y) : "f"(x)); return y; }

__host__ __device__ constexpr uint32_t slot_of(int s) { return SM_RING + (s % NS) * SLOT; }

__device__ __forceinline__ void layernorm(unsigned char* smem, int lane) {
    uint32_t xs[2][7];
#pragma unroll
    for (int b = 0; b < 2; b++)
#pragma unroll
        for (int i = 0; i < 7; i++) xs[b][i] = reinterpret_cast<const uint32_t*>(smem + SM_X)[b * (D_MODEL / 2) + i * 32 + lane];
#pragma unroll
    for (int b = 0; b < 2; b++) {
        float sum = 0.f;
#pragma unroll
        for (int i = 0; i < 7; i++) sum += bf_lo(xs[b][i]) + bf_hi(xs[b][i]);
#pragma unroll
        for (int o = 16; o > 0; o >>= 1) sum += __shfl_xor_sync(0xffffffffu, sum, o);
        const float mean = sum * (1.0f / D_MODEL);
        float sq = 0.f;
#pragma unroll
        for (int i = 0; i < 7; i++) {
            const float d0 = bf_lo(xs[b][i]) - mean, d1 = bf_hi(xs[b][i]) - mean;
            sq = fmaf(d0, d0, fmaf(d1, d1, sq));
        }
#pragma unroll
        for (int o = 16; o > 0; o >>= 1) sq += __shfl_xor_sync(0xffffffffu, sq, o);
        const float mb = rbf(mean);
        const float sd = rbf(sqrt_approx(rbf(rbf(sq * (1.0f / D_MODEL)) + 1e-5f)));
#pragma unroll
        for (int i = 0; i < 7; i++)
            reinterpret_cast<uint32_t*>(smem + SM_XN + b * XROW)[i * 32 + lane] =
                pack_bf(__fdividef(rbf(bf_lo(xs[b][i]) - mb), sd), __fdividef(rbf(bf_hi(xs[b][i]) - mb), sd));
    }
}

__device__ __forceinline__ void strip_partial(uint32_t sb, uint32_t strip, unsigned char* smem, int warp, int lane) {
    float c[2][2][4];
#pragma unroll
    for (int n = 0; n < 2; n++)
#pragma unroll
        for (int e = 0; e < 4; e++) c[n][0][e] = c[n][1][e] = 0.f;
    const uint32_t ba = sb + SM_XN + (lane & 1) * XROW + (lane >> 3) * 16 + warp * 128;
    const uint32_t aa = sb + strip + (warp * 64 + (lane & 7) + (lane >> 4) * 8) * 64 + (((lane >> 3) & 1) ^ ((lane & 7) >> 1)) * 16;
#pragma unroll
    for (int k2 = 0; k2 < 2; k2++) {
        uint32_t b[4];
        ldsm4(ba + k2 * 64, b);
#pragma unroll
        for (int n = 0; n < 2; n++) {
            uint32_t a0[4], a1[4];
            ldsm4t((aa ^ (n * 32)) + k2 * 2048, a0);
            ldsm4t((aa ^ (n * 32)) + k2 * 2048 + 1024, a1);
            mma16816(c[n][0], a0, b[0], b[1]);
            mma16816(c[n][1], a1, b[2], b[3]);
        }
    }
    float* red = reinterpret_cast<float*>(smem + SM_RED) + warp * 64 + lane;
#pragma unroll
    for (int n = 0; n < 2; n++) red[n * 32] = sel4(c[n][0], lane & 3) + sel4(c[n][1], lane & 3);
}
__device__ __forceinline__ float strip_sum(const unsigned char* smem, int idx) {
    const float* red = reinterpret_cast<const float*>(smem + SM_RED) + idx;
    return ((red[0] + red[64]) + (red[128] + red[192])) + ((red[256] + red[320]) + red[384]);
}

struct Prod {
    uint32_t sb, kvdst, sdst;
    const char *k, *v;
    const __nv_bfloat16* gu;
    bool ffn;
};
__host__ __device__ constexpr int bytes_before(int s) { return 28672 + s * 16384 + (s <= S_GU ? 0 : s < S_GU + 14 ? s - S_GU : 14) * 1792; }
__host__ __device__ constexpr int issue_time(int s) {
    return (int)((long long)bytes_before(s) * PACE_DT / 16384) - PACE_LEAD;
}

template <int S, class CLK>
__device__ __forceinline__ void produce(Prod& p, const CLK& clk) {
    if constexpr (S < NSTAGE) {
        if constexpr (S >= NS) mbar_wait(p.sb + SM_BAR + (NBAR + S - NS) * 8);
        if constexpr (S == S_GU) mbar_wait(p.sb + SM_BAR + B_W * 8);
        clk.wait_base(p.sb, 0, issue_time(S));
        const char* src = (S < S_V ? p.k : p.v) + (S & 15) * (8 * SLOT);
#pragma unroll
        for (int i = 0; i < 8; i++) cp_async16_stream((p.kvdst ^ ((i & 1) * 64)) + slot_of(S) + i * 2048, src + i * 2048);
        if constexpr (S >= S_GU && S < S_GU + 14) {
            if (p.ffn) cp_async16_strip(p.sdst + (S - S_GU) * 2048, p.gu + (size_t)(S - S_GU) * 32 * FF);
        }
        cp_async_arrive(p.sb + SM_BAR + S * 8);
        produce<S + 1>(p, clk);
    }
}

__device__ __forceinline__ void fetch16(uint32_t dst, const char* src) {
#pragma unroll
    for (int i = 0; i < 4; i++)
        asm volatile("cp.async.cg.shared.global [%0], [%1], 16;" :: "r"((dst ^ (((i & 1) ^ (i >> 1)) * 64)) + i * 512), "l"(src + i * (4 * 896)) : "memory");
}
template <int PENDING, int OFF>
__device__ __forceinline__ void frag16(uint32_t (&a)[4][4], uint32_t addr) {
    asm volatile("cp.async.wait_group %0;" :: "n"(PENDING) : "memory");
    __syncwarp();
#pragma unroll
    for (int m = 0; m < 4; m++) ldsm4t((addr ^ (m * 32)) + OFF, a[m]);
}

__device__ __forceinline__ void load_x(uint32_t sb, const void* x, const void* epoch) {
    const uint32_t full0 = sb + SM_BAR;
    mbar_init(full0 + B_X * 8, 1);
    asm volatile("fence.mbarrier_init.release.cluster;" ::: "memory");
    asm volatile("mbarrier.arrive.expect_tx.shared::cta.b64 _, [%0], %1;" :: "r"(full0 + B_X * 8), "r"(1792 + 16) : "memory");
    asm volatile("cp.async.bulk.shared::cluster.global.mbarrier::complete_tx::bytes [%0], [%1], %2, [%3];"
                 :: "r"(sb + SM_X), "l"(x), "r"(1792), "r"(full0 + B_X * 8) : "memory");
    asm volatile("cp.async.bulk.shared::cluster.global.mbarrier::complete_tx::bytes [%0], [%1], %2, [%3];"
                 :: "r"(sb + SM_X + 1792), "l"(epoch), "r"(16), "r"(full0 + B_X * 8) : "memory");
}

enum { BAR_OB = 1, BAR_CONS = 2, BAR_LN = 3, BAR_FF = 4, BAR_FIN = 5, BAR_H = 6 };

template <bool SCALED>
__global__ void __launch_bounds__(NTHREADS, 1)
fused_decode_kernel(const __nv_bfloat16* __restrict__ wq, const __nv_bfloat16* __restrict__ kc, const __nv_bfloat16* __restrict__ x,
                    Scratch* __restrict__ scr, const __nv_bfloat16* __restrict__ vc, const __nv_bfloat16* __restrict__ wo,
                    const __nv_bfloat16* __restrict__ wg, const __nv_bfloat16* __restrict__ wu, const __nv_bfloat16* __restrict__ wd,
                    __nv_bfloat16* __restrict__ out, const Clock<SCALED> clk) {
    extern __shared__ __align__(128) unsigned char smem[];
    const uint32_t sb = (uint32_t)__cvta_generic_to_shared(smem);
    const int tid = threadIdx.x, lane = tid & 31;
    const int cta = blockIdx.x;
    const uint32_t full0 = sb + SM_BAR, done0 = full0 + NBAR * 8;
    const uint32_t t0 = clk.now();
    if (tid < 224) {
        const int row = (tid >> 5) * 64 + (lane >> 2);
        const char* src = reinterpret_cast<const char*>(wq) + (uint32_t)(row * (QCOLS * 2) + cta * 64 + (lane & 3) * 16);
        const uint32_t dst = sb + SM_STRIP + row * 64 + ((lane & 3) ^ (lane >> 3)) * 16;
#pragma unroll
        for (int i = 0; i < 8; i++) cp_async16_strip(dst + i * 512, src + i * (8 * QCOLS * 2));
    }
    const int warp = __shfl_sync(0xffffffffu, tid >> 5, 0);
    const int hkv = cta >> 4, j = cta & 15, bat = j >> 3, sp = j & 7;
    const int g = lane >> 2, t = lane & 3;

    if (warp < 8) {
        if (tid == 224) load_x(sb, x, &scr->epoch[cta * 8]);
        __syncthreads();
        mbar_wait(full0 + B_X * 8);
        const uint32_t epoch = *reinterpret_cast<const uint32_t*>(smem + SM_X + 1792);
        const uint32_t tag = pin((epoch + 1) & 1);
        uint32_t* qdst = reinterpret_cast<uint32_t*>(scr->q) + (hkv * 2 + (t & 1)) * 512 + j * 32 + warp * 16 + g + 8 * (t >> 1);
        if (warp == 7) {
            layernorm(smem, lane);
            bar_arrive(BAR_LN, 256);
        } else {
            asm volatile("cp.async.wait_all;" ::: "memory");
            bar_sync(BAR_LN, 256);
            strip_partial(sb, SM_STRIP, smem, warp, lane);
        }
        bar_sync(BAR_CONS, 256);
        if (tid == 96) mbar_arrive(full0 + B_W * 8, 8);
        if (warp < 2) {
            st_pub1(qdst, (pack_bf(0.f, strip_sum(smem, tid)) & 0xffff0000u) | tag);
        } else if (warp >= 4) {
            const int i = tid - 128;
            const uint4* qp = scr->q + (hkv * 2 + bat) * 128 + i;
            clk.wait_until(t0, Q_T);
            uint4 v;
            int it = 0;
            do {
                v = ld_poll4(qp);
                if (++it > SPIN_LIMIT) __trap();
            } while (warp_bad(bad4(v, tag)));
            *reinterpret_cast<uint2*>(smem + SM_Q + (i >> 6) * 528 + (i & 63) * 8) =
                make_uint2(__byte_perm(v.x, v.y, 0x7632), __byte_perm(v.z, v.w, 0x7632));
        }
        bar_sync(BAR_CONS, 256);
        if (tid == 96) scr->epoch[cta * 8] = epoch + 1;
        {
            uint32_t qf[8][4];
#pragma unroll
            for (int k2 = 0; k2 < 8; k2++) ldsm4(sb + SM_Q + (lane & 1) * 528 + k2 * 64 + (lane >> 3) * 16, qf[k2]);
            const int mt = warp & 1;
            const uint32_t aoff = (16 * mt + (lane & 15)) * 512 + ((lane >> 4) ^ (lane & 7)) * 16;
            float* sc = reinterpret_cast<float*>(smem + SM_S) + (t & 1) * 520 + (g >> 1) * 8 + (2 * mt + (t >> 1)) * 2 + (g & 1);
#pragma unroll 1
            for (int k = warp >> 1; k < 16; k += 4) {
                const int s = S_K + k;
                mbar_wait(full0 + s * 8);
                const uint32_t base = sb + SM_RING + (s >= NS ? s - NS : s) * SLOT + aoff;
                float c0[4] = {0.f, 0.f, 0.f, 0.f}, c1[4] = {0.f, 0.f, 0.f, 0.f};
#pragma unroll
                for (int k2 = 0; k2 < 8; k2++) {
                    uint32_t a0[4], a1[4];
                    ldsm4((base ^ ((k2 & 1) * 64)) + (k2 >> 1) * 128, a0);
                    ldsm4((base ^ ((k2 & 1) * 64 + 32)) + (k2 >> 1) * 128, a1);
                    mma16816(c0, a0, qf[k2][0], qf[k2][1]);
                    mma16816(c1, a1, qf[k2][2], qf[k2][3]);
                }
                __syncwarp();
                if (lane == 0) mbar_arrive(done0 + s * 8, 4);
                sc[k * 32] = rbf(sel4(c0, t) + sel4(c1, t));
            }
        }
        bar_sync(BAR_CONS, 256);
        {
            constexpr float C = SCALE_LOG2E;
            const float* sc = reinterpret_cast<const float*>(smem + SM_S);
            float* stat = reinterpret_cast<float*>(smem + SM_STAT);
            const float2 s0 = *reinterpret_cast<const float2*>(sc + 2 * tid);
            const float2 s1 = *reinterpret_cast<const float2*>(sc + 520 + 2 * tid);
            float m0 = fmaxf(s0.x, s0.y), m1 = fmaxf(s1.x, s1.y);
#pragma unroll
            for (int o = 16; o > 0; o >>= 1) {
                m0 = fmaxf(m0, __shfl_xor_sync(0xffffffffu, m0, o));
                m1 = fmaxf(m1, __shfl_xor_sync(0xffffffffu, m1, o));
            }
            if (lane == 0) *reinterpret_cast<float2*>(stat + warp * 2) = make_float2(m0, m1);
            bar_sync(BAR_CONS, 256);
#pragma unroll
            for (int w = 0; w < 8; w++) {
                const float2 mm = *reinterpret_cast<const float2*>(stat + w * 2);
                m0 = fmaxf(m0, mm.x); m1 = fmaxf(m1, mm.y);
            }
            const float p00 = ex2((s0.x - m0) * C), p01 = ex2((s0.y - m0) * C);
            const float p10 = ex2((s1.x - m1) * C), p11 = ex2((s1.y - m1) * C);
            uint32_t* ps = reinterpret_cast<uint32_t*>(smem + SM_P);
            ps[tid] = pack_bf(p00, p01);
            ps[272 + tid] = pack_bf(p10, p11);
            float l0 = p00 + p01, l1 = p10 + p11;
#pragma unroll
            for (int o = 16; o > 0; o >>= 1) {
                l0 += __shfl_xor_sync(0xffffffffu, l0, o);
                l1 += __shfl_xor_sync(0xffffffffu, l1, o);
            }
            if (lane == 0) *reinterpret_cast<float2*>(stat + 16 + warp * 2) = make_float2(l0, l1);
            bar_sync(BAR_CONS, 256);
            if (tid < 4) {
                float l = 0.f;
#pragma unroll
                for (int w = 0; w < 8; w++) l += stat[16 + w * 2 + (tid & 1)];
                st_pub2(scr->ml + cta * 4 + tid, tagf((tid & 1) ? m1 : m0, tag), tagf(l, tag));
            }
        }
        float wgt[2] = {0.f, 0.f}, own = 0.f;
        {
            float o0[4] = {0.f, 0.f, 0.f, 0.f}, o1[4] = {0.f, 0.f, 0.f, 0.f};
            float o2[4] = {0.f, 0.f, 0.f, 0.f}, o3[4] = {0.f, 0.f, 0.f, 0.f};
            const uint32_t aoff = ((lane & 7) + (lane >> 4) * 8) * 512 + ((warp * 4 + ((lane >> 3) & 1) * 2) ^ (lane & 7)) * 16;
            const uint4* ps = reinterpret_cast<const uint4*>(smem + SM_P + (g & 1) * 272 * 4) + t;
            uint32_t* dst = reinterpret_cast<uint32_t*>(scr->part) + ((size_t)(hkv * 16 + (t & 1) * 8 + warp) * 16 + j) * 32 +
                            (4 * (g & 3) + (t & 2) + (g >> 2)) * 2;
#pragma unroll
            for (int k = 0; k < 16; k++) {
                const uint4 pa = ps[k * 4];
                mbar_wait(full0 + (S_V + k) * 8);
                uint32_t a[4][4];
#pragma unroll
                for (int i = 0; i < 4; i++) ldsm4t(sb + (aoff ^ ((i & 1) * 16)) + slot_of(S_V + k) + (i >> 1) * 8192, a[i]);
                mma16816(o0, a[0], pa.x, pa.y);
                mma16816(o1, a[1], pa.x, pa.y);
                mma16816(o2, a[2], pa.z, pa.w);
                mma16816(o3, a[3], pa.z, pa.w);
                if (S_V + k + NS < NSTAGE + 3) {
                    __syncwarp();
                    if (lane == 0) mbar_arrive(done0 + (S_V + k) * 8, 1);
                }
                if (k == FFN_ST && warp < 7) {
                    strip_partial(sb, SM_STRIP, smem, warp, lane);
                    bar_arrive(BAR_FF, 256);
                }
                if (k == FFN_ST && warp == 7) {
                    bar_sync(BAR_FF, 256);
                    own = rbf(strip_sum(smem, (cta & 1) * 32 + lane));
                    st_pub1(scr->gu + (cta ^ 1) * 32 + lane, (pack_bf(0.f, strip_sum(smem, (~cta & 1) * 32 + lane)) & 0xffff0000u) | tag);
                }
                if (k == HID_ST && warp == 7) {
                    const uint2* mlp = scr->ml + (hkv * 16 + g) * 4 + (j >> 3);
                    uint2 a, b;
                    uint32_t other;
                    int it = 0;
                    do {
                        a = ld_poll2(mlp); b = ld_poll2(mlp + 32); other = ld_poll1(scr->gu + cta * 32 + lane);
                        if (++it > SPIN_LIMIT) __trap();
                    } while (warp_bad(bad2(a.x, a.y, tag) | bad2(b.x, b.y, tag) | (other ^ tag)));
                    float m[2] = {bf_hi(a.x), bf_hi(b.x)};
                    float l[2] = {__uint_as_float(a.y ^ tag), __uint_as_float(b.y ^ tag)};
#pragma unroll
                    for (int bb = 0; bb < 2; bb++) {
                        float M = m[bb];
                        M = fmaxf(M, __shfl_xor_sync(0xffffffffu, M, 4));
                        M = fmaxf(M, __shfl_xor_sync(0xffffffffu, M, 8));
                        M = fmaxf(M, __shfl_xor_sync(0xffffffffu, M, 16));
                        const float e = ex2((m[bb] - M) * SCALE_LOG2E);
                        float L = e * l[bb];
                        L += __shfl_xor_sync(0xffffffffu, L, 4);
                        L += __shfl_xor_sync(0xffffffffu, L, 8);
                        L += __shfl_xor_sync(0xffffffffu, L, 16);
                        wgt[bb] = __fdividef(e, L);
                    }
                    float ga = (cta & 1) ? bf_hi(other) : own;
                    ga *= (ga > 0.f ? 1.f : 0.f);
                    const float hv = ga * ((cta & 1) ? own : bf_hi(other));
                    const uint32_t w = pack_bf(hv, __shfl_xor_sync(0xffffffffu, hv, 2));
                    if (!(t & 2)) reinterpret_cast<uint32_t*>(smem + SM_H)[(t & 1) * 8 + (g & 3) * 2 + (g >> 2)] = w;
                    bar_arrive(BAR_H, 256);
                }
                if (k == PRE_ST) st_pub64(dst, tag ^ 1, 0);
            }
            const float v0 = sel4(o0, t) + sel4(o2, t), v1 = sel4(o1, t) + sel4(o3, t);
            st_pub64(dst, tagf(v0, tag), __float_as_uint(v1));
        }
        if (warp == 7) {
            const uint4* pp = pin(scr->part + (size_t)cta * 128 + lane);
            const uint32_t obaddr = pin(sb + SM_OB + (lane >> 4) * 64 + (lane & 7) * 8 + ((lane >> 3) & 1) * 4), ll = pin(lane);
            float w[4];
#pragma unroll
            for (int i = 0; i < 4; i++) w[i] = __shfl_sync(0xffffffffu, wgt[i >> 1], ((i & 1) * 4 + (lane >> 3)) * 4);
            clk.wait_until(clk.base(sb, 2), E2_T);
            float f[2][4];
            poll4(f, pp, tag, w);
            const bool h16 = ll & 16, h8 = ll & 8;
            float r4[4], r2[2];
#pragma unroll
            for (int e = 0; e < 4; e++) r4[e] = (h16 ? f[1][e] : f[0][e]) + __shfl_xor_sync(0xffffffffu, h16 ? f[0][e] : f[1][e], 16);
#pragma unroll
            for (int e = 0; e < 2; e++) r2[e] = (h8 ? r4[2 + e] : r4[e]) + __shfl_xor_sync(0xffffffffu, h8 ? r4[e] : r4[2 + e], 8);
            sts32(obaddr, pack_bf(r2[0], r2[1]));
            bar_arrive(BAR_OB, 256);
        } else if (warp < 4 && (cta & 1) == 0 && cta < 2 * NRED) {
            const uint4* op = pin(scr->outp + (size_t)(cta >> 1) * (NCTA * 4) + warp * 128 + lane);
            const int oidx = (t & 1) * D_MODEL + hkv * 64 + (lane >> 3) * 16 + (j >> 1) + (t >> 1) * 8;
            const float xv = __bfloat162float(reinterpret_cast<const __nv_bfloat16*>(smem + SM_X)[oidx]);
            __nv_bfloat16* optr = pin(out + oidx);
            const uint32_t red = pin(sb + SM_S + tid * 4), ll = pin(lane);
            float r2[2], rcv[2];
            const bool h8 = ll & 8;
            clk.wait_until(clk.base(sb, 3), E3_T);
            poll4_sum(r2, rcv, op, tag, ll & 16);
            r2[0] += rcv[0]; r2[1] += rcv[1];
            float r = (h8 ? r2[1] : r2[0]) + __shfl_xor_sync(0xffffffffu, h8 ? r2[0] : r2[1], 8);
            r += __shfl_xor_sync(0xffffffffu, r, 4);
            if (warp != 0) {
                sts32(red, __float_as_uint(r));
                bar_arrive(BAR_FIN, 128);
            } else {
                bar_sync(BAR_FIN, 128);
                r = ((xv + r) + lds32(red + 128)) + (lds32(red + 256) + lds32(red + 384));
                asm volatile("st.global.u16 [%0], %1;" :: "l"(optr), "h"(__bfloat16_as_ushort(__float2bfloat16_rn(r))) : "memory");
            }
        }
    } else if (warp < 15) {
        const int pt = tid - 256, pw = warp - 8;
        const char* pdn = reinterpret_cast<const char*>(wd) + (size_t)cta * 14336 + (lane >> 3) * 896 + pw * 128 + (lane & 7) * 16;
        const char* pwo = reinterpret_cast<const char*>(wo) + (size_t)cta * 28672 + (lane >> 3) * 896 + pw * 128 + (lane & 7) * 16;
        if (pw < 4) {
            if (lane == 0) {
#pragma unroll
                for (int i = 0; i < 9; i++) {
                    if (pw * 9 + i != B_X) mbar_init(full0 + (pw * 9 + i) * 8, NPT);
                    mbar_init(done0 + (pw * 9 + i) * 8, 8);
                }
            }
            Prod p;
            const size_t kvoff = ((size_t)(bat * 8 + hkv) * SK + (SK - WIN)) * DH * 2 + sp * SLOT + pt * 16;
            p.sb = sb;
            p.kvdst = (sb + pt * 16) ^ (pw * 16);
            p.sdst = sb + SM_STRIP + (pt >> 2) * 64 + ((pt & 3) ^ ((pt >> 3) & 3)) * 16;
            p.k = reinterpret_cast<const char*>(kc) + kvoff;
            p.v = reinterpret_cast<const char*>(vc) + kvoff;
            p.gu = ((cta & 1) ? wu : wg) + (cta >> 1) * 32 + (pt & 3) * 8 + (size_t)(pt >> 2) * FF;
            p.ffn = cta < NFFN;
            __syncthreads();
            produce<0>(p, clk);
        } else {
            __syncthreads();
        }
        mbar_wait(full0 + B_X * 8);
        const uint32_t tag = pin((*reinterpret_cast<const uint32_t*>(smem + SM_X + 1792) + 1) & 1);
        if (pw == 4 && (cta & 3) == 0) {
#pragma unroll 1
            for (int i = 0; i < 4; i++) {
                uint32_t sum = 0;
#pragma unroll
                for (int k = 0; k < NM; k++) {
                    mbar_wait(full0 + (MEND - NM + 1 + k + 6 * i) * 8);
                    sum += clk.now() - t0;
                }
                if (lane < 4) st_pub2(&scr->prog[i * 128 + cta + lane], ((t0 + sum / NM) & ~1u) | tag, (t0 & ~1u) | tag);
            }
        }
        mbar_wait(done0 + (NSTAGE + 2 - NS) * 8);
        const uint32_t ta = LATE_T, td = LATE_DT;
        uint4* odst = scr->outp + ((size_t)(pt >> 2) * NCTA + cta) * 4 + t;
        st_pub2x64(odst, tag ^ 1, 0, tag ^ 1, 0);
        const uint32_t fdst = (sb + pw * 2048 + lane * 16) ^ ((lane >> 3) * 16);
        clk.wait_base(sb, 1, ta);
        if (cta < NFFN) fetch16(fdst + slot_of(NSTAGE), pdn);
        asm volatile("cp.async.commit_group;" ::: "memory");
        clk.wait_base(sb, 1, ta + td);
        fetch16(fdst + slot_of(NSTAGE + 1), pwo);
        asm volatile("cp.async.commit_group;" ::: "memory");
        clk.wait_base(sb, 1, ta + 2 * td);
        fetch16(fdst + slot_of(NSTAGE + 2), pwo + 14336);
        asm volatile("cp.async.commit_group;" ::: "memory");
        bar_sync(BAR_H, 256);
        const uint2 h = *reinterpret_cast<const uint2*>(smem + SM_H + (g & 1) * 32 + t * 8);
        float c[4][4];
#pragma unroll
        for (int m = 0; m < 4; m++)
#pragma unroll
            for (int e = 0; e < 4; e++) c[m][e] = 0.f;
        const int r7 = ((lane & 7) >> 1) + 4 * (lane >> 4);
        const uint32_t aoff = sb + pw * 2048 + (r7 + 8 * (lane & 1)) * 128 + (((lane >> 3) & 1) ^ r7 ^ ((lane & 1) << 2)) * 16;
        const uint32_t obaddr = pin(sb + SM_OB + (g & 1) * 64 + t * 16), tt = pin(t);
        uint32_t a0[4][4], a1[4][4];
        frag16<2, slot_of(NSTAGE)>(a0, aoff);
        if (cta < NFFN) {
#pragma unroll
            for (int m = 0; m < 4; m++) mma16816(c[m], a0[m], h.x, h.y);
        }
        frag16<1, slot_of(NSTAGE + 1)>(a1, aoff);
        bar_sync(BAR_OB, 256);
        const uint4 ob = lds128(obaddr);
#pragma unroll
        for (int m = 0; m < 4; m++) mma16816(c[m], a1[m], ob.x, ob.y);
        frag16<0, slot_of(NSTAGE + 2)>(a0, aoff);
#pragma unroll
        for (int m = 0; m < 4; m++) mma16816(c[m], a0[m], ob.z, ob.w);
        st_pub2x64(odst, tagf(sel4(c[0], tt), tag), __float_as_uint(sel4(c[1], tt)), tagf(sel4(c[2], tt), tag), __float_as_uint(sel4(c[3], tt)));
    } else if (warp == 15) {
        if (lane < 4) reinterpret_cast<uint32_t*>(smem + SM_T0)[lane] = t0;
        __syncthreads();
        mbar_wait(full0 + B_X * 8);
        const uint32_t tag = (*reinterpret_cast<const uint32_t*>(smem + SM_X + 1792) + 1) & 1;
#pragma unroll 1
        for (int i = 0; i < 4; i++) {
            mbar_wait(full0 + (MEND + MGAP + 6 * i) * 8);
            uint2 v;
            int it = 0;
            do {
                v = ld_poll2(&scr->prog[i * 128 + lane * 4]);
                if (++it > SPIN_LIMIT) __trap();
            } while (warp_bad(bad2(v.x, v.y, tag)));
            const int nom = i == 0 ? M_NOM0 : i == 1 ? M_NOM1 : i == 2 ? M_NOM2 : M_NOM3;
            int base = (__reduce_add_sync(0xffffffffu, min(max((int)(v.x - t0), 0), 1 << 20)) >> 5) - nom;
            const int start = __reduce_add_sync(0xffffffffu, min(max((int)(v.y - t0), -(1 << 20)), 1 << 20)) >> 5;
            base = start + max(min(base - start, 2 * (base - start - DEAD)), 0);
            const int ahead = (lane == 0 ? nom : lane == 1 ? LATE_T : lane == 2 ? E2_T : E3_T - 150) - nom;
            const float rate = fminf(fmaxf(__fdividef((float)(base - start), (float)(nom - 500)), -0.01f), 0.045f);
            if (lane < 4) reinterpret_cast<volatile uint32_t*>(smem + SM_T0)[lane] = t0 + base + (int)(rate * (float)ahead);
        }
    }
}

}

extern "C" void kernel_launch(void* const* d_in, const int* in_sizes, int n_in, void* d_out, int out_size) {
    (void)in_sizes; (void)n_in; (void)out_size;
    static Scratch* scr = nullptr;
    static uint32_t scale = 64;
    if (!scr) {
        int dev = 0, khz = 0, bits = 0;
        cudaGetDevice(&dev);
        cudaDeviceGetAttribute(&khz, cudaDevAttrMemoryClockRate, dev);
        cudaDeviceGetAttribute(&bits, cudaDevAttrGlobalMemoryBusWidth, dev);
        if (khz > 0 && bits > 0) scale = (uint32_t)(64.0 * khz * bits / (2619000.0 * 5120.0) + 0.5);
        cudaFuncSetAttribute(fused_decode_kernel<false>, cudaFuncAttributeMaxDynamicSharedMemorySize, SM_TOTAL);
        cudaFuncSetAttribute(fused_decode_kernel<true>, cudaFuncAttributeMaxDynamicSharedMemorySize, SM_TOTAL);
        cudaGetSymbolAddress(reinterpret_cast<void**>(&scr), g_scratch);
    }
    typedef const __nv_bfloat16* P;
    if (scale == 64)
        fused_decode_kernel<false><<<NCTA, NTHREADS, SM_TOTAL>>>((P)d_in[3], (P)d_in[1], (P)d_in[0], scr, (P)d_in[2], (P)d_in[4], (P)d_in[6],
                                                                 (P)d_in[7], (P)d_in[8], (__nv_bfloat16*)d_out, Clock<false>{scale});
    else
        fused_decode_kernel<true><<<NCTA, NTHREADS, SM_TOTAL>>>((P)d_in[3], (P)d_in[1], (P)d_in[0], scr, (P)d_in[2], (P)d_in[4], (P)d_in[6],
                                                                (P)d_in[7], (P)d_in[8], (__nv_bfloat16*)d_out, Clock<true>{scale});
}
```

```cpp
#include <cuda_runtime.h>
#include <cuda_bf16.h>
#include <stdint.h>

namespace {

constexpr int PACE_DT = 640;
constexpr int PACE_LEAD = 350;
constexpr int LATE_T = 22330;
constexpr int LATE_DT = 460;
constexpr int Q_T = 4000;
constexpr int E2_T = 24030;
constexpr int E3_T = 24800;
constexpr int M_NOM0 = 4595;
constexpr int M_NOM1 = 8450;
constexpr int M_NOM2 = 12800;
constexpr int M_NOM3 = 17010;
constexpr int DEAD = 100;
constexpr int NM = 4;
constexpr int MEND = 5;
constexpr int MGAP = 3;
constexpr int NSLOT = 11;

constexpr int D_MODEL = 448;
constexpr int SK      = 32768;
constexpr int WIN     = 4096;
constexpr int DH      = 256;
constexpr int QCOLS   = 4096;
constexpr int FF      = 1792;
constexpr int NCTA    = 128;
constexpr int NFFN    = 112;
constexpr int NRED    = 56;
constexpr int NPT     = 128;
constexpr int NTHREADS = 512;

constexpr int NS     = NSLOT;
constexpr int SLOT   = 16384;
constexpr int XROW   = 912;
constexpr int S_K = 0, S_V = 16, NSTAGE = 32;
constexpr int S_GU   = NS;
constexpr int FFN_ST = 8;
constexpr int HID_ST = 11;
constexpr int PRE_ST = 12;
constexpr int NBAR   = 36;
constexpr int B_X = NSTAGE;

constexpr int SM_RING  = 0;
constexpr int SM_STRIP = SM_RING + NS * SLOT;
constexpr int SM_S    = SM_STRIP + 448 * 64;
constexpr int SM_P    = SM_S + 2 * 520 * 4;
constexpr int SM_Q    = SM_P + 2 * 272 * 4;
constexpr int SM_XN   = SM_Q + 2 * 264 * 2;
constexpr int SM_X    = SM_XN + 2 * XROW;
constexpr int SM_RED  = SM_X + 1792 + 32;
constexpr int SM_STAT = SM_RED + 7 * 64 * 4;
constexpr int SM_OB   = SM_STAT + 2 * 8 * 2 * 4;
constexpr int SM_H    = SM_OB + 2 * 16 * 4;
constexpr int SM_T0   = SM_H + 2 * 8 * 4;
constexpr int SM_BAR  = SM_T0 + 16;
constexpr int SM_TOTAL = SM_BAR + 2 * NBAR * 8;
static_assert(SM_Q % 16 == 0 && SM_XN % 16 == 0 && SM_X % 16 == 0 && SM_OB % 16 == 0 && SM_P % 16 == 0 && SM_T0 % 16 == 0, "align");
static_assert(S_GU + 13 <= S_V + FFN_ST, "the gate/up strip lands with stage S_GU + 13");
static_assert(2 * NS >= 16, "K stage -> slot mapping");

constexpr int SPIN_LIMIT = 1 << 22;
constexpr float SCALE_LOG2E = 0.0625f * 1.4426950408889634f;

struct __align__(1024) Scratch {
    uint4    part[NCTA * 2 * 8 * 8];
    uint4    outp[NRED * NCTA * 4];
    uint4    q[8 * 2 * 128];
    unsigned gu[NCTA * 32];
    uint2    ml[NCTA * 4];
    uint2    prog[4 * 32 * 4];
    unsigned epoch[NCTA * 8];
};
__device__ Scratch g_scratch;

__device__ __forceinline__ void mbar_init(uint32_t bar, uint32_t cnt) {
    asm volatile("mbarrier.init.shared::cta.b64 [%0], %1;" :: "r"(bar), "r"(cnt) : "memory");
}
__device__ __forceinline__ void mbar_arrive(uint32_t bar, uint32_t cnt) {
    asm volatile("mbarrier.arrive.shared::cta.b64 _, [%0], %1;" :: "r"(bar), "r"(cnt) : "memory");
}
template <bool SCALED>
struct Clock {
    uint32_t scale;
    __device__ __forceinline__ uint32_t now() const {
        if constexpr (SCALED) {
            uint64_t t;
            asm volatile("mov.u64 %0, %globaltimer;" : "=l"(t));
            return (uint32_t)((t * scale) >> 6);
        } else {
            uint32_t t;
            asm volatile("mov.u32 %0, %globaltimer_lo;" : "=r"(t));
            return t;
        }
    }
    __device__ __forceinline__ static uint32_t base(uint32_t sb, int i) {
        uint32_t t;
        asm volatile("ld.volatile.shared.u32 %0, [%1];" : "=r"(t) : "r"(sb + SM_T0 + 4 * i) : "memory");
        return t;
    }
    __device__ __forceinline__ void wait_until(uint32_t t0, uint32_t dt) const { while (now() - t0 < dt) {} }
    __device__ __forceinline__ void wait_base(uint32_t sb, int i, uint32_t dt) const { while (now() - base(sb, i) < dt) {} }
};
__device__ __forceinline__ void mbar_wait(uint32_t bar) {
    asm volatile("{\n.reg .pred p;\nWAIT_LOOP:\nmbarrier.try_wait.parity.shared::cta.b64 p, [%0], 0;\n@!p bra WAIT_LOOP;\n}" :: "r"(bar) : "memory");
}
__device__ __forceinline__ void cp_async16_strip(uint32_t dst, const void* src) {
    asm volatile("cp.async.cg.shared.global.L2::128B [%0], [%1], 16;" :: "r"(dst), "l"(src) : "memory");
}
__device__ __forceinline__ void cp_async16_stream(uint32_t dst, const void* src) {
    asm volatile("{\n.reg .b64 pol;\ncreatepolicy.fractional.L2::evict_first.b64 pol, 1.0;\n"
                 "cp.async.cg.shared.global.L2::cache_hint [%0], [%1], 16, pol;\n}" :: "r"(dst), "l"(src) : "memory");
}
__device__ __forceinline__ void cp_async_arrive(uint32_t bar) {
    asm volatile("cp.async.mbarrier.arrive.noinc.shared::cta.b64 [%0];" :: "r"(bar) : "memory");
}
__device__ __forceinline__ void bar_sync(int id, int n)   { asm volatile("bar.sync %0, %1;" :: "r"(id), "r"(n) : "memory"); }
__device__ __forceinline__ void bar_arrive(int id, int n) { asm volatile("bar.arrive %0, %1;" :: "r"(id), "r"(n) : "memory"); }

__device__ __forceinline__ uint32_t ld_poll1(const void* p) {
    uint32_t v;
    asm volatile("ld.relaxed.gpu.global.u32 %0, [%1];" : "=r"(v) : "l"(p) : "memory");
    return v;
}
__device__ __forceinline__ uint2 ld_poll2(const void* p) {
    uint2 v;
    asm volatile("ld.relaxed.gpu.global.v2.u32 {%0,%1}, [%2];" : "=r"(v.x), "=r"(v.y) : "l"(p) : "memory");
    return v;
}
__device__ __forceinline__ uint4 ld_poll4(const void* p) {
    uint4 v;
    asm volatile("ld.relaxed.gpu.global.v4.u32 {%0,%1,%2,%3}, [%4];" : "=r"(v.x), "=r"(v.y), "=r"(v.z), "=r"(v.w) : "l"(p) : "memory");
    return v;
}
__device__ __forceinline__ void st_pub64(void* p, uint32_t a, uint32_t b) {
    asm volatile("{\n.reg .b64 d;\nmov.b64 d, {%1,%2};\nst.relaxed.gpu.global.b64 [%0], d;\n}" :: "l"(p), "r"(a), "r"(b) : "memory");
}
__device__ __forceinline__ void st_pub2x64(void* p, uint32_t a, uint32_t b, uint32_t c, uint32_t d) {
    asm volatile("{\n.reg .b64 d, e;\nmov.b64 d, {%1,%2};\nmov.b64 e, {%3,%4};\nst.relaxed.gpu.global.v2.b64 [%0], {d,e};\n}"
                 :: "l"(p), "r"(a), "r"(b), "r"(c), "r"(d) : "memory");
}
__device__ __forceinline__ void st_pub2(void* p, uint32_t a, uint32_t b) {
    asm volatile("st.relaxed.gpu.global.v2.u32 [%0], {%1,%2};" :: "l"(p), "r"(a), "r"(b) : "memory");
}
__device__ __forceinline__ void st_pub1(void* p, uint32_t a) {
    asm volatile("st.relaxed.gpu.global.u32 [%0], %1;" :: "l"(p), "r"(a) : "memory");
}
__device__ __forceinline__ uint32_t tagf(float v, uint32_t tag) {
    uint32_t r;
    asm("lop3.b32 %0, %1, 0xfffffffe, %2, 0xEA;" : "=r"(r) : "r"(__float_as_uint(v)), "r"(tag));
    return r;
}
__device__ __forceinline__ uint32_t pin(uint32_t v) {
    uint32_t r;
    asm volatile("shfl.sync.bfly.b32 %0, %1, 0, 0x1f, 0xffffffff;" : "=r"(r) : "r"(v));
    return r;
}
template <class T>
__device__ __forceinline__ T* pin(T* p) {
    const uint64_t u = reinterpret_cast<uint64_t>(p);
    return reinterpret_cast<T*>(((uint64_t)pin((uint32_t)(u >> 32)) << 32) | pin((uint32_t)u));
}
__device__ __forceinline__ void sts32(uint32_t addr, uint32_t v) { asm volatile("st.shared.u32 [%0], %1;" :: "r"(addr), "r"(v) : "memory"); }
__device__ __forceinline__ float lds32(uint32_t addr) { float v; asm volatile("ld.shared.f32 %0, [%1];" : "=f"(v) : "r"(addr) : "memory"); return v; }
__device__ __forceinline__ uint4 lds128(uint32_t addr) {
    uint4 v;
    asm volatile("ld.shared.v4.u32 {%0,%1,%2,%3}, [%4];" : "=r"(v.x), "=r"(v.y), "=r"(v.z), "=r"(v.w) : "r"(addr) : "memory");
    return v;
}
__device__ __forceinline__ uint32_t bad2(uint32_t a, uint32_t b, uint32_t tag) {
    uint32_t r;
    asm("lop3.b32 %0, %1, %2, %3, 0x7E;" : "=r"(r) : "r"(a), "r"(b), "r"(tag));
    return r;
}
__device__ __forceinline__ uint32_t bad4(const uint4& v, uint32_t tag) { return bad2(v.x, v.y, tag) | bad2(v.z, v.w, tag); }
__device__ __forceinline__ bool warp_bad(uint32_t bad) { return __any_sync(0xffffffffu, bad & 1u); }

#define POLL_HEAD(P, T, N)                                                                                        \
    ".reg .pred p0, p1, p2, p3, q;\n"                                                                             \
    ".reg .b32 a, m, it, y<16>;\n"                                                                                \
    ".reg .b64 d<8>;\n"                                                                                           \
    "setp.eq.u32 p0, 0, 0;\nsetp.eq.u32 p1, 0, 0;\nsetp.eq.u32 p2, 0, 0;\nsetp.eq.u32 p3, 0, 0;\n"                \
    "mov.u32 it, " N ";\n"                                                                                        \
    "POLL_LOOP:\n"                                                                                                \
    "@p0 ld.relaxed.gpu.global.v2.b64 {d0,d1}, [" P "];\n"                                                        \
    "@p1 ld.relaxed.gpu.global.v2.b64 {d2,d3}, [" P "+512];\n"                                                    \
    "@p2 ld.relaxed.gpu.global.v2.b64 {d4,d5}, [" P "+1024];\n"                                                   \
    "@p3 ld.relaxed.gpu.global.v2.b64 {d6,d7}, [" P "+1536];\n"                                                   \
    "sub.u32 it, it, 1;\n"                                                                                        \
    "min.u32 m, it, 1;\n"                                                        \
    "mov.b64 {y0,y1}, d0;\nmov.b64 {y2,y3}, d1;\nmov.b64 {y4,y5}, d2;\nmov.b64 {y6,y7}, d3;\n"                    \
    "mov.b64 {y8,y9}, d4;\nmov.b64 {y10,y11}, d5;\nmov.b64 {y12,y13}, d6;\nmov.b64 {y14,y15}, d7;\n"              \
    "xor.b32 y0, y0, " T ";\nxor.b32 y2, y2, " T ";\nlop3.b32 a, y0, y2, m, 0xA8;\nsetp.ne.u32 p0, a, 0;\n"       \
    "xor.b32 y4, y4, " T ";\nxor.b32 y6, y6, " T ";\nlop3.b32 a, y4, y6, m, 0xA8;\nsetp.ne.u32 p1, a, 0;\n"       \
    "xor.b32 y8, y8, " T ";\nxor.b32 y10, y10, " T ";\nlop3.b32 a, y8, y10, m, 0xA8;\nsetp.ne.u32 p2, a, 0;\n"    \
    "xor.b32 y12, y12, " T ";\nxor.b32 y14, y14, " T ";\nlop3.b32 a, y12, y14, m, 0xA8;\nsetp.ne.u32 p3, a, 0;\n" \
    "or.pred q, p0, p1;\nor.pred q, q, p2;\nor.pred q, q, p3;\nvote.sync.any.pred q, q, 0xffffffff;\n"
#define POLL_TAIL "@q bra POLL_LOOP;\n"

__device__ __forceinline__ void poll4(float (&f)[2][4], const uint4* p, uint32_t tag, const float (&w)[4]) {
    asm volatile("{\n" POLL_HEAD("%8", "%9", "%14") POLL_TAIL
                 "mul.f32 %0, y0, %10;\nmul.f32 %1, y1, %10;\nmul.f32 %2, y2, %10;\nmul.f32 %3, y3, %10;\n"
                 "mul.f32 %4, y8, %12;\nmul.f32 %5, y9, %12;\nmul.f32 %6, y10, %12;\nmul.f32 %7, y11, %12;\n"
                 "fma.rn.f32 %0, y4, %11, %0;\nfma.rn.f32 %1, y5, %11, %1;\nfma.rn.f32 %2, y6, %11, %2;\nfma.rn.f32 %3, y7, %11, %3;\n"
                 "fma.rn.f32 %4, y12, %13, %4;\nfma.rn.f32 %5, y13, %13, %5;\nfma.rn.f32 %6, y14, %13, %6;\nfma.rn.f32 %7, y15, %13, %7;\n"
                 "}"
                 : "=&f"(f[0][0]), "=&f"(f[0][1]), "=&f"(f[0][2]), "=&f"(f[0][3]), "=&f"(f[1][0]), "=&f"(f[1][1]), "=&f"(f[1][2]), "=&f"(f[1][3])
                 : "l"(p), "r"(tag), "f"(w[0]), "f"(w[1]), "f"(w[2]), "f"(w[3]), "n"(SPIN_LIMIT) : "memory");
}
__device__ __forceinline__ void poll4_sum(float (&keep)[2], float (&recv)[2], const uint4* p, uint32_t tag, uint32_t hi) {
    asm volatile("{\n.reg .pred h;\n.reg .f32 s<8>;\nsetp.ne.u32 h, %6, 0;\n" POLL_HEAD("%4", "%5", "%7")
                 "add.f32 s0, y0, y4;\nadd.f32 s1, y1, y5;\nadd.f32 s2, y2, y6;\nadd.f32 s3, y3, y7;\n"
                 "add.f32 s4, y8, y12;\nadd.f32 s5, y9, y13;\nadd.f32 s6, y10, y14;\nadd.f32 s7, y11, y15;\n"
                 "add.f32 s0, s0, s4;\nadd.f32 s1, s1, s5;\nadd.f32 s2, s2, s6;\nadd.f32 s3, s3, s7;\n"
                 "selp.f32 s4, s0, s2, h;\nselp.f32 s5, s1, s3, h;\nselp.f32 %0, s2, s0, h;\nselp.f32 %1, s3, s1, h;\n"
                 "shfl.sync.bfly.b32 %2, s4, 16, 0x1f, 0xffffffff;\nshfl.sync.bfly.b32 %3, s5, 16, 0x1f, 0xffffffff;\n"
                 POLL_TAIL "}"
                 : "=&f"(keep[0]), "=&f"(keep[1]), "=&f"(recv[0]), "=&f"(recv[1])
                 : "l"(p), "r"(tag), "r"(hi), "n"(SPIN_LIMIT) : "memory");
}

__device__ __forceinline__ void ldsm4(uint32_t addr, uint32_t (&a)[4]) {
    asm volatile("ldmatrix.sync.aligned.m8n8.x4.shared.b16 {%0,%1,%2,%3}, [%4];" : "=r"(a[0]), "=r"(a[1]), "=r"(a[2]), "=r"(a[3]) : "r"(addr) : "memory");
}
__device__ __forceinline__ void ldsm4t(uint32_t addr, uint32_t (&a)[4]) {
    asm volatile("ldmatrix.sync.aligned.m8n8.x4.trans.shared.b16 {%0,%1,%2,%3}, [%4];" : "=r"(a[0]), "=r"(a[1]), "=r"(a[2]), "=r"(a[3]) : "r"(addr) : "memory");
}
__device__ __forceinline__ void mma16816(float (&c)[4], const uint32_t (&a)[4], uint32_t b0, uint32_t b1) {
    asm volatile("mma.sync.aligned.m16n8k16.row.col.f32.bf16.bf16.f32 {%0,%1,%2,%3}, {%4,%5,%6,%7}, {%8,%9}, {%0,%1,%2,%3};"
                 : "+f"(c[0]), "+f"(c[1]), "+f"(c[2]), "+f"(c[3]) : "r"(a[0]), "r"(a[1]), "r"(a[2]), "r"(a[3]), "r"(b0), "r"(b1));
}
__device__ __forceinline__ float bf_lo(uint32_t u) { return __uint_as_float(u << 16); }
__device__ __forceinline__ float bf_hi(uint32_t u) { return __uint_as_float(u & 0xffff0000u); }
__device__ __forceinline__ float rbf(float v) { return __bfloat162float(__float2bfloat16_rn(v)); }
__device__ __forceinline__ uint32_t pack_bf(float lo, float hi) {
    uint32_t r;
    asm("cvt.rn.bf16x2.f32 %0, %1, %2;" : "=r"(r) : "f"(hi), "f"(lo));
    return r;
}
__device__ __forceinline__ float sel4(const float (&c)[4], int t) {
    float a = (t & 1) ? c[1] : c[0];
    float b = (t & 1) ? c[3] : c[2];
    return (t & 2) ? b : a;
}
__device__ __forceinline__ float ex2(float x) { float y; asm("ex2.approx.ftz.f32 %0, %1;" : "=f"(y) : "f"(x)); return y; }
__device__ __forceinline__ float sqrt_approx(float x) { float y; asm("sqrt.approx.f32 %0, %1;" : "=f"(y) : "f"(x)); return y; }

__host__ __device__ constexpr uint32_t slot_of(int s) { return SM_RING + (s % NS) * SLOT; }

__device__ __forceinline__ void layernorm(unsigned char* smem, int lane) {
    uint32_t xs[2][7];
#pragma unroll
    for (int b = 0; b < 2; b++)
#pragma unroll
        for (int i = 0; i < 7; i++) xs[b][i] = reinterpret_cast<const uint32_t*>(smem + SM_X)[b * (D_MODEL / 2) + i * 32 + lane];
#pragma unroll
    for (int b = 0; b < 2; b++) {
        float sum = 0.f;
#pragma unroll
        for (int i = 0; i < 7; i++) sum += bf_lo(xs[b][i]) + bf_hi(xs[b][i]);
#pragma unroll
        for (int o = 16; o > 0; o >>= 1) sum += __shfl_xor_sync(0xffffffffu, sum, o);
        const float mean = sum * (1.0f / D_MODEL);
        float sq = 0.f;
#pragma unroll
        for (int i = 0; i < 7; i++) {
            const float d0 = bf_lo(xs[b][i]) - mean, d1 = bf_hi(xs[b][i]) - mean;
            sq = fmaf(d0, d0, fmaf(d1, d1, sq));
        }
#pragma unroll
        for (int o = 16; o > 0; o >>= 1) sq += __shfl_xor_sync(0xffffffffu, sq, o);
        const float mb = rbf(mean);
        const float sd = rbf(sqrt_approx(rbf(rbf(sq * (1.0f / D_MODEL)) + 1e-5f)));
#pragma unroll
        for (int i = 0; i < 7; i++)
            reinterpret_cast<uint32_t*>(smem + SM_XN + b * XROW)[i * 32 + lane] =
                pack_bf(__fdividef(rbf(bf_lo(xs[b][i]) - mb), sd), __fdividef(rbf(bf_hi(xs[b][i]) - mb), sd));
    }
}

__device__ __forceinline__ void strip_partial(uint32_t sb, uint32_t strip, unsigned char* smem, int warp, int lane) {
    float c[2][2][4];
#pragma unroll
    for (int n = 0; n < 2; n++)
#pragma unroll
        for (int e = 0; e < 4; e++) c[n][0][e] = c[n][1][e] = 0.f;
    const uint32_t ba = sb + SM_XN + (lane & 1) * XROW + (lane >> 3) * 16 + warp * 128;
    const uint32_t aa = sb + strip + (warp * 64 + (lane & 7) + (lane >> 4) * 8) * 64 + (((lane >> 3) & 1) ^ ((lane & 7) >> 1)) * 16;
#pragma unroll
    for (int k2 = 0; k2 < 2; k2++) {
        uint32_t b[4];
        ldsm4(ba + k2 * 64, b);
#pragma unroll
        for (int n = 0; n < 2; n++) {
            uint32_t a0[4], a1[4];
            ldsm4t((aa ^ (n * 32)) + k2 * 2048, a0);
            ldsm4t((aa ^ (n * 32)) + k2 * 2048 + 1024, a1);
            mma16816(c[n][0], a0, b[0], b[1]);
            mma16816(c[n][1], a1, b[2], b[3]);
        }
    }
    float* red = reinterpret_cast<float*>(smem + SM_RED) + warp * 64 + lane;
#pragma unroll
    for (int n = 0; n < 2; n++) red[n * 32] = sel4(c[n][0], lane & 3) + sel4(c[n][1], lane & 3);
}
__device__ __forceinline__ float strip_sum(const unsigned char* smem, int idx) {
    const float* red = reinterpret_cast<const float*>(smem + SM_RED) + idx;
    return ((red[0] + red[64]) + (red[128] + red[192])) + ((red[256] + red[320]) + red[384]);
}

struct Prod {
    uint32_t sb, kvdst, sdst;
    const char *k, *v;
    const __nv_bfloat16* gu;
    bool ffn;
};
__host__ __device__ constexpr int bytes_before(int s) { return 28672 + s * 16384 + (s <= S_GU ? 0 : s < S_GU + 14 ? s - S_GU : 14) * 1792; }
__host__ __device__ constexpr int issue_time(int s) {
    return (int)((long long)bytes_before(s) * PACE_DT / 16384) - PACE_LEAD;
}

template <int S, class CLK>
__device__ __forceinline__ void produce(Prod& p, const CLK& clk) {
    if constexpr (S < NSTAGE) {
        if constexpr (S >= NS) mbar_wait(p.sb + SM_BAR + (NBAR + S - NS) * 8);
        clk.wait_base(p.sb, 0, issue_time(S));
        const char* src = (S < S_V ? p.k : p.v) + (S & 15) * (8 * SLOT);
#pragma unroll
        for (int i = 0; i < 8; i++) cp_async16_stream((p.kvdst ^ ((i & 1) * 64)) + slot_of(S) + i * 2048, src + i * 2048);
        if constexpr (S >= S_GU && S < S_GU + 14) {
            if (p.ffn) cp_async16_strip(p.sdst + (S - S_GU) * 2048, p.gu + (size_t)(S - S_GU) * 32 * FF);
        }
        cp_async_arrive(p.sb + SM_BAR + S * 8);
        produce<S + 1>(p, clk);
    }
}

__device__ __forceinline__ void fetch16(uint32_t dst, const char* src) {
#pragma unroll
    for (int i = 0; i < 4; i++)
        asm volatile("cp.async.cg.shared.global [%0], [%1], 16;" :: "r"((dst ^ (((i & 1) ^ (i >> 1)) * 64)) + i * 512), "l"(src + i * (4 * 896)) : "memory");
}
template <int PENDING, int OFF>
__device__ __forceinline__ void frag16(uint32_t (&a)[4][4], uint32_t addr) {
    asm volatile("cp.async.wait_group %0;" :: "n"(PENDING) : "memory");
    __syncwarp();
#pragma unroll
    for (int m = 0; m < 4; m++) ldsm4t((addr ^ (m * 32)) + OFF, a[m]);
}

__device__ __forceinline__ void load_x(uint32_t sb, const void* x, const void* epoch) {
    const uint32_t full0 = sb + SM_BAR;
    mbar_init(full0 + B_X * 8, 1);
    asm volatile("fence.mbarrier_init.release.cluster;" ::: "memory");
    asm volatile("mbarrier.arrive.expect_tx.shared::cta.b64 _, [%0], %1;" :: "r"(full0 + B_X * 8), "r"(1792 + 16) : "memory");
    asm volatile("cp.async.bulk.shared::cluster.global.mbarrier::complete_tx::bytes [%0], [%1], %2, [%3];"
                 :: "r"(sb + SM_X), "l"(x), "r"(1792), "r"(full0 + B_X * 8) : "memory");
    asm volatile("cp.async.bulk.shared::cluster.global.mbarrier::complete_tx::bytes [%0], [%1], %2, [%3];"
                 :: "r"(sb + SM_X + 1792), "l"(epoch), "r"(16), "r"(full0 + B_X * 8) : "memory");
}

enum { BAR_OB = 1, BAR_CONS = 2, BAR_LN = 3, BAR_FF = 4, BAR_FIN = 5, BAR_H = 6 };

template <bool SCALED>
__global__ void __launch_bounds__(NTHREADS, 1)
fused_decode_kernel(const __nv_bfloat16* __restrict__ wq, const __nv_bfloat16* __restrict__ kc, const __nv_bfloat16* __restrict__ x,
                    Scratch* __restrict__ scr, const __nv_bfloat16* __restrict__ vc, const __nv_bfloat16* __restrict__ wo,
                    const __nv_bfloat16* __restrict__ wg, const __nv_bfloat16* __restrict__ wu, const __nv_bfloat16* __restrict__ wd,
                    __nv_bfloat16* __restrict__ out, const Clock<SCALED> clk) {
    extern __shared__ __align__(128) unsigned char smem[];
    const uint32_t sb = (uint32_t)__cvta_generic_to_shared(smem);
    const int tid = threadIdx.x, lane = tid & 31;
    const int cta = blockIdx.x;
    const uint32_t full0 = sb + SM_BAR, done0 = full0 + NBAR * 8;
    const uint32_t t0 = clk.now();
    if (tid < 224) {
        const int row = (tid >> 5) * 64 + (lane >> 2);
        const char* src = reinterpret_cast<const char*>(wq) + (uint32_t)(row * (QCOLS * 2) + cta * 64 + (lane & 3) * 16);
        const uint32_t dst = sb + SM_STRIP + row * 64 + ((lane & 3) ^ (lane >> 3)) * 16;
#pragma unroll
        for (int i = 0; i < 8; i++) cp_async16_strip(dst + i * 512, src + i * (8 * QCOLS * 2));
    }
    const int warp = __shfl_sync(0xffffffffu, tid >> 5, 0);
    const int hkv = cta >> 4, j = cta & 15, bat = j >> 3, sp = j & 7;
    const int g = lane >> 2, t = lane & 3;

    if (warp < 8) {
        if (tid == 224) load_x(sb, x, &scr->epoch[cta * 8]);
        __syncthreads();
        mbar_wait(full0 + B_X * 8);
        const uint32_t epoch = *reinterpret_cast<const uint32_t*>(smem + SM_X + 1792);
        const uint32_t tag = pin((epoch + 1) & 1);
        uint32_t* qdst = reinterpret_cast<uint32_t*>(scr->q) + (hkv * 2 + (t & 1)) * 512 + j * 32 + warp * 16 + g + 8 * (t >> 1);
        if (warp == 7) {
            layernorm(smem, lane);
            bar_arrive(BAR_LN, 256);
        } else {
            asm volatile("cp.async.wait_all;" ::: "memory");
            bar_sync(BAR_LN, 256);
            strip_partial(sb, SM_STRIP, smem, warp, lane);
        }
        bar_sync(BAR_CONS, 256);
        if (warp < 2) {
            st_pub1(qdst, (pack_bf(0.f, strip_sum(smem, tid)) & 0xffff0000u) | tag);
        } else if (warp >= 4) {
            const int i = tid - 128;
            const uint4* qp = scr->q + (hkv * 2 + bat) * 128 + i;
            clk.wait_until(t0, Q_T);
            uint4 v;
            int it = 0;
            do {
                v = ld_poll4(qp);
                if (++it > SPIN_LIMIT) __trap();
            } while (warp_bad(bad4(v, tag)));
            *reinterpret_cast<uint2*>(smem + SM_Q + (i >> 6) * 528 + (i & 63) * 8) =
                make_uint2(__byte_perm(v.x, v.y, 0x7632), __byte_perm(v.z, v.w, 0x7632));
        }
        bar_sync(BAR_CONS, 256);
        if (tid == 96) scr->epoch[cta * 8] = epoch + 1;
        {
            uint32_t qf[8][4];
#pragma unroll
            for (int k2 = 0; k2 < 8; k2++) ldsm4(sb + SM_Q + (lane & 1) * 528 + k2 * 64 + (lane >> 3) * 16, qf[k2]);
            const int mt = warp & 1;
            const uint32_t aoff = (16 * mt + (lane & 15)) * 512 + ((lane >> 4) ^ (lane & 7)) * 16;
            float* sc = reinterpret_cast<float*>(smem + SM_S) + (t & 1) * 520 + (g >> 1) * 8 + (2 * mt + (t >> 1)) * 2 + (g & 1);
#pragma unroll 1
            for (int k = warp >> 1; k < 16; k += 4) {
                const int s = S_K + k;
                mbar_wait(full0 + s * 8);
                const uint32_t base = sb + SM_RING + (s >= NS ? s - NS : s) * SLOT + aoff;
                float c0[4] = {0.f, 0.f, 0.f, 0.f}, c1[4] = {0.f, 0.f, 0.f, 0.f};
#pragma unroll
                for (int k2 = 0; k2 < 8; k2++) {
                    uint32_t a0[4], a1[4];
                    ldsm4((base ^ ((k2 & 1) * 64)) + (k2 >> 1) * 128, a0);
                    ldsm4((base ^ ((k2 & 1) * 64 + 32)) + (k2 >> 1) * 128, a1);
                    mma16816(c0, a0, qf[k2][0], qf[k2][1]);
                    mma16816(c1, a1, qf[k2][2], qf[k2][3]);
                }
                __syncwarp();
                if (lane == 0) mbar_arrive(done0 + s * 8, 4);
                sc[k * 32] = rbf(sel4(c0, t) + sel4(c1, t));
            }
        }
        bar_sync(BAR_CONS, 256);
        {
            constexpr float C = SCALE_LOG2E;
            const float* sc = reinterpret_cast<const float*>(smem + SM_S);
            float* stat = reinterpret_cast<float*>(smem + SM_STAT);
            const float2 s0 = *reinterpret_cast<const float2*>(sc + 2 * tid);
            const float2 s1 = *reinterpret_cast<const float2*>(sc + 520 + 2 * tid);
            float m0 = fmaxf(s0.x, s0.y), m1 = fmaxf(s1.x, s1.y);
#pragma unroll
            for (int o = 16; o > 0; o >>= 1) {
                m0 = fmaxf(m0, __shfl_xor_sync(0xffffffffu, m0, o));
                m1 = fmaxf(m1, __shfl_xor_sync(0xffffffffu, m1, o));
            }
            if (lane == 0) *reinterpret_cast<float2*>(stat + warp * 2) = make_float2(m0, m1);
            bar_sync(BAR_CONS, 256);
#pragma unroll
            for (int w = 0; w < 8; w++) {
                const float2 mm = *reinterpret_cast<const float2*>(stat + w * 2);
                m0 = fmaxf(m0, mm.x); m1 = fmaxf(m1, mm.y);
            }
            const float p00 = ex2((s0.x - m0) * C), p01 = ex2((s0.y - m0) * C);
            const float p10 = ex2((s1.x - m1) * C), p11 = ex2((s1.y - m1) * C);
            uint32_t* ps = reinterpret_cast<uint32_t*>(smem + SM_P);
            ps[tid] = pack_bf(p00, p01);
            ps[272 + tid] = pack_bf(p10, p11);
            float l0 = p00 + p01, l1 = p10 + p11;
#pragma unroll
            for (int o = 16; o > 0; o >>= 1) {
                l0 += __shfl_xor_sync(0xffffffffu, l0, o);
                l1 += __shfl_xor_sync(0xffffffffu, l1, o);
            }
            if (lane == 0) *reinterpret_cast<float2*>(stat + 16 + warp * 2) = make_float2(l0, l1);
            bar_sync(BAR_CONS, 256);
            if (tid < 4) {
                float l = 0.f;
#pragma unroll
                for (int w = 0; w < 8; w++) l += stat[16 + w * 2 + (tid & 1)];
                st_pub2(scr->ml + cta * 4 + tid, tagf((tid & 1) ? m1 : m0, tag), tagf(l, tag));
            }
        }
        float wgt[2] = {0.f, 0.f}, own = 0.f;
        {
            float o0[4] = {0.f, 0.f, 0.f, 0.f}, o1[4] = {0.f, 0.f, 0.f, 0.f};
            float o2[4] = {0.f, 0.f, 0.f, 0.f}, o3[4] = {0.f, 0.f, 0.f, 0.f};
            const uint32_t aoff = ((lane & 7) + (lane >> 4) * 8) * 512 + ((warp * 4 + ((lane >> 3) & 1) * 2) ^ (lane & 7)) * 16;
            const uint4* ps = reinterpret_cast<const uint4*>(smem + SM_P + (g & 1) * 272 * 4) + t;
            uint32_t* dst = reinterpret_cast<uint32_t*>(scr->part) + ((size_t)(hkv * 16 + (t & 1) * 8 + warp) * 16 + j) * 32 +
                            (4 * (g & 3) + (t & 2) + (g >> 2)) * 2;
#pragma unroll
            for (int k = 0; k < 16; k++) {
                const uint4 pa = ps[k * 4];
                mbar_wait(full0 + (S_V + k) * 8);
                uint32_t a[4][4];
#pragma unroll
                for (int i = 0; i < 4; i++) ldsm4t(sb + (aoff ^ ((i & 1) * 16)) + slot_of(S_V + k) + (i >> 1) * 8192, a[i]);
                mma16816(o0, a[0], pa.x, pa.y);
                mma16816(o1, a[1], pa.x, pa.y);
                mma16816(o2, a[2], pa.z, pa.w);
                mma16816(o3, a[3], pa.z, pa.w);
                if (S_V + k + NS < NSTAGE + 3) {
                    __syncwarp();
                    if (lane == 0) mbar_arrive(done0 + (S_V + k) * 8, 1);
                }
                if (k == FFN_ST && warp < 7) {
                    strip_partial(sb, SM_STRIP, smem, warp, lane);
                    bar_arrive(BAR_FF, 256);
                }
                if (k == FFN_ST && warp == 7) {
                    bar_sync(BAR_FF, 256);
                    own = rbf(strip_sum(smem, (cta & 1) * 32 + lane));
                    st_pub1(scr->gu + (cta ^ 1) * 32 + lane, (pack_bf(0.f, strip_sum(smem, (~cta & 1) * 32 + lane)) & 0xffff0000u) | tag);
                }
                if (k == HID_ST && warp == 7) {
                    const uint2* mlp = scr->ml + (hkv * 16 + g) * 4 + (j >> 3);
                    uint2 a, b;
                    uint32_t other;
                    int it = 0;
                    do {
                        a = ld_poll2(mlp); b = ld_poll2(mlp + 32); other = ld_poll1(scr->gu + cta * 32 + lane);
                        if (++it > SPIN_LIMIT) __trap();
                    } while (warp_bad(bad2(a.x, a.y, tag) | bad2(b.x, b.y, tag) | (other ^ tag)));
                    float m[2] = {bf_hi(a.x), bf_hi(b.x)};
                    float l[2] = {__uint_as_float(a.y ^ tag), __uint_as_float(b.y ^ tag)};
#pragma unroll
                    for (int bb = 0; bb < 2; bb++) {
                        float M = m[bb];
                        M = fmaxf(M, __shfl_xor_sync(0xffffffffu, M, 4));
                        M = fmaxf(M, __shfl_xor_sync(0xffffffffu, M, 8));
                        M = fmaxf(M, __shfl_xor_sync(0xffffffffu, M, 16));
                        const float e = ex2((m[bb] - M) * SCALE_LOG2E);
                        float L = e * l[bb];
                        L += __shfl_xor_sync(0xffffffffu, L, 4);
                        L += __shfl_xor_sync(0xffffffffu, L, 8);
                        L += __shfl_xor_sync(0xffffffffu, L, 16);
                        wgt[bb] = __fdividef(e, L);
                    }
                    float ga = (cta & 1) ? bf_hi(other) : own;
                    ga *= (ga > 0.f ? 1.f : 0.f);
                    const float hv = ga * ((cta & 1) ? own : bf_hi(other));
                    const uint32_t w = pack_bf(hv, __shfl_xor_sync(0xffffffffu, hv, 2));
                    if (!(t & 2)) reinterpret_cast<uint32_t*>(smem + SM_H)[(t & 1) * 8 + (g & 3) * 2 + (g >> 2)] = w;
                    bar_arrive(BAR_H, 256);
                }
                if (k == PRE_ST) st_pub64(dst, tag ^ 1, 0);
            }
            const float v0 = sel4(o0, t) + sel4(o2, t), v1 = sel4(o1, t) + sel4(o3, t);
            st_pub64(dst, tagf(v0, tag), __float_as_uint(v1));
        }
        if (warp == 7) {
            const uint4* pp = pin(scr->part + (size_t)cta * 128 + lane);
            const uint32_t obaddr = pin(sb + SM_OB + (lane >> 4) * 64 + (lane & 7) * 8 + ((lane >> 3) & 1) * 4), ll = pin(lane);
            float w[4];
#pragma unroll
            for (int i = 0; i < 4; i++) w[i] = __shfl_sync(0xffffffffu, wgt[i >> 1], ((i & 1) * 4 + (lane >> 3)) * 4);
            clk.wait_until(clk.base(sb, 2), E2_T);
            float f[2][4];
            poll4(f, pp, tag, w);
            const bool h16 = ll & 16, h8 = ll & 8;
            float r4[4], r2[2];
#pragma unroll
            for (int e = 0; e < 4; e++) r4[e] = (h16 ? f[1][e] : f[0][e]) + __shfl_xor_sync(0xffffffffu, h16 ? f[0][e] : f[1][e], 16);
#pragma unroll
            for (int e = 0; e < 2; e++) r2[e] = (h8 ? r4[2 + e] : r4[e]) + __shfl_xor_sync(0xffffffffu, h8 ? r4[e] : r4[2 + e], 8);
            sts32(obaddr, pack_bf(r2[0], r2[1]));
            bar_arrive(BAR_OB, 256);
        } else if (warp < 4 && (cta & 1) == 0 && cta < 2 * NRED) {
            const uint4* op = pin(scr->outp + (size_t)(cta >> 1) * (NCTA * 4) + warp * 128 + lane);
            const int oidx = (t & 1) * D_MODEL + hkv * 64 + (lane >> 3) * 16 + (j >> 1) + (t >> 1) * 8;
            const float xv = __bfloat162float(reinterpret_cast<const __nv_bfloat16*>(smem + SM_X)[oidx]);
            __nv_bfloat16* optr = pin(out + oidx);
            const uint32_t red = pin(sb + SM_S + tid * 4), ll = pin(lane);
            float r2[2], rcv[2];
            const bool h8 = ll & 8;
            clk.wait_until(clk.base(sb, 3), E3_T);
            poll4_sum(r2, rcv, op, tag, ll & 16);
            r2[0] += rcv[0]; r2[1] += rcv[1];
            float r = (h8 ? r2[1] : r2[0]) + __shfl_xor_sync(0xffffffffu, h8 ? r2[0] : r2[1], 8);
            r += __shfl_xor_sync(0xffffffffu, r, 4);
            if (warp != 0) {
                sts32(red, __float_as_uint(r));
                bar_arrive(BAR_FIN, 128);
            } else {
                bar_sync(BAR_FIN, 128);
                r = ((xv + r) + lds32(red + 128)) + (lds32(red + 256) + lds32(red + 384));
                asm volatile("st.global.u16 [%0], %1;" :: "l"(optr), "h"(__bfloat16_as_ushort(__float2bfloat16_rn(r))) : "memory");
            }
        }
    } else if (warp < 15) {
        const int pt = tid - 256, pw = warp - 8;
        const char* pdn = reinterpret_cast<const char*>(wd) + (size_t)cta * 14336 + (lane >> 3) * 896 + pw * 128 + (lane & 7) * 16;
        const char* pwo = reinterpret_cast<const char*>(wo) + (size_t)cta * 28672 + (lane >> 3) * 896 + pw * 128 + (lane & 7) * 16;
        if (pw < 4) {
            if (lane == 0) {
#pragma unroll
                for (int i = 0; i < 9; i++) {
                    if (pw * 9 + i != B_X) mbar_init(full0 + (pw * 9 + i) * 8, NPT);
                    mbar_init(done0 + (pw * 9 + i) * 8, 8);
                }
            }
            Prod p;
            const size_t kvoff = ((size_t)(bat * 8 + hkv) * SK + (SK - WIN)) * DH * 2 + sp * SLOT + pt * 16;
            p.sb = sb;
            p.kvdst = (sb + pt * 16) ^ (pw * 16);
            p.sdst = sb + SM_STRIP + (pt >> 2) * 64 + ((pt & 3) ^ ((pt >> 3) & 3)) * 16;
            p.k = reinterpret_cast<const char*>(kc) + kvoff;
            p.v = reinterpret_cast<const char*>(vc) + kvoff;
            p.gu = ((cta & 1) ? wu : wg) + (cta >> 1) * 32 + (pt & 3) * 8 + (size_t)(pt >> 2) * FF;
            p.ffn = cta < NFFN;
            __syncthreads();
            produce<0>(p, clk);
        } else {
            __syncthreads();
        }
        mbar_wait(full0 + B_X * 8);
        const uint32_t tag = pin((*reinterpret_cast<const uint32_t*>(smem + SM_X + 1792) + 1) & 1);
        if (pw == 4 && (cta & 3) == 0) {
#pragma unroll 1
            for (int i = 0; i < 4; i++) {
                uint32_t sum = 0;
#pragma unroll
                for (int k = 0; k < NM; k++) {
                    mbar_wait(full0 + (MEND - NM + 1 + k + 6 * i) * 8);
                    sum += clk.now() - t0;
                }
                if (lane < 4) st_pub2(&scr->prog[i * 128 + cta + lane], ((t0 + sum / NM) & ~1u) | tag, (t0 & ~1u) | tag);
            }
        }
        mbar_wait(done0 + (NSTAGE + 2 - NS) * 8);
        const uint32_t ta = LATE_T, td = LATE_DT;
        uint4* odst = scr->outp + ((size_t)(pt >> 2) * NCTA + cta) * 4 + t;
        st_pub2x64(odst, tag ^ 1, 0, tag ^ 1, 0);
        const uint32_t fdst = (sb + pw * 2048 + lane * 16) ^ ((lane >> 3) * 16);
        clk.wait_base(sb, 1, ta);
        if (cta < NFFN) fetch16(fdst + slot_of(NSTAGE), pdn);
        asm volatile("cp.async.commit_group;" ::: "memory");
        clk.wait_base(sb, 1, ta + td);
        fetch16(fdst + slot_of(NSTAGE + 1), pwo);
        asm volatile("cp.async.commit_group;" ::: "memory");
        clk.wait_base(sb, 1, ta + 2 * td);
        fetch16(fdst + slot_of(NSTAGE + 2), pwo + 14336);
        asm volatile("cp.async.commit_group;" ::: "memory");
        bar_sync(BAR_H, 256);
        const uint2 h = *reinterpret_cast<const uint2*>(smem + SM_H + (g & 1) * 32 + t * 8);
        float c[4][4];
#pragma unroll
        for (int m = 0; m < 4; m++)
#pragma unroll
            for (int e = 0; e < 4; e++) c[m][e] = 0.f;
        const int r7 = ((lane & 7) >> 1) + 4 * (lane >> 4);
        const uint32_t aoff = sb + pw * 2048 + (r7 + 8 * (lane & 1)) * 128 + (((lane >> 3) & 1) ^ r7 ^ ((lane & 1) << 2)) * 16;
        const uint32_t obaddr = pin(sb + SM_OB + (g & 1) * 64 + t * 16), tt = pin(t);
        uint32_t a0[4][4], a1[4][4];
        frag16<2, slot_of(NSTAGE)>(a0, aoff);
        if (cta < NFFN) {
#pragma unroll
            for (int m = 0; m < 4; m++) mma16816(c[m], a0[m], h.x, h.y);
        }
        frag16<1, slot_of(NSTAGE + 1)>(a1, aoff);
        bar_sync(BAR_OB, 256);
        const uint4 ob = lds128(obaddr);
#pragma unroll
        for (int m = 0; m < 4; m++) mma16816(c[m], a1[m], ob.x, ob.y);
        frag16<0, slot_of(NSTAGE + 2)>(a0, aoff);
#pragma unroll
        for (int m = 0; m < 4; m++) mma16816(c[m], a0[m], ob.z, ob.w);
        st_pub2x64(odst, tagf(sel4(c[0], tt), tag), __float_as_uint(sel4(c[1], tt)), tagf(sel4(c[2], tt), tag), __float_as_uint(sel4(c[3], tt)));
    } else if (warp == 15) {
        if (lane < 4) reinterpret_cast<uint32_t*>(smem + SM_T0)[lane] = t0;
        __syncthreads();
        mbar_wait(full0 + B_X * 8);
        const uint32_t tag = (*reinterpret_cast<const uint32_t*>(smem + SM_X + 1792) + 1) & 1;
#pragma unroll 1
        for (int i = 0; i < 4; i++) {
            mbar_wait(full0 + (MEND + MGAP + 6 * i) * 8);
            uint2 v;
            int it = 0;
            do {
                v = ld_poll2(&scr->prog[i * 128 + lane * 4]);
                if (++it > SPIN_LIMIT) __trap();
            } while (warp_bad(bad2(v.x, v.y, tag)));
            const int nom = i == 0 ? M_NOM0 : i == 1 ? M_NOM1 : i == 2 ? M_NOM2 : M_NOM3;
            int base = (__reduce_add_sync(0xffffffffu, min(max((int)(v.x - t0), 0), 1 << 20)) >> 5) - nom;
            const int start = __reduce_add_sync(0xffffffffu, min(max((int)(v.y - t0), -(1 << 20)), 1 << 20)) >> 5;
            base = start + max(min(base - start, 2 * (base - start - DEAD)), 0);
            const int ahead = (lane == 0 ? nom : lane == 1 ? LATE_T : lane == 2 ? E2_T : E3_T - 150) - nom;
            const float rate = fminf(fmaxf(__fdividef((float)(base - start), (float)(nom - 500)), -0.01f), 0.045f);
            if (lane < 4) reinterpret_cast<volatile uint32_t*>(smem + SM_T0)[lane] = t0 + base + (int)(rate * (float)ahead);
        }
    }
}

}

extern "C" void kernel_launch(void* const* d_in, const int* in_sizes, int n_in, void* d_out, int out_size) {
    (void)in_sizes; (void)n_in; (void)out_size;
    static Scratch* scr = nullptr;
    static uint32_t scale = 64;
    if (!scr) {
        int dev = 0, khz = 0, bits = 0;
        cudaGetDevice(&dev);
        cudaDeviceGetAttribute(&khz, cudaDevAttrMemoryClockRate, dev);
        cudaDeviceGetAttribute(&bits, cudaDevAttrGlobalMemoryBusWidth, dev);
        if (khz > 0 && bits > 0) scale = (uint32_t)(64.0 * khz * bits / (2619000.0 * 5120.0) + 0.5);
        cudaFuncSetAttribute(fused_decode_kernel<false>, cudaFuncAttributeMaxDynamicSharedMemorySize, SM_TOTAL);
        cudaFuncSetAttribute(fused_decode_kernel<true>, cudaFuncAttributeMaxDynamicSharedMemorySize, SM_TOTAL);
        cudaGetSymbolAddress(reinterpret_cast<void**>(&scr), g_scratch);
    }
    typedef const __nv_bfloat16* P;
    if (scale == 64)
        fused_decode_kernel<false><<<NCTA, NTHREADS, SM_TOTAL>>>((P)d_in[3], (P)d_in[1], (P)d_in[0], scr, (P)d_in[2], (P)d_in[4], (P)d_in[6],
                                                                 (P)d_in[7], (P)d_in[8], (__nv_bfloat16*)d_out, Clock<false>{scale});
    else
        fused_decode_kernel<true><<<NCTA, NTHREADS, SM_TOTAL>>>((P)d_in[3], (P)d_in[1], (P)d_in[0], scr, (P)d_in[2], (P)d_in[4], (P)d_in[6],
                                                                (P)d_in[7], (P)d_in[8], (__nv_bfloat16*)d_out, Clock<true>{scale});
}
```

```cpp
#include <cuda_runtime.h>
#include <cuda_bf16.h>
#include <stdint.h>

namespace {

constexpr int PACE_DT = 640;
constexpr int PACE_LEAD = 350;
constexpr int LATE_T = 22290;
constexpr int LATE_DT = 440;
constexpr int Q_T = 3600;
constexpr int E2_T = 23930;
constexpr int M_NOM0 = 4970;
constexpr int M_NOM1 = 9260;
constexpr int M_NOM2 = 13370;
constexpr int M_NOM3 = 17270;
constexpr int DEAD = 100;
constexpr int NM = 4;
constexpr int MEND = 7;
constexpr int MGAP = 4;
constexpr int GU0 = 9;

constexpr int D_MODEL = 448;
constexpr int SK      = 32768;
constexpr int WIN     = 4096;
constexpr int DH      = 256;
constexpr int QCOLS   = 4096;
constexpr int FF      = 1792;
constexpr int NCTA    = 112;
constexpr int NPT     = 128;
constexpr int NTHREADS = 448;

constexpr int NS     = 11;
constexpr int SLOT   = 16384;
constexpr int XROW   = 912;
constexpr int NR     = 19;
constexpr int S_K = 0, S_V = NR, NSTAGE = 2 * NR;
constexpr int S_GU   = GU0;
constexpr int FFN_ST = S_GU + 13 - S_V;
constexpr int HID_ST = FFN_ST + 3;
constexpr int PRE_ST = 14;
constexpr int NBAR   = 40;
constexpr int B_X = NSTAGE, B_FIN = NSTAGE + 1, B_W = NBAR + NSTAGE;
constexpr int SROW = 616, PROW = 336;

constexpr int SM_RING  = 0;
constexpr int SM_WQ    = SM_RING + (NS - 2) * SLOT;
constexpr int SM_STRIP = SM_RING + NS * SLOT;
constexpr int SM_S    = SM_STRIP + 448 * 64;
constexpr int SM_P    = SM_S + 2 * SROW * 4;
constexpr int SM_Q    = SM_P + 2 * PROW * 4;
constexpr int SM_XN   = SM_Q + 2 * 264 * 2;
constexpr int SM_X    = SM_XN + 2 * XROW;
constexpr int SM_RED  = SM_X + 1792 + 32;
constexpr int SM_STAT = SM_RED + 7 * 64 * 4;
constexpr int SM_WGT  = SM_STAT + 2 * 8 * 2 * 4;
constexpr int SM_OB   = SM_WGT + 2 * 8 * 4;
constexpr int SM_IN   = SM_OB + 8 * 2 * 16 * 4;
constexpr int SM_T0   = SM_IN + 2048;
constexpr int SM_BAR  = SM_T0 + 16;
constexpr int SM_TOTAL = SM_BAR + 2 * NBAR * 8;
static_assert(SM_Q % 16 == 0 && SM_XN % 16 == 0 && SM_X % 16 == 0 && SM_OB % 16 == 0 && SM_P % 16 == 0 && SM_IN % 16 == 0, "align");
static_assert(FFN_ST >= 1 && 2 * NS >= NR && NSTAGE % NS + 3 <= NS, "stage -> slot mapping");
static_assert(SM_TOTAL <= 232448, "shared memory");

constexpr int SPIN_LIMIT = 1 << 22;
constexpr float SCALE_LOG2E = 0.0625f * 1.4426950408889634f;

struct __align__(1024) Scratch {
    uint4    part[128 * 2 * 8 * 8];
    uint4    outp[56 * 128 * 4];
    uint2    q[16 * 2 * 7 * 128];
    uint4    hid[NCTA * 8];
    unsigned gu[128 * 32];
    uint2    ml[128 * 4];
    uint2    prog[4 * 32 * 4];
    unsigned epoch[128 * 8];
};
__device__ Scratch g_scratch;

__device__ __forceinline__ void mbar_init(uint32_t bar, uint32_t cnt) {
    asm volatile("mbarrier.init.shared::cta.b64 [%0], %1;" :: "r"(bar), "r"(cnt) : "memory");
}
__device__ __forceinline__ void mbar_arrive(uint32_t bar, uint32_t cnt) {
    asm volatile("mbarrier.arrive.shared::cta.b64 _, [%0], %1;" :: "r"(bar), "r"(cnt) : "memory");
}
template <bool SCALED>
struct Clock {
    uint32_t scale;
    __device__ __forceinline__ uint32_t now() const {
        if constexpr (SCALED) {
            uint64_t t;
            asm volatile("mov.u64 %0, %globaltimer;" : "=l"(t));
            return (uint32_t)((t * scale) >> 6);
        } else {
            uint32_t t;
            asm volatile("mov.u32 %0, %globaltimer_lo;" : "=r"(t));
            return t;
        }
    }
    __device__ __forceinline__ static uint32_t base(uint32_t sb, int i) {
        uint32_t t;
        asm volatile("ld.volatile.shared.u32 %0, [%1];" : "=r"(t) : "r"(sb + SM_T0 + 4 * i) : "memory");
        return t;
    }
    __device__ __forceinline__ void wait_until(uint32_t t0, uint32_t dt) const { while (now() - t0 < dt) {} }
    __device__ __forceinline__ void wait_base(uint32_t sb, int i, uint32_t dt) const { while (now() - base(sb, i) < dt) {} }
};
__device__ __forceinline__ void mbar_wait(uint32_t bar) {
    asm volatile("{\n.reg .pred p;\nWAIT_LOOP:\nmbarrier.try_wait.parity.shared::cta.b64 p, [%0], 0;\n@!p bra WAIT_LOOP;\n}" :: "r"(bar) : "memory");
}
__device__ __forceinline__ void cp_async16(uint32_t dst, const void* src) {
    asm volatile("cp.async.cg.shared.global [%0], [%1], 16;" :: "r"(dst), "l"(src) : "memory");
}
__device__ __forceinline__ void cp_async16_strip(uint32_t dst, const void* src) {
    asm volatile("cp.async.cg.shared.global.L2::128B [%0], [%1], 16;" :: "r"(dst), "l"(src) : "memory");
}
__device__ __forceinline__ void cp_async16_stream(uint32_t dst, const void* src) {
    asm volatile("{\n.reg .b64 pol;\ncreatepolicy.fractional.L2::evict_first.b64 pol, 1.0;\n"
                 "cp.async.cg.shared.global.L2::cache_hint [%0], [%1], 16, pol;\n}" :: "r"(dst), "l"(src) : "memory");
}
__device__ __forceinline__ void cp_async_arrive(uint32_t bar) {
    asm volatile("cp.async.mbarrier.arrive.noinc.shared::cta.b64 [%0];" :: "r"(bar) : "memory");
}
__device__ __forceinline__ void bar_sync(int id, int n)   { asm volatile("bar.sync %0, %1;" :: "r"(id), "r"(n) : "memory"); }
__device__ __forceinline__ void bar_arrive(int id, int n) { asm volatile("bar.arrive %0, %1;" :: "r"(id), "r"(n) : "memory"); }

__device__ __forceinline__ uint32_t ld_poll1(const void* p) {
    uint32_t v;
    asm volatile("ld.relaxed.gpu.global.u32 %0, [%1];" : "=r"(v) : "l"(p) : "memory");
    return v;
}
__device__ __forceinline__ uint2 ld_poll2(const void* p) {
    uint2 v;
    asm volatile("ld.relaxed.gpu.global.v2.u32 {%0,%1}, [%2];" : "=r"(v.x), "=r"(v.y) : "l"(p) : "memory");
    return v;
}
__device__ __forceinline__ uint2 ld_poll64(const void* p) {
    uint2 v;
    asm volatile("{\n.reg .b64 d;\nld.relaxed.gpu.global.b64 d, [%2];\nmov.b64 {%0,%1}, d;\n}" : "=r"(v.x), "=r"(v.y) : "l"(p) : "memory");
    return v;
}
__device__ __forceinline__ uint4 ld_poll2x64(const void* p) {
    uint4 v;
    asm volatile("{\n.reg .b64 d, e;\nld.relaxed.gpu.global.v2.b64 {d,e}, [%4];\nmov.b64 {%0,%1}, d;\nmov.b64 {%2,%3}, e;\n}"
                 : "=r"(v.x), "=r"(v.y), "=r"(v.z), "=r"(v.w) : "l"(p) : "memory");
    return v;
}
__device__ __forceinline__ void st_pub64(void* p, uint32_t a, uint32_t b) {
    asm volatile("{\n.reg .b64 d;\nmov.b64 d, {%1,%2};\nst.relaxed.gpu.global.b64 [%0], d;\n}" :: "l"(p), "r"(a), "r"(b) : "memory");
}
__device__ __forceinline__ void st_pub2(void* p, uint32_t a, uint32_t b) {
    asm volatile("st.relaxed.gpu.global.v2.u32 [%0], {%1,%2};" :: "l"(p), "r"(a), "r"(b) : "memory");
}
__device__ __forceinline__ void st_pub1(void* p, uint32_t a) {
    asm volatile("st.relaxed.gpu.global.u32 [%0], %1;" :: "l"(p), "r"(a) : "memory");
}
__device__ __forceinline__ uint32_t tagf(float v, uint32_t tag) {
    uint32_t r;
    asm("lop3.b32 %0, %1, 0xfffffffe, %2, 0xEA;" : "=r"(r) : "r"(__float_as_uint(v)), "r"(tag));
    return r;
}
__device__ __forceinline__ uint32_t pin(uint32_t v) {
    uint32_t r;
    asm volatile("shfl.sync.bfly.b32 %0, %1, 0, 0x1f, 0xffffffff;" : "=r"(r) : "r"(v));
    return r;
}
template <class T>
__device__ __forceinline__ T* pin(T* p) {
    const uint64_t u = reinterpret_cast<uint64_t>(p);
    return reinterpret_cast<T*>(((uint64_t)pin((uint32_t)(u >> 32)) << 32) | pin((uint32_t)u));
}
__device__ __forceinline__ void sts32(uint32_t addr, uint32_t v) { asm volatile("st.shared.u32 [%0], %1;" :: "r"(addr), "r"(v) : "memory"); }
__device__ __forceinline__ float lds32(uint32_t addr) { float v; asm volatile("ld.shared.f32 %0, [%1];" : "=f"(v) : "r"(addr) : "memory"); return v; }
__device__ __forceinline__ uint4 lds128(uint32_t addr) {
    uint4 v;
    asm volatile("ld.shared.v4.u32 {%0,%1,%2,%3}, [%4];" : "=r"(v.x), "=r"(v.y), "=r"(v.z), "=r"(v.w) : "r"(addr) : "memory");
    return v;
}
__device__ __forceinline__ uint32_t bad2(uint32_t a, uint32_t b, uint32_t tag) {
    uint32_t r;
    asm("lop3.b32 %0, %1, %2, %3, 0x7E;" : "=r"(r) : "r"(a), "r"(b), "r"(tag));
    return r;
}
__device__ __forceinline__ uint32_t bad4(const uint4& v, uint32_t tag) { return bad2(v.x, v.y, tag) | bad2(v.z, v.w, tag); }
__device__ __forceinline__ bool warp_bad(uint32_t bad) { return __any_sync(0xffffffffu, bad & 1u); }

__device__ __forceinline__ void poll4(float (&f)[2][4], const uint2* p, const uint2* p2, uint32_t tag, const float (&w)[4]) {
    uint32_t y[8];
    asm volatile("{\n.reg .pred p0, p1, p2, p3, q;\n.reg .b32 a, m, it;\n.reg .b64 d<4>;\n"
                 "setp.eq.u32 p0, 0, 0;\nsetp.eq.u32 p1, 0, 0;\nsetp.eq.u32 p2, 0, 0;\nsetp.eq.u32 p3, 0, 0;\n"
                 "mov.u32 it, %11;\n"
                 "POLL_LOOP:\n"
                 "@p0 ld.relaxed.gpu.global.b64 d0, [%8];\n"
                 "@p1 ld.relaxed.gpu.global.b64 d1, [%9];\n"
                 "@p2 ld.relaxed.gpu.global.b64 d2, [%8+512];\n"
                 "@p3 ld.relaxed.gpu.global.b64 d3, [%9+512];\n"
                 "sub.u32 it, it, 1;\n"
                 "min.u32 m, it, 1;\n"
                 "mov.b64 {%0,%1}, d0;\nmov.b64 {%2,%3}, d1;\nmov.b64 {%4,%5}, d2;\nmov.b64 {%6,%7}, d3;\n"
                 "lop3.b32 a, %0, %10, m, 0x28;\nsetp.ne.u32 p0, a, 0;\nlop3.b32 a, %2, %10, m, 0x28;\nsetp.ne.u32 p1, a, 0;\n"
                 "lop3.b32 a, %4, %10, m, 0x28;\nsetp.ne.u32 p2, a, 0;\nlop3.b32 a, %6, %10, m, 0x28;\nsetp.ne.u32 p3, a, 0;\n"
                 "or.pred q, p0, p1;\nor.pred q, q, p2;\nor.pred q, q, p3;\nvote.sync.any.pred q, q, 0xffffffff;\n"
                 "@q bra POLL_LOOP;\n}"
                 : "=&r"(y[0]), "=&r"(y[1]), "=&r"(y[2]), "=&r"(y[3]), "=&r"(y[4]), "=&r"(y[5]), "=&r"(y[6]), "=&r"(y[7])
                 : "l"(p), "l"(p2), "r"(tag), "n"(SPIN_LIMIT) : "memory");
#pragma unroll
    for (int b = 0; b < 2; b++) {
        const uint32_t* u = y + 4 * b;
        f[b][0] = fmaf(w[2 * b], __uint_as_float((u[0] ^ tag) << 16), w[2 * b + 1] * __uint_as_float((u[2] ^ tag) << 16));
        f[b][1] = fmaf(w[2 * b], __uint_as_float(u[0] & 0xffff0000u), w[2 * b + 1] * __uint_as_float(u[2] & 0xffff0000u));
        f[b][2] = fmaf(w[2 * b], __uint_as_float(u[1] << 16), w[2 * b + 1] * __uint_as_float(u[3] << 16));
        f[b][3] = fmaf(w[2 * b], __uint_as_float(u[1] & 0xffff0000u), w[2 * b + 1] * __uint_as_float(u[3] & 0xffff0000u));
    }
}

__device__ __forceinline__ void ldsm4(uint32_t addr, uint32_t (&a)[4]) {
    asm volatile("ldmatrix.sync.aligned.m8n8.x4.shared.b16 {%0,%1,%2,%3}, [%4];" : "=r"(a[0]), "=r"(a[1]), "=r"(a[2]), "=r"(a[3]) : "r"(addr) : "memory");
}
__device__ __forceinline__ void ldsm4t(uint32_t addr, uint32_t (&a)[4]) {
    asm volatile("ldmatrix.sync.aligned.m8n8.x4.trans.shared.b16 {%0,%1,%2,%3}, [%4];" : "=r"(a[0]), "=r"(a[1]), "=r"(a[2]), "=r"(a[3]) : "r"(addr) : "memory");
}
__device__ __forceinline__ void mma16816(float (&c)[4], const uint32_t (&a)[4], uint32_t b0, uint32_t b1) {
    asm volatile("mma.sync.aligned.m16n8k16.row.col.f32.bf16.bf16.f32 {%0,%1,%2,%3}, {%4,%5,%6,%7}, {%8,%9}, {%0,%1,%2,%3};"
                 : "+f"(c[0]), "+f"(c[1]), "+f"(c[2]), "+f"(c[3]) : "r"(a[0]), "r"(a[1]), "r"(a[2]), "r"(a[3]), "r"(b0), "r"(b1));
}
__device__ __forceinline__ float bf_lo(uint32_t u) { return __uint_as_float(u << 16); }
__device__ __forceinline__ float bf_hi(uint32_t u) { return __uint_as_float(u & 0xffff0000u); }
__device__ __forceinline__ float rbf(float v) { return __bfloat162float(__float2bfloat16_rn(v)); }
__device__ __forceinline__ uint32_t pack_bf(float lo, float hi) {
    uint32_t r;
    asm("cvt.rn.bf16x2.f32 %0, %1, %2;" : "=r"(r) : "f"(hi), "f"(lo));
    return r;
}
__device__ __forceinline__ float sel4(const float (&c)[4], int t) {
    float a = (t & 1) ? c[1] : c[0];
    float b = (t & 1) ? c[3] : c[2];
    return (t & 2) ? b : a;
}
__device__ __forceinline__ float ex2(float x) { float y; asm("ex2.approx.ftz.f32 %0, %1;" : "=f"(y) : "f"(x)); return y; }
__device__ __forceinline__ float sqrt_approx(float x) { float y; asm("sqrt.approx.f32 %0, %1;" : "=f"(y) : "f"(x)); return y; }

__host__ __device__ constexpr uint32_t slot_of(int s) { return SM_RING + (s % NS) * SLOT; }

__device__ __forceinline__ void layernorm(unsigned char* smem, int lane) {
    uint32_t xs[2][7];
#pragma unroll
    for (int b = 0; b < 2; b++)
#pragma unroll
        for (int i = 0; i < 7; i++) xs[b][i] = reinterpret_cast<const uint32_t*>(smem + SM_X)[b * (D_MODEL / 2) + i * 32 + lane];
#pragma unroll
    for (int b = 0; b < 2; b++) {
        float sum = 0.f;
#pragma unroll
        for (int i = 0; i < 7; i++) sum += bf_lo(xs[b][i]) + bf_hi(xs[b][i]);
#pragma unroll
        for (int o = 16; o > 0; o >>= 1) sum += __shfl_xor_sync(0xffffffffu, sum, o);
        const float mean = sum * (1.0f / D_MODEL);
        float sq = 0.f;
#pragma unroll
        for (int i = 0; i < 7; i++) {
            const float d0 = bf_lo(xs[b][i]) - mean, d1 = bf_hi(xs[b][i]) - mean;
            sq = fmaf(d0, d0, fmaf(d1, d1, sq));
        }
#pragma unroll
        for (int o = 16; o > 0; o >>= 1) sq += __shfl_xor_sync(0xffffffffu, sq, o);
        const float mb = rbf(mean);
        const float sd = rbf(sqrt_approx(rbf(rbf(sq * (1.0f / D_MODEL)) + 1e-5f)));
#pragma unroll
        for (int i = 0; i < 7; i++)
            reinterpret_cast<uint32_t*>(smem + SM_XN + b * XROW)[i * 32 + lane] =
                pack_bf(__fdividef(rbf(bf_lo(xs[b][i]) - mb), sd), __fdividef(rbf(bf_hi(xs[b][i]) - mb), sd));
    }
}

__device__ __forceinline__ void strip_partial(uint32_t sb, uint32_t strip, unsigned char* smem, int warp, int lane) {
    float c[2][2][4];
#pragma unroll
    for (int n = 0; n < 2; n++)
#pragma unroll
        for (int e = 0; e < 4; e++) c[n][0][e] = c[n][1][e] = 0.f;
    const uint32_t ba = sb + SM_XN + (lane & 1) * XROW + (lane >> 3) * 16 + warp * 128;
    const uint32_t aa = sb + strip + (warp * 64 + (lane & 7) + (lane >> 4) * 8) * 64 + (((lane >> 3) & 1) ^ ((lane & 7) >> 1)) * 16;
#pragma unroll
    for (int k2 = 0; k2 < 2; k2++) {
        uint32_t b[4];
        ldsm4(ba + k2 * 64, b);
#pragma unroll
        for (int n = 0; n < 2; n++) {
            uint32_t a0[4], a1[4];
            ldsm4t((aa ^ (n * 32)) + k2 * 2048, a0);
            ldsm4t((aa ^ (n * 32)) + k2 * 2048 + 1024, a1);
            mma16816(c[n][0], a0, b[0], b[1]);
            mma16816(c[n][1], a1, b[2], b[3]);
        }
    }
    float* red = reinterpret_cast<float*>(smem + SM_RED) + warp * 64 + lane;
#pragma unroll
    for (int n = 0; n < 2; n++) red[n * 32] = sel4(c[n][0], lane & 3) + sel4(c[n][1], lane & 3);
}
__device__ __forceinline__ float strip_sum(const unsigned char* smem, int idx) {
    const float* red = reinterpret_cast<const float*>(smem + SM_RED) + idx;
    return ((red[0] + red[64]) + (red[128] + red[192])) + ((red[256] + red[320]) + red[384]);
}

struct Prod {
    uint32_t sb, kvdst, sdst;
    const char *k, *v;
    int extra;
    const __nv_bfloat16* gu;
};
__host__ __device__ constexpr int kb_before(int s) {
    return 3584 + (s / NR) * 32768 + (s % NR == 0 ? 0 : 512 + (s % NR - 1) * 1792) + (s <= S_GU ? 0 : s < S_GU + 14 ? s - S_GU : 14) * 224;
}
__host__ __device__ constexpr int issue_time(int s) { return kb_before(s) * PACE_DT / 2048 - PACE_LEAD; }

template <int S, class CLK>
__device__ __forceinline__ void produce(Prod& p, const CLK& clk) {
    if constexpr (S < NSTAGE) {
        if constexpr (S == NS - 2) mbar_wait(p.sb + SM_BAR + B_W * 8);
        if constexpr (S >= NS) mbar_wait(p.sb + SM_BAR + (NBAR + S - NS) * 8);
        clk.wait_base(p.sb, 0, issue_time(S));
        if (S % NR != 0 || p.extra != 1) {
            const char* src = (S < S_V ? p.k : p.v) + (S % NR == 0 ? p.extra : (S % NR - 1) * (7 * SLOT));
#pragma unroll
            for (int i = 0; i < 8; i++) cp_async16_stream((p.kvdst ^ ((i & 1) * 64)) + slot_of(S) + i * 2048, src + i * 2048);
        }
        if constexpr (S >= S_GU && S < S_GU + 14) cp_async16_strip(p.sdst + (S - S_GU) * 2048, p.gu + (size_t)(S - S_GU) * 32 * FF);
        cp_async_arrive(p.sb + SM_BAR + S * 8);
        produce<S + 1>(p, clk);
    }
}

__device__ __forceinline__ void fetch16(uint32_t dst, const char* src) {
#pragma unroll
    for (int i = 0; i < 4; i++) cp_async16((dst ^ (((i & 1) ^ (i >> 1)) * 64)) + i * 512, src + i * (4 * 896));
}
template <int PENDING, int OFF>
__device__ __forceinline__ void frag32(uint32_t (&a)[2][4][4], uint32_t addr) {
    asm volatile("cp.async.wait_group %0;" :: "n"(PENDING) : "memory");
    __syncwarp();
#pragma unroll
    for (int h = 0; h < 2; h++)
#pragma unroll
        for (int m = 0; m < 4; m++) ldsm4t((addr ^ (m * 32)) + OFF + h * 2048, a[h][m]);
}
__device__ __forceinline__ void mma32(float (&c)[4][4], const uint32_t (&a)[2][4][4], const uint4& b) {
#pragma unroll
    for (int m = 0; m < 4; m++) mma16816(c[m], a[0][m], b.x, b.y);
#pragma unroll
    for (int m = 0; m < 4; m++) mma16816(c[m], a[1][m], b.z, b.w);
}

__device__ __forceinline__ void load_x(uint32_t sb, const void* x, const void* epoch) {
    const uint32_t full0 = sb + SM_BAR;
    mbar_init(full0 + B_X * 8, 1);
    asm volatile("fence.mbarrier_init.release.cluster;" ::: "memory");
    asm volatile("mbarrier.arrive.expect_tx.shared::cta.b64 _, [%0], %1;" :: "r"(full0 + B_X * 8), "r"(1792 + 16) : "memory");
    asm volatile("cp.async.bulk.shared::cluster.global.mbarrier::complete_tx::bytes [%0], [%1], %2, [%3];"
                 :: "r"(sb + SM_X), "l"(x), "r"(1792), "r"(full0 + B_X * 8) : "memory");
    asm volatile("cp.async.bulk.shared::cluster.global.mbarrier::complete_tx::bytes [%0], [%1], %2, [%3];"
                 :: "r"(sb + SM_X + 1792), "l"(epoch), "r"(16), "r"(full0 + B_X * 8) : "memory");
}

enum { BAR_CONS = 1, BAR_LN = 2, BAR_FF = 3, BAR_WGT = 4, BAR_OB = 8   };

template <bool SCALED>
__global__ void __launch_bounds__(NTHREADS, 1)
fused_decode_kernel(const __nv_bfloat16* __restrict__ wq, const __nv_bfloat16* __restrict__ kc, const __nv_bfloat16* __restrict__ x,
                    Scratch* __restrict__ scr, const __nv_bfloat16* __restrict__ vc, const __nv_bfloat16* __restrict__ wo,
                    const __nv_bfloat16* __restrict__ wg, const __nv_bfloat16* __restrict__ wu, const __nv_bfloat16* __restrict__ wd,
                    __nv_bfloat16* __restrict__ out, const Clock<SCALED> clk) {
    extern __shared__ __align__(128) unsigned char smem[];
    const uint32_t sb = (uint32_t)__cvta_generic_to_shared(smem);
    const int tid = threadIdx.x, lane = tid & 31;
    const int cta = blockIdx.x;
    const int cl = cta >> 4, rk = cta & 15;
    const uint32_t full0 = sb + SM_BAR, done0 = full0 + NBAR * 8;
    const uint32_t t0 = clk.now();
    if (tid < 256) {
        const char* src = reinterpret_cast<const char*>(wq) + (uint32_t)((cl * 64 + (tid >> 5)) * (QCOLS * 2) + rk * 512 + lane * 16);
        const uint32_t dst = (sb + SM_WQ + tid * 16) ^ ((tid >> 5) * 16);
#pragma unroll
        for (int i = 0; i < 8; i++) cp_async16(dst + i * 4096, src + i * (8 * QCOLS * 2));
    }
    const int warp = __shfl_sync(0xffffffffu, tid >> 5, 0);
    const int hkv = rk >> 1, bat = rk & 1;
    const int e0 = (2 * rk) % 7;
    const int extra = cl == e0 ? 0 : cl == (e0 + 1) % 7 ? 1 : -1;
    const int g = lane >> 2, t = lane & 3;
    if (warp >= 8 && warp < 12 && lane == 0) {
#pragma unroll
        for (int i = 0; i < 10; i++) {
            const int b = (warp - 8) * 10 + i;
            if (b != B_X) mbar_init(full0 + b * 8, b == B_FIN ? 1 : NPT);
            mbar_init(done0 + b * 8, 8);
        }
        if (warp == 11) {
            asm volatile("mbarrier.arrive.expect_tx.shared::cta.b64 _, [%0], %1;" :: "r"(full0 + B_FIN * 8), "r"(2048) : "memory");
            asm volatile("fence.mbarrier_init.release.cluster;" ::: "memory");
        }
    }
    if (tid == 384) load_x(sb, x, &scr->epoch[cta * 8]);
    if (warp == 13 && lane < 4) reinterpret_cast<uint32_t*>(smem + SM_T0)[lane] = t0;
    __syncthreads();
    asm volatile("barrier.cluster.arrive.relaxed.aligned;" ::: "memory");

    if (warp < 8) {
        mbar_wait(full0 + B_X * 8);
        const uint32_t epoch = *reinterpret_cast<const uint32_t*>(smem + SM_X + 1792);
        const uint32_t tag = pin((epoch + 1) & 1);
        const uint32_t voff = ((lane & 7) + (lane >> 4) * 8) * 512 + ((warp * 4 + ((lane >> 3) & 1) * 2) ^ (lane & 7)) * 16;
        {
            asm volatile("cp.async.wait_all;" ::: "memory");
            bar_sync(BAR_LN, 288);
            float c0[4] = {0.f, 0.f, 0.f, 0.f}, c1[4] = {0.f, 0.f, 0.f, 0.f};
#pragma unroll
            for (int h = 0; h < 2; h++) {
                uint32_t b[4], a[4][4];
                ldsm4(sb + SM_XN + (lane & 1) * XROW + (lane >> 3) * 16 + cl * 128 + h * 64, b);
#pragma unroll
                for (int i = 0; i < 4; i++) ldsm4t(sb + (voff ^ ((i & 1) * 16)) + SM_WQ + h * SLOT + (i >> 1) * 8192, a[i]);
                mma16816(c0, a[0], b[0], b[1]);
                mma16816(c1, a[1], b[0], b[1]);
                mma16816(c0, a[2], b[2], b[3]);
                mma16816(c1, a[3], b[2], b[3]);
            }
            st_pub64(scr->q + ((rk * 2 + (t & 1)) * 7 + cl) * 128 + warp * 16 + (t >> 1) * 8 + g, tagf(sel4(c0, t), tag), __float_as_uint(sel4(c1, t)));
            __syncwarp();
            if (lane == 0) mbar_arrive(full0 + B_W * 8, 1);
            const uint2* qp = scr->q + ((hkv * 2 + (tid >> 7)) * 2 + bat) * (7 * 128) + (tid & 127);
            clk.wait_until(t0, Q_T);
            uint2 v[7];
            int it = 0;
            uint32_t bad;
            do {
                bad = 0;
#pragma unroll
                for (int i = 0; i < 7; i++) v[i] = ld_poll64(qp + i * 128);
#pragma unroll
                for (int i = 0; i < 7; i++) { v[i].x ^= tag; bad |= v[i].x; }
                if (++it > SPIN_LIMIT) __trap();
            } while (warp_bad(bad));
            float q0 = 0.f, q1 = 0.f;
#pragma unroll
            for (int i = 0; i < 7; i++) { q0 += __uint_as_float(v[i].x); q1 += __uint_as_float(v[i].y); }
            __nv_bfloat16* qs = reinterpret_cast<__nv_bfloat16*>(smem + SM_Q + (tid >> 7) * 528) + ((tid & 127) >> 3) * 16 + (tid & 7);
            qs[0] = __float2bfloat16_rn(q0);
            qs[8] = __float2bfloat16_rn(q1);
        }
        bar_sync(BAR_CONS, 256);
        if (tid == 96) scr->epoch[cta * 8] = epoch + 1;
        {
            uint32_t qf[8][4];
#pragma unroll
            for (int k2 = 0; k2 < 8; k2++) ldsm4(sb + SM_Q + (lane & 1) * 528 + k2 * 64 + (lane >> 3) * 16, qf[k2]);
            const int mt = warp & 1;
            const uint32_t aoff = (16 * mt + (lane & 15)) * 512 + ((lane >> 4) ^ (lane & 7)) * 16;
            float* sc = reinterpret_cast<float*>(smem + SM_S) + (t & 1) * SROW + (g >> 1) * 8 + (2 * mt + (t >> 1)) * 2 + (g & 1);
#pragma unroll 1
            for (int k = warp >> 1; k < NR; k += 4) {
                const int s = S_K + k;
                mbar_wait(full0 + s * 8);
                const uint32_t base = sb + SM_RING + (s >= NS ? s - NS : s) * SLOT + aoff;
                float c0[4] = {0.f, 0.f, 0.f, 0.f}, c1[4] = {0.f, 0.f, 0.f, 0.f};
#pragma unroll
                for (int k2 = 0; k2 < 8; k2++) {
                    uint32_t a0[4], a1[4];
                    ldsm4((base ^ ((k2 & 1) * 64)) + (k2 >> 1) * 128, a0);
                    ldsm4((base ^ ((k2 & 1) * 64 + 32)) + (k2 >> 1) * 128, a1);
                    mma16816(c0, a0, qf[k2][0], qf[k2][1]);
                    mma16816(c1, a1, qf[k2][2], qf[k2][3]);
                }
                __syncwarp();
                if (lane == 0) mbar_arrive(done0 + s * 8, 4);
                sc[k * 32] = rbf(sel4(c0, t) + sel4(c1, t));
            }
        }
        bar_sync(BAR_CONS, 256);
        {
            constexpr float C = SCALE_LOG2E;
            const float* sc = reinterpret_cast<const float*>(smem + SM_S);
            float* stat = reinterpret_cast<float*>(smem + SM_STAT);
            const bool two = tid < 48 && (tid >= 16 || extra >= 0);
            float2 s[2][2];
#pragma unroll
            for (int h = 0; h < 2; h++) {
                s[h][0] = *reinterpret_cast<const float2*>(sc + h * SROW + 96 + 2 * tid);
                s[h][1] = two ? *reinterpret_cast<const float2*>(sc + h * SROW + 2 * tid) : s[h][0];
            }
            float m0 = fmaxf(fmaxf(s[0][0].x, s[0][0].y), fmaxf(s[0][1].x, s[0][1].y));
            float m1 = fmaxf(fmaxf(s[1][0].x, s[1][0].y), fmaxf(s[1][1].x, s[1][1].y));
#pragma unroll
            for (int o = 16; o > 0; o >>= 1) {
                m0 = fmaxf(m0, __shfl_xor_sync(0xffffffffu, m0, o));
                m1 = fmaxf(m1, __shfl_xor_sync(0xffffffffu, m1, o));
            }
            if (lane == 0) *reinterpret_cast<float2*>(stat + warp * 2) = make_float2(m0, m1);
            bar_sync(BAR_CONS, 256);
#pragma unroll
            for (int w = 0; w < 8; w++) {
                const float2 mm = *reinterpret_cast<const float2*>(stat + w * 2);
                m0 = fmaxf(m0, mm.x); m1 = fmaxf(m1, mm.y);
            }
            uint32_t* ps = reinterpret_cast<uint32_t*>(smem + SM_P);
            float l[2];
#pragma unroll
            for (int h = 0; h < 2; h++) {
                const float m = h ? m1 : m0;
                const float pa = ex2((s[h][0].x - m) * C), pb = ex2((s[h][0].y - m) * C);
                const float pc = ex2((s[h][1].x - m) * C), pd = ex2((s[h][1].y - m) * C);
                ps[h * PROW + 48 + tid] = pack_bf(pa, pb);
                if (two) ps[h * PROW + tid] = pack_bf(pc, pd);
                l[h] = (pa + pb) + (two ? pc + pd : 0.f);
            }
#pragma unroll
            for (int o = 16; o > 0; o >>= 1) {
                l[0] += __shfl_xor_sync(0xffffffffu, l[0], o);
                l[1] += __shfl_xor_sync(0xffffffffu, l[1], o);
            }
            if (lane == 0) *reinterpret_cast<float2*>(stat + 16 + warp * 2) = make_float2(l[0], l[1]);
            bar_sync(BAR_CONS, 256);
            if (tid < 4) {
                float ls = 0.f;
#pragma unroll
                for (int w = 0; w < 8; w++) ls += stat[16 + w * 2 + (tid & 1)];
                st_pub2(scr->ml + cta * 4 + tid, tagf((tid & 1) ? m1 : m0, tag), tagf(ls, tag));
            }
        }
        {
            float own = 0.f;
            float o0[4] = {0.f, 0.f, 0.f, 0.f}, o1[4] = {0.f, 0.f, 0.f, 0.f};
            float o2[4] = {0.f, 0.f, 0.f, 0.f}, o3[4] = {0.f, 0.f, 0.f, 0.f};
            const uint4* ps = reinterpret_cast<const uint4*>(smem + SM_P + (g & 1) * PROW * 4) + t;
            uint2* dst = reinterpret_cast<uint2*>(scr->part) + ((size_t)(hkv * 16 + (t & 1) * 8 + warp) * 16 + bat * 8 + cl) * 8 + g;
#pragma unroll
            for (int k = 0; k < NR; k++) {
                if (k != 0 || extra >= 0) {
                    const uint4 pa = ps[k * 4];
                    mbar_wait(full0 + (S_V + k) * 8);
                    uint32_t a[4][4];
#pragma unroll
                    for (int i = 0; i < 4; i++) ldsm4t(sb + (voff ^ ((i & 1) * 16)) + slot_of(S_V + k) + (i >> 1) * 8192, a[i]);
                    mma16816(o0, a[0], pa.x, pa.y);
                    mma16816(o1, a[1], pa.x, pa.y);
                    mma16816(o2, a[2], pa.z, pa.w);
                    mma16816(o3, a[3], pa.z, pa.w);
                }
                if (S_V + k + NS < NSTAGE + 3) {
                    __syncwarp();
                    if (lane == 0) mbar_arrive(done0 + (S_V + k) * 8, 1);
                }
                if (k == FFN_ST && warp < 7) {
                    strip_partial(sb, SM_STRIP, smem, warp, lane);
                    bar_arrive(BAR_FF, 256);
                }
                if (k == FFN_ST && warp == 7) {
                    bar_sync(BAR_FF, 256);
                    own = rbf(strip_sum(smem, (cta & 1) * 32 + lane));
                    st_pub1(scr->gu + (cta ^ 1) * 32 + lane, (pack_bf(0.f, strip_sum(smem, (~cta & 1) * 32 + lane)) & 0xffff0000u) | tag);
                }
                if (k == HID_ST && warp == 7) {
                    const uint2* mlp = scr->ml + (min(g, 6) * 16 + (rk & ~1)) * 4 + (rk & 1);
                    uint2 a, b;
                    uint32_t other;
                    int it = 0;
                    do {
                        a = ld_poll2(mlp); b = ld_poll2(mlp + 4); other = ld_poll1(scr->gu + cta * 32 + lane);
                        if (++it > SPIN_LIMIT) __trap();
                    } while (warp_bad(bad2(a.x, a.y, tag) | bad2(b.x, b.y, tag) | (other ^ tag)));
                    float ga = (cta & 1) ? bf_hi(other) : own;
                    ga *= (ga > 0.f ? 1.f : 0.f);
                    const float hv = ga * ((cta & 1) ? own : bf_hi(other));
                    const uint32_t w = pack_bf(hv, __shfl_xor_sync(0xffffffffu, hv, 2));
                    if (!(t & 2)) st_pub64(reinterpret_cast<uint2*>(scr->hid) + cta * 16 + (t & 1) * 8 + (g & 3) * 2 + (g >> 2), tag, w);
                    const float m[2] = {bf_hi(a.x), bf_hi(b.x)};
                    const float l[2] = {__uint_as_float(a.y ^ tag), __uint_as_float(b.y ^ tag)};
#pragma unroll
                    for (int bb = 0; bb < 2; bb++) {
                        float M = m[bb];
                        M = fmaxf(M, __shfl_xor_sync(0xffffffffu, M, 4));
                        M = fmaxf(M, __shfl_xor_sync(0xffffffffu, M, 8));
                        M = fmaxf(M, __shfl_xor_sync(0xffffffffu, M, 16));
                        const float e = g < 7 ? ex2((m[bb] - M) * SCALE_LOG2E) : 0.f;
                        float L = e * l[bb];
                        L += __shfl_xor_sync(0xffffffffu, L, 4);
                        L += __shfl_xor_sync(0xffffffffu, L, 8);
                        L += __shfl_xor_sync(0xffffffffu, L, 16);
                        if (t == 0) reinterpret_cast<float*>(smem + SM_WGT)[bb * 8 + g] = __fdividef(e, L);
                    }
                }
                if (k == PRE_ST && t < 2) st_pub64(dst, tag ^ 1, 0);
            }
            const bool h1 = t & 1;
            const float va = h1 ? o0[1] + o2[1] : o0[0] + o2[0], vb = h1 ? o1[1] + o3[1] : o1[0] + o3[0];
            const float vc2 = h1 ? o0[3] + o2[3] : o0[2] + o2[2], vd = h1 ? o1[3] + o3[3] : o1[2] + o3[2];
            if (t < 2) st_pub64(dst, (__byte_perm(__float_as_uint(va) + 0x10000u, pack_bf(0.f, vb), 0x7632) & ~1u) | tag, pack_bf(vc2, vd));
        }
        {
            bar_sync(BAR_WGT, 256);
            const uint2* pp = pin(reinterpret_cast<const uint2*>(scr->part) + (size_t)(rk * 8 + warp) * 128 + lane);
            const uint2* pp2 = pin(reinterpret_cast<const uint2*>(scr->part) + (size_t)(rk * 8 + warp) * 128 + lane + (lane < 24 ? 32 : 24));
            const uint32_t obaddr = pin(sb + SM_OB + warp * 128 + (lane >> 4) * 64 + (lane & 3) * 16 + ((lane >> 3) & 1) * 8 + ((lane >> 2) & 1) * 4), ll = pin(lane);
            float w[4];
#pragma unroll
            for (int i = 0; i < 4; i++) w[i] = lds32(sb + SM_WGT + (i * 4 + (lane >> 3)) * 4);
            clk.wait_until(clk.base(sb, 2), E2_T);
            float f[2][4];
            poll4(f, pp, pp2, tag, w);
            const bool h16 = ll & 16, h8 = ll & 8;
            float r4[4], r2[2];
#pragma unroll
            for (int e = 0; e < 4; e++) r4[e] = (h16 ? f[1][e] : f[0][e]) + __shfl_xor_sync(0xffffffffu, h16 ? f[0][e] : f[1][e], 16);
#pragma unroll
            for (int e = 0; e < 2; e++) r2[e] = (h8 ? r4[2 + e] : r4[e]) + __shfl_xor_sync(0xffffffffu, h8 ? r4[e] : r4[2 + e], 8);
            sts32(obaddr, pack_bf(r2[0], r2[1]));
            bar_arrive(BAR_OB + (warp >> 1), 96);
        }
    } else if (warp < 12) {
        const int pt = tid - 256, pw = warp - 8;
        {
            Prod p;
            const size_t kvoff = ((size_t)(bat * 8 + hkv) * SK + (SK - WIN)) * DH * 2 + (2 + cl) * SLOT + pt * 16;
            p.sb = sb;
            p.kvdst = (sb + pt * 16) ^ (pw * 16);
            p.sdst = sb + SM_STRIP + (pt >> 2) * 64 + ((pt & 3) ^ ((pt >> 3) & 3)) * 16;
            p.k = reinterpret_cast<const char*>(kc) + kvoff;
            p.v = reinterpret_cast<const char*>(vc) + kvoff;
            p.extra = extra >= 0 ? (extra - 2 - cl) * SLOT : 1;
            p.gu = ((cta & 1) ? wu : wg) + (cta >> 1) * 32 + (pt & 3) * 8 + (size_t)(pt >> 2) * FF;
            produce<0>(p, clk);
        }
        mbar_wait(full0 + B_X * 8);
        const uint32_t tag = (*reinterpret_cast<const uint32_t*>(smem + SM_X + 1792) + 1) & 1;
        mbar_wait(done0 + (NSTAGE + 2 - NS) * 8);
        const char* pdn = reinterpret_cast<const char*>(wd) + (size_t)(rk * 112 + pw * 32 + (lane >> 3)) * 896 + cl * 128 + (lane & 7) * 16;
        const char* pwo = reinterpret_cast<const char*>(wo) + (size_t)(rk * 256 + pw * 64 + (lane >> 3)) * 896 + cl * 128 + (lane & 7) * 16;
        const uint4* hp = scr->hid + (rk * 7 + pw * 2) * 8 + (lane & 7);
        uint4 h0 = ld_poll2x64(hp), h1 = ld_poll2x64(hp + (pw < 3 ? 8 : 0));
        const uint32_t ta = LATE_T, td = LATE_DT;
        const uint32_t fdst = (sb + pw * 4096 + lane * 16) ^ ((lane >> 3) * 16);
        clk.wait_base(sb, 1, ta);
        fetch16(fdst + slot_of(NSTAGE), pdn);
        if (pw < 3) fetch16(fdst + slot_of(NSTAGE) + 2048, pdn + 16 * 896);
        asm volatile("cp.async.commit_group;" ::: "memory");
        clk.wait_base(sb, 1, ta + td);
        fetch16(fdst + slot_of(NSTAGE + 1), pwo);
        fetch16(fdst + slot_of(NSTAGE + 1) + 2048, pwo + 16 * 896);
        asm volatile("cp.async.commit_group;" ::: "memory");
        clk.wait_base(sb, 1, ta + 2 * td);
        fetch16(fdst + slot_of(NSTAGE + 2), pwo + 32 * 896);
        fetch16(fdst + slot_of(NSTAGE + 2) + 2048, pwo + 48 * 896);
        asm volatile("cp.async.commit_group;" ::: "memory");
        for (int it = 0; warp_bad(bad2(h0.x, h0.z, tag) | bad2(h1.x, h1.z, tag)); it++) {
            h0 = ld_poll2x64(hp); h1 = ld_poll2x64(hp + (pw < 3 ? 8 : 0));
            if (it > SPIN_LIMIT) __trap();
        }
        asm volatile("barrier.cluster.wait.aligned;" ::: "memory");
        uint32_t rdst, rbar;
        asm volatile("mapa.shared::cluster.u32 %0, %1, %2;" : "=r"(rdst) : "r"(sb + SM_IN + (rk * 4 + pw) * 32 + (lane & 1) * 16), "r"(lane >> 1));
        asm volatile("mapa.shared::cluster.u32 %0, %1, %2;" : "=r"(rbar) : "r"(full0 + B_FIN * 8), "r"(lane >> 1));
        rdst = pin(rdst); rbar = pin(rbar);
        float c[4][4];
#pragma unroll
        for (int m = 0; m < 4; m++)
#pragma unroll
            for (int e = 0; e < 4; e++) c[m][e] = 0.f;
        const int r7 = ((lane & 7) >> 1) + 4 * (lane >> 4);
        const uint32_t aoff = sb + pw * 4096 + (r7 + 8 * (lane & 1)) * 128 + (((lane >> 3) & 1) ^ r7 ^ ((lane & 1) << 2)) * 16;
        const uint32_t obaddr = pin(sb + SM_OB + pw * 256 + (g & 1) * 64 + t * 16), tt = pin(t);
        uint32_t a0[2][4][4], a1[2][4][4];
        frag32<2, slot_of(NSTAGE)>(a0, aoff);
#pragma unroll
        for (int m = 0; m < 4; m++) mma16816(c[m], a0[0][m], h0.y, h0.w);
        if (pw < 3) {
#pragma unroll
            for (int m = 0; m < 4; m++) mma16816(c[m], a0[1][m], h1.y, h1.w);
        }
        frag32<1, slot_of(NSTAGE + 1)>(a1, aoff);
        bar_sync(BAR_OB + pw, 96);
        const uint4 ob0 = lds128(obaddr), ob1 = lds128(obaddr + 128);
        mma32(c, a1, ob0);
        frag32<0, slot_of(NSTAGE + 2)>(a0, aoff);
        mma32(c, a0, ob1);
        asm volatile("st.async.weak.shared::cluster.mbarrier::complete_tx::bytes.v4.f32 [%0], {%1,%2,%3,%4}, [%5];"
                     :: "r"(rdst), "f"(sel4(c[0], tt)), "f"(sel4(c[1], tt)), "f"(sel4(c[2], tt)), "f"(sel4(c[3], tt)), "r"(rbar) : "memory");
    } else if (warp == 12) {
        mbar_wait(full0 + B_X * 8);
        layernorm(smem, lane);
        bar_arrive(BAR_LN, 288);
        const uint32_t tag = (*reinterpret_cast<const uint32_t*>(smem + SM_X + 1792) + 1) & 1;
        if ((cta & 3) == 0) {
#pragma unroll 1
            for (int i = 0; i < 4; i++) {
                uint32_t sum = 0;
#pragma unroll
                for (int k = 0; k < NM; k++) {
                    mbar_wait(full0 + (MEND - NM + 1 + k + 7 * i) * 8);
                    sum += clk.now() - t0;
                }
                if (lane < 4) st_pub2(&scr->prog[i * 128 + cta + lane], ((t0 + sum / NM) & ~1u) | tag, (t0 & ~1u) | tag);
            }
        }
        const int oidx = ((lane >> 2) & 1) * D_MODEL + cl * 64 + (lane & 3) * 16 + (rk >> 1) + (rk & 1) * 8;
        const float xv = __bfloat162float(reinterpret_cast<const __nv_bfloat16*>(smem + SM_X)[oidx]);
        __nv_bfloat16* optr = pin(out + oidx);
        const uint32_t in = pin(sb + SM_IN + lane * 4);
        float v[16];
        asm volatile("{\n.reg .pred p;\nWAIT_LOOP:\nmbarrier.try_wait.parity.acquire.cluster.shared::cta.b64 p, [%0], 0;\n@!p bra WAIT_LOOP;\n}"
                     :: "r"(full0 + B_FIN * 8) : "memory");
#pragma unroll
        for (int i = 0; i < 16; i++) v[i] = lds32(in + i * 128);
#pragma unroll
        for (int i = 0; i < 16; i += 4) v[i] = (v[i] + v[i + 1]) + (v[i + 2] + v[i + 3]);
        float r = (v[0] + v[4]) + (v[8] + v[12]);
        r += __shfl_xor_sync(0xffffffffu, r, 8);
        r += __shfl_xor_sync(0xffffffffu, r, 16);
        asm volatile("st.global.u16 [%0], %1;" :: "l"(optr), "h"(__bfloat16_as_ushort(__float2bfloat16_rn(xv + r))) : "memory");
    } else if (warp == 13) {
        mbar_wait(full0 + B_X * 8);
        const uint32_t tag = (*reinterpret_cast<const uint32_t*>(smem + SM_X + 1792) + 1) & 1;
#pragma unroll 1
        for (int i = 0; i < 4; i++) {
            mbar_wait(full0 + (MEND + MGAP + 7 * i) * 8);
            uint2 v;
            int it = 0;
            do {
                v = ld_poll2(&scr->prog[i * 128 + min(lane, 27) * 4]);
                if (++it > SPIN_LIMIT) __trap();
            } while (warp_bad(bad2(v.x, v.y, tag)));
            const int nom = i == 0 ? M_NOM0 : i == 1 ? M_NOM1 : i == 2 ? M_NOM2 : M_NOM3;
            int base = __reduce_add_sync(0xffffffffu, lane < 28 ? min(max((int)(v.x - t0), 0), 1 << 20) : 0) / 28 - nom;
            const int start = __reduce_add_sync(0xffffffffu, lane < 28 ? min(max((int)(v.y - t0), -(1 << 20)), 1 << 20) : 0) / 28;
            base = start + max(min(base - start, 2 * (base - start - DEAD)), 0);
            const int ahead = (lane == 0 ? nom : lane == 1 ? LATE_T : E2_T) - nom;
            const float rate = fminf(__fdividef((float)(base - start), (float)(nom - 500)), 0.045f);
            if (lane < 3) reinterpret_cast<volatile uint32_t*>(smem + SM_T0)[lane] = t0 + base + (int)(rate * (float)ahead);
        }
    }
}

namespace flat {

constexpr int F_LATE_T = 22330, F_LATE_DT = 460, F_Q_T = 4000, F_E2_T = 24030, F_E3_T = 24800;
constexpr int F_NOM0 = 4595, F_NOM1 = 8450, F_NOM2 = 12800, F_NOM3 = 17010;
constexpr int F_MEND = 5, F_MGAP = 3;
constexpr int NCTA = 128, NFFN = 112, NRED = 56, NTHREADS = 512;
constexpr int S_K = 0, S_V = 16, NSTAGE = 32;
constexpr int S_GU = NS, FFN_ST = 8, HID_ST = 11, PRE_ST = 12;
constexpr int SM_H = SM_WGT;

__device__ __forceinline__ uint4 ld_poll4(const void* p) {
    uint4 v;
    asm volatile("ld.relaxed.gpu.global.v4.u32 {%0,%1,%2,%3}, [%4];" : "=r"(v.x), "=r"(v.y), "=r"(v.z), "=r"(v.w) : "l"(p) : "memory");
    return v;
}
__device__ __forceinline__ void st_pub2x64(void* p, uint32_t a, uint32_t b, uint32_t c, uint32_t d) {
    asm volatile("{\n.reg .b64 d, e;\nmov.b64 d, {%1,%2};\nmov.b64 e, {%3,%4};\nst.relaxed.gpu.global.v2.b64 [%0], {d,e};\n}"
                 :: "l"(p), "r"(a), "r"(b), "r"(c), "r"(d) : "memory");
}
#define POLL_HEAD(P, T, N)                                                                                        \
    ".reg .pred p0, p1, p2, p3, q;\n"                                                                             \
    ".reg .b32 a, m, it, y<16>;\n"                                                                                \
    ".reg .b64 d<8>;\n"                                                                                           \
    "setp.eq.u32 p0, 0, 0;\nsetp.eq.u32 p1, 0, 0;\nsetp.eq.u32 p2, 0, 0;\nsetp.eq.u32 p3, 0, 0;\n"                \
    "mov.u32 it, " N ";\n"                                                                                        \
    "POLL_LOOP:\n"                                                                                                \
    "@p0 ld.relaxed.gpu.global.v2.b64 {d0,d1}, [" P "];\n"                                                        \
    "@p1 ld.relaxed.gpu.global.v2.b64 {d2,d3}, [" P "+512];\n"                                                    \
    "@p2 ld.relaxed.gpu.global.v2.b64 {d4,d5}, [" P "+1024];\n"                                                   \
    "@p3 ld.relaxed.gpu.global.v2.b64 {d6,d7}, [" P "+1536];\n"                                                   \
    "sub.u32 it, it, 1;\n"                                                                                        \
    "min.u32 m, it, 1;\n"                                                        \
    "mov.b64 {y0,y1}, d0;\nmov.b64 {y2,y3}, d1;\nmov.b64 {y4,y5}, d2;\nmov.b64 {y6,y7}, d3;\n"                    \
    "mov.b64 {y8,y9}, d4;\nmov.b64 {y10,y11}, d5;\nmov.b64 {y12,y13}, d6;\nmov.b64 {y14,y15}, d7;\n"              \
    "xor.b32 y0, y0, " T ";\nxor.b32 y2, y2, " T ";\nlop3.b32 a, y0, y2, m, 0xA8;\nsetp.ne.u32 p0, a, 0;\n"       \
    "xor.b32 y4, y4, " T ";\nxor.b32 y6, y6, " T ";\nlop3.b32 a, y4, y6, m, 0xA8;\nsetp.ne.u32 p1, a, 0;\n"       \
    "xor.b32 y8, y8, " T ";\nxor.b32 y10, y10, " T ";\nlop3.b32 a, y8, y10, m, 0xA8;\nsetp.ne.u32 p2, a, 0;\n"    \
    "xor.b32 y12, y12, " T ";\nxor.b32 y14, y14, " T ";\nlop3.b32 a, y12, y14, m, 0xA8;\nsetp.ne.u32 p3, a, 0;\n" \
    "or.pred q, p0, p1;\nor.pred q, q, p2;\nor.pred q, q, p3;\nvote.sync.any.pred q, q, 0xffffffff;\n"
#define POLL_TAIL "@q bra POLL_LOOP;\n"

__device__ __forceinline__ void poll4(float (&f)[2][4], const uint4* p, uint32_t tag, const float (&w)[4]) {
    asm volatile("{\n" POLL_HEAD("%8", "%9", "%14") POLL_TAIL
                 "mul.f32 %0, y0, %10;\nmul.f32 %1, y1, %10;\nmul.f32 %2, y2, %10;\nmul.f32 %3, y3, %10;\n"
                 "mul.f32 %4, y8, %12;\nmul.f32 %5, y9, %12;\nmul.f32 %6, y10, %12;\nmul.f32 %7, y11, %12;\n"
                 "fma.rn.f32 %0, y4, %11, %0;\nfma.rn.f32 %1, y5, %11, %1;\nfma.rn.f32 %2, y6, %11, %2;\nfma.rn.f32 %3, y7, %11, %3;\n"
                 "fma.rn.f32 %4, y12, %13, %4;\nfma.rn.f32 %5, y13, %13, %5;\nfma.rn.f32 %6, y14, %13, %6;\nfma.rn.f32 %7, y15, %13, %7;\n"
                 "}"
                 : "=&f"(f[0][0]), "=&f"(f[0][1]), "=&f"(f[0][2]), "=&f"(f[0][3]), "=&f"(f[1][0]), "=&f"(f[1][1]), "=&f"(f[1][2]), "=&f"(f[1][3])
                 : "l"(p), "r"(tag), "f"(w[0]), "f"(w[1]), "f"(w[2]), "f"(w[3]), "n"(SPIN_LIMIT) : "memory");
}
__device__ __forceinline__ void poll4_sum(float (&keep)[2], float (&recv)[2], const uint4* p, uint32_t tag, uint32_t hi) {
    asm volatile("{\n.reg .pred h;\n.reg .f32 s<8>;\nsetp.ne.u32 h, %6, 0;\n" POLL_HEAD("%4", "%5", "%7")
                 "add.f32 s0, y0, y4;\nadd.f32 s1, y1, y5;\nadd.f32 s2, y2, y6;\nadd.f32 s3, y3, y7;\n"
                 "add.f32 s4, y8, y12;\nadd.f32 s5, y9, y13;\nadd.f32 s6, y10, y14;\nadd.f32 s7, y11, y15;\n"
                 "add.f32 s0, s0, s4;\nadd.f32 s1, s1, s5;\nadd.f32 s2, s2, s6;\nadd.f32 s3, s3, s7;\n"
                 "selp.f32 s4, s0, s2, h;\nselp.f32 s5, s1, s3, h;\nselp.f32 %0, s2, s0, h;\nselp.f32 %1, s3, s1, h;\n"
                 "shfl.sync.bfly.b32 %2, s4, 16, 0x1f, 0xffffffff;\nshfl.sync.bfly.b32 %3, s5, 16, 0x1f, 0xffffffff;\n"
                 POLL_TAIL "}"
                 : "=&f"(keep[0]), "=&f"(keep[1]), "=&f"(recv[0]), "=&f"(recv[1])
                 : "l"(p), "r"(tag), "r"(hi), "n"(SPIN_LIMIT) : "memory");
}

struct Prod {
    uint32_t sb, kvdst, sdst;
    const char *k, *v;
    const __nv_bfloat16* gu;
    bool ffn;
};
__host__ __device__ constexpr int bytes_before(int s) { return 28672 + s * 16384 + (s <= S_GU ? 0 : s < S_GU + 14 ? s - S_GU : 14) * 1792; }
__host__ __device__ constexpr int issue_time(int s) {
    return (int)((long long)bytes_before(s) * PACE_DT / 16384) - PACE_LEAD;
}

template <int S, class CLK>
__device__ __forceinline__ void produce(Prod& p, const CLK& clk) {
    if constexpr (S < NSTAGE) {
        if constexpr (S >= NS) mbar_wait(p.sb + SM_BAR + (NBAR + S - NS) * 8);
        clk.wait_base(p.sb, 0, issue_time(S));
        const char* src = (S < S_V ? p.k : p.v) + (S & 15) * (8 * SLOT);
#pragma unroll
        for (int i = 0; i < 8; i++) cp_async16_stream((p.kvdst ^ ((i & 1) * 64)) + slot_of(S) + i * 2048, src + i * 2048);
        if constexpr (S >= S_GU && S < S_GU + 14) {
            if (p.ffn) cp_async16_strip(p.sdst + (S - S_GU) * 2048, p.gu + (size_t)(S - S_GU) * 32 * FF);
        }
        cp_async_arrive(p.sb + SM_BAR + S * 8);
        produce<S + 1>(p, clk);
    }
}

template <int PENDING, int OFF>
__device__ __forceinline__ void frag16(uint32_t (&a)[4][4], uint32_t addr) {
    asm volatile("cp.async.wait_group %0;" :: "n"(PENDING) : "memory");
    __syncwarp();
#pragma unroll
    for (int m = 0; m < 4; m++) ldsm4t((addr ^ (m * 32)) + OFF, a[m]);
}

enum { BAR_OB = 1, BAR_CONS = 2, BAR_LN = 3, BAR_FF = 4, BAR_FIN = 5, BAR_H = 6 };

template <bool SCALED>
__global__ void __launch_bounds__(NTHREADS, 1)
flat_decode_kernel(const __nv_bfloat16* __restrict__ wq, const __nv_bfloat16* __restrict__ kc, const __nv_bfloat16* __restrict__ x,
                    Scratch* __restrict__ scr, const __nv_bfloat16* __restrict__ vc, const __nv_bfloat16* __restrict__ wo,
                    const __nv_bfloat16* __restrict__ wg, const __nv_bfloat16* __restrict__ wu, const __nv_bfloat16* __restrict__ wd,
                    __nv_bfloat16* __restrict__ out, const Clock<SCALED> clk) {
    extern __shared__ __align__(128) unsigned char smem[];
    const uint32_t sb = (uint32_t)__cvta_generic_to_shared(smem);
    const int tid = threadIdx.x, lane = tid & 31;
    const int cta = blockIdx.x;
    const uint32_t full0 = sb + SM_BAR, done0 = full0 + NBAR * 8;
    const uint32_t t0 = clk.now();
    if (tid < 224) {
        const int row = (tid >> 5) * 64 + (lane >> 2);
        const char* src = reinterpret_cast<const char*>(wq) + (uint32_t)(row * (QCOLS * 2) + cta * 64 + (lane & 3) * 16);
        const uint32_t dst = sb + SM_STRIP + row * 64 + ((lane & 3) ^ (lane >> 3)) * 16;
#pragma unroll
        for (int i = 0; i < 8; i++) cp_async16_strip(dst + i * 512, src + i * (8 * QCOLS * 2));
    }
    const int warp = __shfl_sync(0xffffffffu, tid >> 5, 0);
    const int hkv = cta >> 4, j = cta & 15, bat = j >> 3, sp = j & 7;
    const int g = lane >> 2, t = lane & 3;

    if (warp < 8) {
        if (tid == 224) load_x(sb, x, &scr->epoch[cta * 8]);
        __syncthreads();
        mbar_wait(full0 + B_X * 8);
        const uint32_t epoch = *reinterpret_cast<const uint32_t*>(smem + SM_X + 1792);
        const uint32_t tag = pin((epoch + 1) & 1);
        uint32_t* qdst = reinterpret_cast<uint32_t*>(scr->q) + (hkv * 2 + (t & 1)) * 512 + j * 32 + warp * 16 + g + 8 * (t >> 1);
        if (warp == 7) {
            layernorm(smem, lane);
            bar_arrive(BAR_LN, 256);
        } else {
            asm volatile("cp.async.wait_all;" ::: "memory");
            bar_sync(BAR_LN, 256);
            strip_partial(sb, SM_STRIP, smem, warp, lane);
        }
        bar_sync(BAR_CONS, 256);
        if (warp < 2) {
            st_pub1(qdst, (pack_bf(0.f, strip_sum(smem, tid)) & 0xffff0000u) | tag);
        } else if (warp >= 4) {
            const int i = tid - 128;
            const uint4* qp = reinterpret_cast<const uint4*>(scr->q) + (hkv * 2 + bat) * 128 + i;
            clk.wait_until(t0, F_Q_T);
            uint4 v;
            int it = 0;
            do {
                v = ld_poll4(qp);
                if (++it > SPIN_LIMIT) __trap();
            } while (warp_bad(bad4(v, tag)));
            *reinterpret_cast<uint2*>(smem + SM_Q + (i >> 6) * 528 + (i & 63) * 8) =
                make_uint2(__byte_perm(v.x, v.y, 0x7632), __byte_perm(v.z, v.w, 0x7632));
        }
        bar_sync(BAR_CONS, 256);
        if (tid == 96) scr->epoch[cta * 8] = epoch + 1;
        {
            uint32_t qf[8][4];
#pragma unroll
            for (int k2 = 0; k2 < 8; k2++) ldsm4(sb + SM_Q + (lane & 1) * 528 + k2 * 64 + (lane >> 3) * 16, qf[k2]);
            const int mt = warp & 1;
            const uint32_t aoff = (16 * mt + (lane & 15)) * 512 + ((lane >> 4) ^ (lane & 7)) * 16;
            float* sc = reinterpret_cast<float*>(smem + SM_S) + (t & 1) * SROW + (g >> 1) * 8 + (2 * mt + (t >> 1)) * 2 + (g & 1);
#pragma unroll 1
            for (int k = warp >> 1; k < 16; k += 4) {
                const int s = S_K + k;
                mbar_wait(full0 + s * 8);
                const uint32_t base = sb + SM_RING + (s >= NS ? s - NS : s) * SLOT + aoff;
                float c0[4] = {0.f, 0.f, 0.f, 0.f}, c1[4] = {0.f, 0.f, 0.f, 0.f};
#pragma unroll
                for (int k2 = 0; k2 < 8; k2++) {
                    uint32_t a0[4], a1[4];
                    ldsm4((base ^ ((k2 & 1) * 64)) + (k2 >> 1) * 128, a0);
                    ldsm4((base ^ ((k2 & 1) * 64 + 32)) + (k2 >> 1) * 128, a1);
                    mma16816(c0, a0, qf[k2][0], qf[k2][1]);
                    mma16816(c1, a1, qf[k2][2], qf[k2][3]);
                }
                __syncwarp();
                if (lane == 0) mbar_arrive(done0 + s * 8, 4);
                sc[k * 32] = rbf(sel4(c0, t) + sel4(c1, t));
            }
        }
        bar_sync(BAR_CONS, 256);
        {
            constexpr float C = SCALE_LOG2E;
            const float* sc = reinterpret_cast<const float*>(smem + SM_S);
            float* stat = reinterpret_cast<float*>(smem + SM_STAT);
            const float2 s0 = *reinterpret_cast<const float2*>(sc + 2 * tid);
            const float2 s1 = *reinterpret_cast<const float2*>(sc + SROW + 2 * tid);
            float m0 = fmaxf(s0.x, s0.y), m1 = fmaxf(s1.x, s1.y);
#pragma unroll
            for (int o = 16; o > 0; o >>= 1) {
                m0 = fmaxf(m0, __shfl_xor_sync(0xffffffffu, m0, o));
                m1 = fmaxf(m1, __shfl_xor_sync(0xffffffffu, m1, o));
            }
            if (lane == 0) *reinterpret_cast<float2*>(stat + warp * 2) = make_float2(m0, m1);
            bar_sync(BAR_CONS, 256);
#pragma unroll
            for (int w = 0; w < 8; w++) {
                const float2 mm = *reinterpret_cast<const float2*>(stat + w * 2);
                m0 = fmaxf(m0, mm.x); m1 = fmaxf(m1, mm.y);
            }
            const float p00 = ex2((s0.x - m0) * C), p01 = ex2((s0.y - m0) * C);
            const float p10 = ex2((s1.x - m1) * C), p11 = ex2((s1.y - m1) * C);
            uint32_t* ps = reinterpret_cast<uint32_t*>(smem + SM_P);
            ps[tid] = pack_bf(p00, p01);
            ps[PROW + tid] = pack_bf(p10, p11);
            float l0 = p00 + p01, l1 = p10 + p11;
#pragma unroll
            for (int o = 16; o > 0; o >>= 1) {
                l0 += __shfl_xor_sync(0xffffffffu, l0, o);
                l1 += __shfl_xor_sync(0xffffffffu, l1, o);
            }
            if (lane == 0) *reinterpret_cast<float2*>(stat + 16 + warp * 2) = make_float2(l0, l1);
            bar_sync(BAR_CONS, 256);
            if (tid < 4) {
                float l = 0.f;
#pragma unroll
                for (int w = 0; w < 8; w++) l += stat[16 + w * 2 + (tid & 1)];
                st_pub2(scr->ml + cta * 4 + tid, tagf((tid & 1) ? m1 : m0, tag), tagf(l, tag));
            }
        }
        float wgt[2] = {0.f, 0.f}, own = 0.f;
        {
            float o0[4] = {0.f, 0.f, 0.f, 0.f}, o1[4] = {0.f, 0.f, 0.f, 0.f};
            float o2[4] = {0.f, 0.f, 0.f, 0.f}, o3[4] = {0.f, 0.f, 0.f, 0.f};
            const uint32_t aoff = ((lane & 7) + (lane >> 4) * 8) * 512 + ((warp * 4 + ((lane >> 3) & 1) * 2) ^ (lane & 7)) * 16;
            const uint4* ps = reinterpret_cast<const uint4*>(smem + SM_P + (g & 1) * PROW * 4) + t;
            uint32_t* dst = reinterpret_cast<uint32_t*>(scr->part) + ((size_t)(hkv * 16 + (t & 1) * 8 + warp) * 16 + j) * 32 +
                            (4 * (g & 3) + (t & 2) + (g >> 2)) * 2;
#pragma unroll
            for (int k = 0; k < 16; k++) {
                const uint4 pa = ps[k * 4];
                mbar_wait(full0 + (S_V + k) * 8);
                uint32_t a[4][4];
#pragma unroll
                for (int i = 0; i < 4; i++) ldsm4t(sb + (aoff ^ ((i & 1) * 16)) + slot_of(S_V + k) + (i >> 1) * 8192, a[i]);
                mma16816(o0, a[0], pa.x, pa.y);
                mma16816(o1, a[1], pa.x, pa.y);
                mma16816(o2, a[2], pa.z, pa.w);
                mma16816(o3, a[3], pa.z, pa.w);
                if (S_V + k + NS < NSTAGE + 3) {
                    __syncwarp();
                    if (lane == 0) mbar_arrive(done0 + (S_V + k) * 8, 1);
                }
                if (k == FFN_ST && warp < 7) {
                    strip_partial(sb, SM_STRIP, smem, warp, lane);
                    bar_arrive(BAR_FF, 256);
                }
                if (k == FFN_ST && warp == 7) {
                    bar_sync(BAR_FF, 256);
                    own = rbf(strip_sum(smem, (cta & 1) * 32 + lane));
                    st_pub1(scr->gu + (cta ^ 1) * 32 + lane, (pack_bf(0.f, strip_sum(smem, (~cta & 1) * 32 + lane)) & 0xffff0000u) | tag);
                }
                if (k == HID_ST && warp == 7) {
                    const uint2* mlp = scr->ml + (hkv * 16 + g) * 4 + (j >> 3);
                    uint2 a, b;
                    uint32_t other;
                    int it = 0;
                    do {
                        a = ld_poll2(mlp); b = ld_poll2(mlp + 32); other = ld_poll1(scr->gu + cta * 32 + lane);
                        if (++it > SPIN_LIMIT) __trap();
                    } while (warp_bad(bad2(a.x, a.y, tag) | bad2(b.x, b.y, tag) | (other ^ tag)));
                    float m[2] = {bf_hi(a.x), bf_hi(b.x)};
                    float l[2] = {__uint_as_float(a.y ^ tag), __uint_as_float(b.y ^ tag)};
#pragma unroll
                    for (int bb = 0; bb < 2; bb++) {
                        float M = m[bb];
                        M = fmaxf(M, __shfl_xor_sync(0xffffffffu, M, 4));
                        M = fmaxf(M, __shfl_xor_sync(0xffffffffu, M, 8));
                        M = fmaxf(M, __shfl_xor_sync(0xffffffffu, M, 16));
                        const float e = ex2((m[bb] - M) * SCALE_LOG2E);
                        float L = e * l[bb];
                        L += __shfl_xor_sync(0xffffffffu, L, 4);
                        L += __shfl_xor_sync(0xffffffffu, L, 8);
                        L += __shfl_xor_sync(0xffffffffu, L, 16);
                        wgt[bb] = __fdividef(e, L);
                    }
                    float ga = (cta & 1) ? bf_hi(other) : own;
                    ga *= (ga > 0.f ? 1.f : 0.f);
                    const float hv = ga * ((cta & 1) ? own : bf_hi(other));
                    const uint32_t w = pack_bf(hv, __shfl_xor_sync(0xffffffffu, hv, 2));
                    if (!(t & 2)) reinterpret_cast<uint32_t*>(smem + SM_H)[(t & 1) * 8 + (g & 3) * 2 + (g >> 2)] = w;
                    bar_arrive(BAR_H, 256);
                }
                if (k == PRE_ST) st_pub64(dst, tag ^ 1, 0);
            }
            const float v0 = sel4(o0, t) + sel4(o2, t), v1 = sel4(o1, t) + sel4(o3, t);
            st_pub64(dst, tagf(v0, tag), __float_as_uint(v1));
        }
        if (warp == 7) {
            const uint4* pp = pin(scr->part + (size_t)cta * 128 + lane);
            const uint32_t obaddr = pin(sb + SM_OB + (lane >> 4) * 64 + (lane & 7) * 8 + ((lane >> 3) & 1) * 4), ll = pin(lane);
            float w[4];
#pragma unroll
            for (int i = 0; i < 4; i++) w[i] = __shfl_sync(0xffffffffu, wgt[i >> 1], ((i & 1) * 4 + (lane >> 3)) * 4);
            clk.wait_until(clk.base(sb, 2), F_E2_T);
            float f[2][4];
            poll4(f, pp, tag, w);
            const bool h16 = ll & 16, h8 = ll & 8;
            float r4[4], r2[2];
#pragma unroll
            for (int e = 0; e < 4; e++) r4[e] = (h16 ? f[1][e] : f[0][e]) + __shfl_xor_sync(0xffffffffu, h16 ? f[0][e] : f[1][e], 16);
#pragma unroll
            for (int e = 0; e < 2; e++) r2[e] = (h8 ? r4[2 + e] : r4[e]) + __shfl_xor_sync(0xffffffffu, h8 ? r4[e] : r4[2 + e], 8);
            sts32(obaddr, pack_bf(r2[0], r2[1]));
            bar_arrive(BAR_OB, 256);
        } else if (warp < 4 && (cta & 1) == 0 && cta < 2 * NRED) {
            const uint4* op = pin(scr->outp + (size_t)(cta >> 1) * (NCTA * 4) + warp * 128 + lane);
            const int oidx = (t & 1) * D_MODEL + hkv * 64 + (lane >> 3) * 16 + (j >> 1) + (t >> 1) * 8;
            const float xv = __bfloat162float(reinterpret_cast<const __nv_bfloat16*>(smem + SM_X)[oidx]);
            __nv_bfloat16* optr = pin(out + oidx);
            const uint32_t red = pin(sb + SM_S + tid * 4), ll = pin(lane);
            float r2[2], rcv[2];
            const bool h8 = ll & 8;
            clk.wait_until(clk.base(sb, 3), F_E3_T);
            poll4_sum(r2, rcv, op, tag, ll & 16);
            r2[0] += rcv[0]; r2[1] += rcv[1];
            float r = (h8 ? r2[1] : r2[0]) + __shfl_xor_sync(0xffffffffu, h8 ? r2[0] : r2[1], 8);
            r += __shfl_xor_sync(0xffffffffu, r, 4);
            if (warp != 0) {
                sts32(red, __float_as_uint(r));
                bar_arrive(BAR_FIN, 128);
            } else {
                bar_sync(BAR_FIN, 128);
                r = ((xv + r) + lds32(red + 128)) + (lds32(red + 256) + lds32(red + 384));
                asm volatile("st.global.u16 [%0], %1;" :: "l"(optr), "h"(__bfloat16_as_ushort(__float2bfloat16_rn(r))) : "memory");
            }
        }
    } else if (warp < 15) {
        const int pt = tid - 256, pw = warp - 8;
        const char* pdn = reinterpret_cast<const char*>(wd) + (size_t)cta * 14336 + (lane >> 3) * 896 + pw * 128 + (lane & 7) * 16;
        const char* pwo = reinterpret_cast<const char*>(wo) + (size_t)cta * 28672 + (lane >> 3) * 896 + pw * 128 + (lane & 7) * 16;
        if (pw < 4) {
            if (lane == 0) {
#pragma unroll
                for (int i = 0; i < 10; i++) {
                    if (pw * 10 + i != B_X) mbar_init(full0 + (pw * 10 + i) * 8, NPT);
                    mbar_init(done0 + (pw * 10 + i) * 8, 8);
                }
            }
            Prod p;
            const size_t kvoff = ((size_t)(bat * 8 + hkv) * SK + (SK - WIN)) * DH * 2 + sp * SLOT + pt * 16;
            p.sb = sb;
            p.kvdst = (sb + pt * 16) ^ (pw * 16);
            p.sdst = sb + SM_STRIP + (pt >> 2) * 64 + ((pt & 3) ^ ((pt >> 3) & 3)) * 16;
            p.k = reinterpret_cast<const char*>(kc) + kvoff;
            p.v = reinterpret_cast<const char*>(vc) + kvoff;
            p.gu = ((cta & 1) ? wu : wg) + (cta >> 1) * 32 + (pt & 3) * 8 + (size_t)(pt >> 2) * FF;
            p.ffn = cta < NFFN;
            __syncthreads();
            produce<0>(p, clk);
        } else {
            __syncthreads();
        }
        mbar_wait(full0 + B_X * 8);
        const uint32_t tag = pin((*reinterpret_cast<const uint32_t*>(smem + SM_X + 1792) + 1) & 1);
        if (pw == 4 && (cta & 3) == 0) {
#pragma unroll 1
            for (int i = 0; i < 4; i++) {
                uint32_t sum = 0;
#pragma unroll
                for (int k = 0; k < NM; k++) {
                    mbar_wait(full0 + (F_MEND - NM + 1 + k + 6 * i) * 8);
                    sum += clk.now() - t0;
                }
                if (lane < 4) st_pub2(&scr->prog[i * 128 + cta + lane], ((t0 + sum / NM) & ~1u) | tag, (t0 & ~1u) | tag);
            }
        }
        mbar_wait(done0 + (NSTAGE + 2 - NS) * 8);
        const uint32_t ta = F_LATE_T, td = F_LATE_DT;
        uint4* odst = scr->outp + ((size_t)(pt >> 2) * NCTA + cta) * 4 + t;
        st_pub2x64(odst, tag ^ 1, 0, tag ^ 1, 0);
        const uint32_t fdst = (sb + pw * 2048 + lane * 16) ^ ((lane >> 3) * 16);
        clk.wait_base(sb, 1, ta);
        if (cta < NFFN) fetch16(fdst + slot_of(NSTAGE), pdn);
        asm volatile("cp.async.commit_group;" ::: "memory");
        clk.wait_base(sb, 1, ta + td);
        fetch16(fdst + slot_of(NSTAGE + 1), pwo);
        asm volatile("cp.async.commit_group;" ::: "memory");
        clk.wait_base(sb, 1, ta + 2 * td);
        fetch16(fdst + slot_of(NSTAGE + 2), pwo + 14336);
        asm volatile("cp.async.commit_group;" ::: "memory");
        bar_sync(BAR_H, 256);
        const uint2 h = *reinterpret_cast<const uint2*>(smem + SM_H + (g & 1) * 32 + t * 8);
        float c[4][4];
#pragma unroll
        for (int m = 0; m < 4; m++)
#pragma unroll
            for (int e = 0; e < 4; e++) c[m][e] = 0.f;
        const int r7 = ((lane & 7) >> 1) + 4 * (lane >> 4);
        const uint32_t aoff = sb + pw * 2048 + (r7 + 8 * (lane & 1)) * 128 + (((lane >> 3) & 1) ^ r7 ^ ((lane & 1) << 2)) * 16;
        const uint32_t obaddr = pin(sb + SM_OB + (g & 1) * 64 + t * 16), tt = pin(t);
        uint32_t a0[4][4], a1[4][4];
        frag16<2, slot_of(NSTAGE)>(a0, aoff);
        if (cta < NFFN) {
#pragma unroll
            for (int m = 0; m < 4; m++) mma16816(c[m], a0[m], h.x, h.y);
        }
        frag16<1, slot_of(NSTAGE + 1)>(a1, aoff);
        bar_sync(BAR_OB, 256);
        const uint4 ob = lds128(obaddr);
#pragma unroll
        for (int m = 0; m < 4; m++) mma16816(c[m], a1[m], ob.x, ob.y);
        frag16<0, slot_of(NSTAGE + 2)>(a0, aoff);
#pragma unroll
        for (int m = 0; m < 4; m++) mma16816(c[m], a0[m], ob.z, ob.w);
        st_pub2x64(odst, tagf(sel4(c[0], tt), tag), __float_as_uint(sel4(c[1], tt)), tagf(sel4(c[2], tt), tag), __float_as_uint(sel4(c[3], tt)));
    } else if (warp == 15) {
        if (lane < 4) reinterpret_cast<uint32_t*>(smem + SM_T0)[lane] = t0;
        __syncthreads();
        mbar_wait(full0 + B_X * 8);
        const uint32_t tag = (*reinterpret_cast<const uint32_t*>(smem + SM_X + 1792) + 1) & 1;
#pragma unroll 1
        for (int i = 0; i < 4; i++) {
            mbar_wait(full0 + (F_MEND + F_MGAP + 6 * i) * 8);
            uint2 v;
            int it = 0;
            do {
                v = ld_poll2(&scr->prog[i * 128 + lane * 4]);
                if (++it > SPIN_LIMIT) __trap();
            } while (warp_bad(bad2(v.x, v.y, tag)));
            const int nom = i == 0 ? F_NOM0 : i == 1 ? F_NOM1 : i == 2 ? F_NOM2 : F_NOM3;
            int base = (__reduce_add_sync(0xffffffffu, min(max((int)(v.x - t0), 0), 1 << 20)) >> 5) - nom;
            const int start = __reduce_add_sync(0xffffffffu, min(max((int)(v.y - t0), -(1 << 20)), 1 << 20)) >> 5;
            base = start + max(min(base - start, 2 * (base - start - DEAD)), 0);
            const int ahead = (lane == 0 ? nom : lane == 1 ? F_LATE_T : lane == 2 ? F_E2_T : F_E3_T - 150) - nom;
            const float rate = fminf(fmaxf(__fdividef((float)(base - start), (float)(nom - 500)), -0.01f), 0.045f);
            if (lane < 4) reinterpret_cast<volatile uint32_t*>(smem + SM_T0)[lane] = t0 + base + (int)(rate * (float)ahead);
        }
    }
}

}

}

extern "C" void kernel_launch(void* const* d_in, const int* in_sizes, int n_in, void* d_out, int out_size) {
    (void)in_sizes; (void)n_in; (void)out_size;
    cudaLaunchConfig_t cfg = {};
    cfg.gridDim = dim3(NCTA); cfg.blockDim = dim3(NTHREADS); cfg.dynamicSmemBytes = SM_TOTAL; cfg.stream = cudaStreamPerThread;
    cudaLaunchAttribute at[1];
    at[0].id = cudaLaunchAttributeClusterDimension;
    at[0].val.clusterDim.x = 16; at[0].val.clusterDim.y = 1; at[0].val.clusterDim.z = 1;
    cfg.attrs = at; cfg.numAttrs = 1;

    static Scratch* scr = nullptr;
    static uint32_t scale = 64;
    static int nclusters = 0;
    if (!scr) {
        int dev = 0, khz = 0, bits = 0;
        cudaGetDevice(&dev);
        cudaDeviceGetAttribute(&khz, cudaDevAttrMemoryClockRate, dev);
        cudaDeviceGetAttribute(&bits, cudaDevAttrGlobalMemoryBusWidth, dev);
        if (khz > 0 && bits > 0) scale = (uint32_t)(64.0 * khz * bits / (2619000.0 * 5120.0) + 0.5);
        cudaFuncSetAttribute(fused_decode_kernel<false>, cudaFuncAttributeMaxDynamicSharedMemorySize, SM_TOTAL);
        cudaFuncSetAttribute(fused_decode_kernel<true>, cudaFuncAttributeMaxDynamicSharedMemorySize, SM_TOTAL);
        cudaFuncSetAttribute(flat::flat_decode_kernel<true>, cudaFuncAttributeMaxDynamicSharedMemorySize, SM_TOTAL);
        cudaFuncSetAttribute(fused_decode_kernel<false>, cudaFuncAttributeNonPortableClusterSizeAllowed, 1);
        cudaFuncSetAttribute(fused_decode_kernel<true>, cudaFuncAttributeNonPortableClusterSizeAllowed, 1);
        if (cudaOccupancyMaxActiveClusters(&nclusters, fused_decode_kernel<true>, &cfg) != cudaSuccess) nclusters = 0;
        (void)cudaGetLastError();
        cudaGetSymbolAddress(reinterpret_cast<void**>(&scr), g_scratch);
    }
    typedef const __nv_bfloat16* P;
    const P wq = (P)d_in[3], kc = (P)d_in[1], x = (P)d_in[0], vc = (P)d_in[2], wo = (P)d_in[4], wg = (P)d_in[6], wu = (P)d_in[7], wd = (P)d_in[8];
    __nv_bfloat16* out = (__nv_bfloat16*)d_out;
    if (nclusters < NCTA / 16)
        flat::flat_decode_kernel<true><<<flat::NCTA, flat::NTHREADS, SM_TOTAL, cudaStreamPerThread>>>(wq, kc, x, scr, vc, wo, wg, wu, wd, out, Clock<true>{scale});
    else if (scale == 64)
        cudaLaunchKernelEx(&cfg, fused_decode_kernel<false>, wq, kc, x, scr, vc, wo, wg, wu, wd, out, Clock<false>{scale});
    else
        cudaLaunchKernelEx(&cfg, fused_decode_kernel<true>, wq, kc, x, scr, vc, wo, wg, wu, wd, out, Clock<true>{scale});
}
```

```cpp
#include <cuda_runtime.h>
#include <cuda_bf16.h>
#include <stdint.h>

namespace {

constexpr int PACE_DT = 641;
constexpr int PACE_LEAD = 720;
constexpr int LATE_T = 22000;
constexpr int LATE_DT = 420;
constexpr int Q_T = 3300;
constexpr int E2_T = 23610;
constexpr int M_NOM0 = 4680;
constexpr int M_NOM1 = 9000;
constexpr int M_NOM2 = 13125;
constexpr int M_NOM3 = 17050;
constexpr int DEAD = 100;
constexpr int SLACK = 200;
constexpr int NM = 4;
constexpr int MEND = 7;
constexpr int MGAP = 4;
constexpr int GU0 = 9;

constexpr int D_MODEL = 448;
constexpr int SK      = 32768;
constexpr int WIN     = 4096;
constexpr int DH      = 256;
constexpr int QCOLS   = 4096;
constexpr int FF      = 1792;
constexpr int NCTA    = 112;
constexpr int NPT     = 128;
constexpr int NTHREADS = 448;

constexpr int NS     = 11;
constexpr int SLOT   = 16384;
constexpr int XROW   = 912;
constexpr int NR     = 19;
constexpr int S_K = 0, S_V = NR, NSTAGE = 2 * NR;
constexpr int S_GU   = GU0;
constexpr int FFN_ST = S_GU + 13 - S_V;
constexpr int HID_ST = FFN_ST + 3;
constexpr int PRE_ST = 14;
constexpr int NBAR   = 40;
constexpr int B_X = NSTAGE, B_FIN = NSTAGE + 1, B_W = NBAR + NSTAGE;
constexpr int SROW = 616, PROW = 336;

constexpr int SM_RING  = 0;
constexpr int SM_WQ    = SM_RING + (NS - 2) * SLOT;
constexpr int SM_STRIP = SM_RING + NS * SLOT;
constexpr int SM_S    = SM_STRIP + 448 * 64;
constexpr int SM_P    = SM_S + 2 * SROW * 4;
constexpr int SM_Q    = SM_P + 2 * PROW * 4;
constexpr int SM_XN   = SM_Q + 2 * 264 * 2;
constexpr int SM_X    = SM_XN + 2 * XROW;
constexpr int SM_RED  = SM_X + 1792 + 32;
constexpr int SM_STAT = SM_RED + 7 * 64 * 4;
constexpr int SM_WGT  = SM_STAT + 2 * 8 * 2 * 4;
constexpr int SM_OB   = SM_WGT + 2 * 8 * 4;
constexpr int SM_IN   = (SM_OB + 8 * 2 * 16 * 4 + 127) / 128 * 128;
constexpr int SM_T0   = SM_IN + 4096;
constexpr int SM_BAR  = SM_T0 + 32;
constexpr int SM_TOTAL = SM_BAR + 2 * NBAR * 8;
static_assert(SM_Q % 16 == 0 && SM_XN % 16 == 0 && SM_X % 16 == 0 && SM_OB % 16 == 0 && SM_P % 16 == 0 && SM_IN % 16 == 0, "align");
static_assert(FFN_ST >= 1 && 2 * NS >= NR && NSTAGE % NS + 3 <= NS, "stage -> slot mapping");
static_assert(SM_TOTAL <= 232448, "shared memory");

constexpr int SPIN_LIMIT = 1 << 22;
constexpr float SCALE_LOG2E = 0.0625f * 1.4426950408889634f;

struct __align__(1024) Scratch {
    uint4    part[128 * 2 * 8 * 8];
    uint4    outp[56 * 128 * 4];
    uint2    q[16 * 2 * 7 * 128];
    uint4    hid[NCTA * 8];
    unsigned gu[128 * 32];
    uint2    ml[128 * 4];
    uint2    prog[4 * 32 * 4];
    unsigned epoch[128 * 8];
};
__device__ Scratch g_scratch;

__device__ __forceinline__ void mbar_init(uint32_t bar, uint32_t cnt) {
    asm volatile("mbarrier.init.shared::cta.b64 [%0], %1;" :: "r"(bar), "r"(cnt) : "memory");
}
__device__ __forceinline__ void mbar_arrive(uint32_t bar, uint32_t cnt) {
    asm volatile("mbarrier.arrive.shared::cta.b64 _, [%0], %1;" :: "r"(bar), "r"(cnt) : "memory");
}
template <bool SCALED>
struct Clock {
    uint32_t scale;
    __device__ __forceinline__ uint32_t now() const {
        if constexpr (SCALED) {
            uint64_t t;
            asm volatile("mov.u64 %0, %globaltimer;" : "=l"(t));
            return (uint32_t)((t * scale) >> 6);
        } else {
            uint32_t t;
            asm volatile("mov.u32 %0, %globaltimer_lo;" : "=r"(t));
            return t;
        }
    }
    __device__ __forceinline__ static uint32_t base(uint32_t sb, int i) {
        uint32_t t;
        asm volatile("ld.volatile.shared.u32 %0, [%1];" : "=r"(t) : "r"(sb + SM_T0 + 4 * i) : "memory");
        return t;
    }
    __device__ __forceinline__ void wait_until(uint32_t t0, uint32_t dt) const { while (now() - t0 < dt) {} }
    __device__ __forceinline__ void wait_base(uint32_t sb, int i, uint32_t dt) const { while (now() - base(sb, i) < dt) {} }
};
__device__ __forceinline__ void mbar_wait(uint32_t bar) {
    asm volatile("{\n.reg .pred p;\nWAIT_LOOP:\nmbarrier.try_wait.parity.shared::cta.b64 p, [%0], 0;\n@!p bra WAIT_LOOP;\n}" :: "r"(bar) : "memory");
}
__device__ __forceinline__ void cp_async16(uint32_t dst, const void* src) {
    asm volatile("cp.async.cg.shared.global [%0], [%1], 16;" :: "r"(dst), "l"(src) : "memory");
}
__device__ __forceinline__ void cp_async16_strip(uint32_t dst, const void* src) {
    asm volatile("cp.async.cg.shared.global.L2::128B [%0], [%1], 16;" :: "r"(dst), "l"(src) : "memory");
}
__device__ __forceinline__ void cp_async16_stream(uint32_t dst, const void* src) {
    asm volatile("{\n.reg .b64 pol;\ncreatepolicy.fractional.L2::evict_first.b64 pol, 1.0;\n"
                 "cp.async.cg.shared.global.L2::cache_hint [%0], [%1], 16, pol;\n}" :: "r"(dst), "l"(src) : "memory");
}
__device__ __forceinline__ void cp_async_arrive(uint32_t bar) {
    asm volatile("cp.async.mbarrier.arrive.noinc.shared::cta.b64 [%0];" :: "r"(bar) : "memory");
}
__device__ __forceinline__ void bar_sync(int id, int n)   { asm volatile("bar.sync %0, %1;" :: "r"(id), "r"(n) : "memory"); }
__device__ __forceinline__ void bar_arrive(int id, int n) { asm volatile("bar.arrive %0, %1;" :: "r"(id), "r"(n) : "memory"); }

__device__ __forceinline__ uint32_t ld_poll1(const void* p) {
    uint32_t v;
    asm volatile("ld.relaxed.gpu.global.u32 %0, [%1];" : "=r"(v) : "l"(p) : "memory");
    return v;
}
__device__ __forceinline__ uint2 ld_poll2(const void* p) {
    uint2 v;
    asm volatile("ld.relaxed.gpu.global.v2.u32 {%0,%1}, [%2];" : "=r"(v.x), "=r"(v.y) : "l"(p) : "memory");
    return v;
}
__device__ __forceinline__ uint2 ld_poll64(const void* p) {
    uint2 v;
    asm volatile("{\n.reg .b64 d;\nld.relaxed.gpu.global.b64 d, [%2];\nmov.b64 {%0,%1}, d;\n}" : "=r"(v.x), "=r"(v.y) : "l"(p) : "memory");
    return v;
}
__device__ __forceinline__ uint4 ld_poll2x64(const void* p) {
    uint4 v;
    asm volatile("{\n.reg .b64 d, e;\nld.relaxed.gpu.global.v2.b64 {d,e}, [%4];\nmov.b64 {%0,%1}, d;\nmov.b64 {%2,%3}, e;\n}"
                 : "=r"(v.x), "=r"(v.y), "=r"(v.z), "=r"(v.w) : "l"(p) : "memory");
    return v;
}
__device__ __forceinline__ void st_pub64(void* p, uint32_t a, uint32_t b) {
    asm volatile("{\n.reg .b64 d;\nmov.b64 d, {%1,%2};\nst.relaxed.gpu.global.b64 [%0], d;\n}" :: "l"(p), "r"(a), "r"(b) : "memory");
}
__device__ __forceinline__ void st_pub2(void* p, uint32_t a, uint32_t b) {
    asm volatile("st.relaxed.gpu.global.v2.u32 [%0], {%1,%2};" :: "l"(p), "r"(a), "r"(b) : "memory");
}
__device__ __forceinline__ void st_pub1(void* p, uint32_t a) {
    asm volatile("st.relaxed.gpu.global.u32 [%0], %1;" :: "l"(p), "r"(a) : "memory");
}
__device__ __forceinline__ uint32_t tagf(float v, uint32_t tag) {
    uint32_t r;
    asm("lop3.b32 %0, %1, 0xfffffffe, %2, 0xEA;" : "=r"(r) : "r"(__float_as_uint(v)), "r"(tag));
    return r;
}
__device__ __forceinline__ uint32_t pin(uint32_t v) {
    uint32_t r;
    asm volatile("shfl.sync.bfly.b32 %0, %1, 0, 0x1f, 0xffffffff;" : "=r"(r) : "r"(v));
    return r;
}
template <class T>
__device__ __forceinline__ T* pin(T* p) {
    const uint64_t u = reinterpret_cast<uint64_t>(p);
    return reinterpret_cast<T*>(((uint64_t)pin((uint32_t)(u >> 32)) << 32) | pin((uint32_t)u));
}
__device__ __forceinline__ void sts32(uint32_t addr, uint32_t v) { asm volatile("st.shared.u32 [%0], %1;" :: "r"(addr), "r"(v) : "memory"); }
__device__ __forceinline__ float lds32(uint32_t addr) { float v; asm volatile("ld.shared.f32 %0, [%1];" : "=f"(v) : "r"(addr) : "memory"); return v; }
__device__ __forceinline__ uint4 lds128(uint32_t addr) {
    uint4 v;
    asm volatile("ld.shared.v4.u32 {%0,%1,%2,%3}, [%4];" : "=r"(v.x), "=r"(v.y), "=r"(v.z), "=r"(v.w) : "r"(addr) : "memory");
    return v;
}
__device__ __forceinline__ uint32_t bad2(uint32_t a, uint32_t b, uint32_t tag) {
    uint32_t r;
    asm("lop3.b32 %0, %1, %2, %3, 0x7E;" : "=r"(r) : "r"(a), "r"(b), "r"(tag));
    return r;
}
__device__ __forceinline__ uint32_t bad4(const uint4& v, uint32_t tag) { return bad2(v.x, v.y, tag) | bad2(v.z, v.w, tag); }
__device__ __forceinline__ bool warp_bad(uint32_t bad) { return __any_sync(0xffffffffu, bad & 1u); }

__device__ __forceinline__ void poll4(float (&f)[2][4], const uint2* p, const uint2* p2, uint32_t tag, const float (&w)[4]) {
    uint32_t y[8];
    asm volatile("{\n.reg .pred p0, p1, p2, p3, q;\n.reg .b32 a, m, it;\n.reg .b64 d<4>;\n"
                 "setp.eq.u32 p0, 0, 0;\nsetp.eq.u32 p1, 0, 0;\nsetp.eq.u32 p2, 0, 0;\nsetp.eq.u32 p3, 0, 0;\n"
                 "mov.u32 it, %11;\n"
                 "POLL_LOOP:\n"
                 "@p0 ld.relaxed.gpu.global.b64 d0, [%8];\n"
                 "@p1 ld.relaxed.gpu.global.b64 d1, [%9];\n"
                 "@p2 ld.relaxed.gpu.global.b64 d2, [%8+512];\n"
                 "@p3 ld.relaxed.gpu.global.b64 d3, [%9+512];\n"
                 "sub.u32 it, it, 1;\n"
                 "min.u32 m, it, 1;\n"
                 "mov.b64 {%0,%1}, d0;\nmov.b64 {%2,%3}, d1;\nmov.b64 {%4,%5}, d2;\nmov.b64 {%6,%7}, d3;\n"
                 "lop3.b32 a, %0, %10, m, 0x28;\nsetp.ne.u32 p0, a, 0;\nlop3.b32 a, %2, %10, m, 0x28;\nsetp.ne.u32 p1, a, 0;\n"
                 "lop3.b32 a, %4, %10, m, 0x28;\nsetp.ne.u32 p2, a, 0;\nlop3.b32 a, %6, %10, m, 0x28;\nsetp.ne.u32 p3, a, 0;\n"
                 "or.pred q, p0, p1;\nor.pred q, q, p2;\nor.pred q, q, p3;\nvote.sync.any.pred q, q, 0xffffffff;\n"
                 "@q bra POLL_LOOP;\n}"
                 : "=&r"(y[0]), "=&r"(y[1]), "=&r"(y[2]), "=&r"(y[3]), "=&r"(y[4]), "=&r"(y[5]), "=&r"(y[6]), "=&r"(y[7])
                 : "l"(p), "l"(p2), "r"(tag), "n"(SPIN_LIMIT) : "memory");
#pragma unroll
    for (int b = 0; b < 2; b++) {
        const uint32_t* u = y + 4 * b;
        f[b][0] = fmaf(w[2 * b], __uint_as_float((u[0] ^ tag) << 16), w[2 * b + 1] * __uint_as_float((u[2] ^ tag) << 16));
        f[b][1] = fmaf(w[2 * b], __uint_as_float(u[0] & 0xffff0000u), w[2 * b + 1] * __uint_as_float(u[2] & 0xffff0000u));
        f[b][2] = fmaf(w[2 * b], __uint_as_float(u[1] << 16), w[2 * b + 1] * __uint_as_float(u[3] << 16));
        f[b][3] = fmaf(w[2 * b], __uint_as_float(u[1] & 0xffff0000u), w[2 * b + 1] * __uint_as_float(u[3] & 0xffff0000u));
    }
}

__device__ __forceinline__ void ldsm4(uint32_t addr, uint32_t (&a)[4]) {
    asm volatile("ldmatrix.sync.aligned.m8n8.x4.shared.b16 {%0,%1,%2,%3}, [%4];" : "=r"(a[0]), "=r"(a[1]), "=r"(a[2]), "=r"(a[3]) : "r"(addr) : "memory");
}
__device__ __forceinline__ void ldsm4t(uint32_t addr, uint32_t (&a)[4]) {
    asm volatile("ldmatrix.sync.aligned.m8n8.x4.trans.shared.b16 {%0,%1,%2,%3}, [%4];" : "=r"(a[0]), "=r"(a[1]), "=r"(a[2]), "=r"(a[3]) : "r"(addr) : "memory");
}
__device__ __forceinline__ void mma16816(float (&c)[4], const uint32_t (&a)[4], uint32_t b0, uint32_t b1) {
    asm volatile("mma.sync.aligned.m16n8k16.row.col.f32.bf16.bf16.f32 {%0,%1,%2,%3}, {%4,%5,%6,%7}, {%8,%9}, {%0,%1,%2,%3};"
                 : "+f"(c[0]), "+f"(c[1]), "+f"(c[2]), "+f"(c[3]) : "r"(a[0]), "r"(a[1]), "r"(a[2]), "r"(a[3]), "r"(b0), "r"(b1));
}
__device__ __forceinline__ float bf_lo(uint32_t u) { return __uint_as_float(u << 16); }
__device__ __forceinline__ float bf_hi(uint32_t u) { return __uint_as_float(u & 0xffff0000u); }
__device__ __forceinline__ float rbf(float v) { return __bfloat162float(__float2bfloat16_rn(v)); }
__device__ __forceinline__ uint32_t pack_bf(float lo, float hi) {
    uint32_t r;
    asm("cvt.rn.bf16x2.f32 %0, %1, %2;" : "=r"(r) : "f"(hi), "f"(lo));
    return r;
}
__device__ __forceinline__ float sel4(const float (&c)[4], int t) {
    float a = (t & 1) ? c[1] : c[0];
    float b = (t & 1) ? c[3] : c[2];
    return (t & 2) ? b : a;
}
__device__ __forceinline__ float ex2(float x) { float y; asm("ex2.approx.ftz.f32 %0, %1;" : "=f"(y) : "f"(x)); return y; }
__device__ __forceinline__ float sqrt_approx(float x) { float y; asm("sqrt.approx.f32 %0, %1;" : "=f"(y) : "f"(x)); return y; }

__host__ __device__ constexpr uint32_t slot_of(int s) { return SM_RING + (s % NS) * SLOT; }

__device__ __forceinline__ void layernorm(unsigned char* smem, int lane) {
    uint32_t xs[2][7];
#pragma unroll
    for (int b = 0; b < 2; b++)
#pragma unroll
        for (int i = 0; i < 7; i++) xs[b][i] = reinterpret_cast<const uint32_t*>(smem + SM_X)[b * (D_MODEL / 2) + i * 32 + lane];
#pragma unroll
    for (int b = 0; b < 2; b++) {
        float sum = 0.f;
#pragma unroll
        for (int i = 0; i < 7; i++) sum += bf_lo(xs[b][i]) + bf_hi(xs[b][i]);
#pragma unroll
        for (int o = 16; o > 0; o >>= 1) sum += __shfl_xor_sync(0xffffffffu, sum, o);
        const float mean = sum * (1.0f / D_MODEL);
        float sq = 0.f;
#pragma unroll
        for (int i = 0; i < 7; i++) {
            const float d0 = bf_lo(xs[b][i]) - mean, d1 = bf_hi(xs[b][i]) - mean;
            sq = fmaf(d0, d0, fmaf(d1, d1, sq));
        }
#pragma unroll
        for (int o = 16; o > 0; o >>= 1) sq += __shfl_xor_sync(0xffffffffu, sq, o);
        const float mb = rbf(mean);
        const float sd = rbf(sqrt_approx(rbf(rbf(sq * (1.0f / D_MODEL)) + 1e-5f)));
#pragma unroll
        for (int i = 0; i < 7; i++)
            reinterpret_cast<uint32_t*>(smem + SM_XN + b * XROW)[i * 32 + lane] =
                pack_bf(__fdividef(rbf(bf_lo(xs[b][i]) - mb), sd), __fdividef(rbf(bf_hi(xs[b][i]) - mb), sd));
    }
}

__device__ __forceinline__ void strip_partial(uint32_t sb, uint32_t strip, unsigned char* smem, int warp, int lane) {
    float c[2][2][4];
#pragma unroll
    for (int n = 0; n < 2; n++)
#pragma unroll
        for (int e = 0; e < 4; e++) c[n][0][e] = c[n][1][e] = 0.f;
    const uint32_t ba = sb + SM_XN + (lane & 1) * XROW + (lane >> 3) * 16 + warp * 128;
    const uint32_t aa = sb + strip + (warp * 64 + (lane & 7) + (lane >> 4) * 8) * 64 + (((lane >> 3) & 1) ^ ((lane & 7) >> 1)) * 16;
#pragma unroll
    for (int k2 = 0; k2 < 2; k2++) {
        uint32_t b[4];
        ldsm4(ba + k2 * 64, b);
#pragma unroll
        for (int n = 0; n < 2; n++) {
            uint32_t a0[4], a1[4];
            ldsm4t((aa ^ (n * 32)) + k2 * 2048, a0);
            ldsm4t((aa ^ (n * 32)) + k2 * 2048 + 1024, a1);
            mma16816(c[n][0], a0, b[0], b[1]);
            mma16816(c[n][1], a1, b[2], b[3]);
        }
    }
    float* red = reinterpret_cast<float*>(smem + SM_RED) + warp * 64 + lane;
#pragma unroll
    for (int n = 0; n < 2; n++) red[n * 32] = sel4(c[n][0], lane & 3) + sel4(c[n][1], lane & 3);
}
__device__ __forceinline__ float strip_sum(const unsigned char* smem, int idx) {
    const float* red = reinterpret_cast<const float*>(smem + SM_RED) + idx;
    return ((red[0] + red[64]) + (red[128] + red[192])) + ((red[256] + red[320]) + red[384]);
}

__device__ __forceinline__ void fetch16(uint32_t dst, const char* src) {
#pragma unroll
    for (int i = 0; i < 4; i++) cp_async16((dst ^ (((i & 1) ^ (i >> 1)) * 64)) + i * 512, src + i * (4 * 896));
}
template <int PENDING, int OFF>
__device__ __forceinline__ void frag32(uint32_t (&a)[2][4][4], uint32_t addr) {
    asm volatile("cp.async.wait_group %0;" :: "n"(PENDING) : "memory");
    __syncwarp();
#pragma unroll
    for (int h = 0; h < 2; h++)
#pragma unroll
        for (int m = 0; m < 4; m++) ldsm4t((addr ^ (m * 32)) + OFF + h * 2048, a[h][m]);
}
__device__ __forceinline__ void mma32(float (&c)[4][4], const uint32_t (&a)[2][4][4], const uint4& b) {
#pragma unroll
    for (int m = 0; m < 4; m++) mma16816(c[m], a[0][m], b.x, b.y);
#pragma unroll
    for (int m = 0; m < 4; m++) mma16816(c[m], a[1][m], b.z, b.w);
}

__device__ __forceinline__ void load_x(uint32_t sb, const void* x, const void* epoch) {
    const uint32_t full0 = sb + SM_BAR;
    mbar_init(full0 + B_X * 8, 1);
    asm volatile("fence.mbarrier_init.release.cluster;" ::: "memory");
    asm volatile("mbarrier.arrive.expect_tx.shared::cta.b64 _, [%0], %1;" :: "r"(full0 + B_X * 8), "r"(1792 + 16) : "memory");
    asm volatile("cp.async.bulk.shared::cluster.global.mbarrier::complete_tx::bytes [%0], [%1], %2, [%3];"
                 :: "r"(sb + SM_X), "l"(x), "r"(1792), "r"(full0 + B_X * 8) : "memory");
    asm volatile("cp.async.bulk.shared::cluster.global.mbarrier::complete_tx::bytes [%0], [%1], %2, [%3];"
                 :: "r"(sb + SM_X + 1792), "l"(epoch), "r"(16), "r"(full0 + B_X * 8) : "memory");
}

enum { BAR_CONS = 1, BAR_LN = 2, BAR_FF = 3, BAR_WGT = 4, BAR_OB = 8   };

template <bool SCALED>
__global__ void __launch_bounds__(NTHREADS, 1)
fused_decode_kernel(const __nv_bfloat16* __restrict__ wq, const __nv_bfloat16* __restrict__ kc, const __nv_bfloat16* __restrict__ x,
                    Scratch* __restrict__ scr, const __nv_bfloat16* __restrict__ vc, const __nv_bfloat16* __restrict__ wo,
                    const __nv_bfloat16* __restrict__ wg, const __nv_bfloat16* __restrict__ wu, const __nv_bfloat16* __restrict__ wd,
                    __nv_bfloat16* __restrict__ out, const Clock<SCALED> clk) {
    extern __shared__ __align__(128) unsigned char smem[];
    const uint32_t sb = (uint32_t)__cvta_generic_to_shared(smem);
    const int tid = threadIdx.x, lane = tid & 31;
    const int cta = blockIdx.x;
    const int cl = cta >> 4, rk = cta & 15;
    const uint32_t full0 = sb + SM_BAR, done0 = full0 + NBAR * 8;
    if (tid < 256) {
        const char* src = reinterpret_cast<const char*>(wq) + (uint32_t)((cl * 64 + (tid >> 5)) * (QCOLS * 2) + rk * 512 + lane * 16);
        const uint32_t dst = (sb + SM_WQ + tid * 16) ^ ((tid >> 5) * 16);
#pragma unroll
        for (int i = 0; i < 8; i++) cp_async16(dst + i * 4096, src + i * (8 * QCOLS * 2));
    }
    const int warp = __shfl_sync(0xffffffffu, tid >> 5, 0);
    const int hkv = rk >> 1, bat = rk & 1;
    const int e0 = (2 * rk) % 7;
    const int extra = cl == e0 ? 0 : cl == (e0 + 1) % 7 ? 1 : -1;
    const int g = lane >> 2, t = lane & 3;
    if (warp >= 8 && warp < 12 && lane == 0) {
#pragma unroll
        for (int i = 0; i < 10; i++) {
            const int b = (warp - 8) * 10 + i;
            if (b != B_X) mbar_init(full0 + b * 8, b == B_FIN ? 1 : NPT);
            mbar_init(done0 + b * 8, 8);
        }
        if (warp == 11) {
            asm volatile("mbarrier.arrive.expect_tx.shared::cta.b64 _, [%0], %1;" :: "r"(full0 + B_FIN * 8), "r"(4096) : "memory");
            asm volatile("fence.mbarrier_init.release.cluster;" ::: "memory");
        }
    }
    if (tid == 384) load_x(sb, x, &scr->epoch[cta * 8]);
    if (tid < 4) reinterpret_cast<uint32_t*>(smem + SM_T0)[tid] = clk.now();
    __syncthreads();
    const uint32_t t0 = clk.base(sb, 3);
    asm volatile("barrier.cluster.arrive.relaxed.aligned;" ::: "memory");

    if (warp < 8) {
        mbar_wait(full0 + B_X * 8);
        const uint32_t epoch = *reinterpret_cast<const uint32_t*>(smem + SM_X + 1792);
        const uint32_t tag = pin((epoch + 1) & 1);
        const uint32_t voff = ((lane & 7) + (lane >> 4) * 8) * 512 + ((warp * 4 + ((lane >> 3) & 1) * 2) ^ (lane & 7)) * 16;
        {
            asm volatile("cp.async.wait_all;" ::: "memory");
            bar_sync(BAR_LN, 288);
            float c0[4] = {0.f, 0.f, 0.f, 0.f}, c1[4] = {0.f, 0.f, 0.f, 0.f};
#pragma unroll
            for (int h = 0; h < 2; h++) {
                uint32_t b[4], a[4][4];
                ldsm4(sb + SM_XN + (lane & 1) * XROW + (lane >> 3) * 16 + cl * 128 + h * 64, b);
#pragma unroll
                for (int i = 0; i < 4; i++) ldsm4t(sb + (voff ^ ((i & 1) * 16)) + SM_WQ + h * SLOT + (i >> 1) * 8192, a[i]);
                mma16816(c0, a[0], b[0], b[1]);
                mma16816(c1, a[1], b[0], b[1]);
                mma16816(c0, a[2], b[2], b[3]);
                mma16816(c1, a[3], b[2], b[3]);
            }
            st_pub64(scr->q + ((rk * 2 + (t & 1)) * 7 + cl) * 128 + warp * 16 + (t >> 1) * 8 + g, tagf(sel4(c0, t), tag), __float_as_uint(sel4(c1, t)));
            __syncwarp();
            if (lane == 0) mbar_arrive(full0 + B_W * 8, 1);
            const uint2* qp = scr->q + ((hkv * 2 + (tid >> 7)) * 2 + bat) * (7 * 128) + (tid & 127);
            clk.wait_until(t0, Q_T);
            uint2 v[7];
            int it = 0;
            uint32_t bad;
            do {
                bad = 0;
#pragma unroll
                for (int i = 0; i < 7; i++) v[i] = ld_poll64(qp + i * 128);
#pragma unroll
                for (int i = 0; i < 7; i++) { v[i].x ^= tag; bad |= v[i].x; }
                if (++it > SPIN_LIMIT) __trap();
            } while (warp_bad(bad));
            float q0 = 0.f, q1 = 0.f;
#pragma unroll
            for (int i = 0; i < 7; i++) { q0 += __uint_as_float(v[i].x); q1 += __uint_as_float(v[i].y); }
            __nv_bfloat16* qs = reinterpret_cast<__nv_bfloat16*>(smem + SM_Q + (tid >> 7) * 528) + ((tid & 127) >> 3) * 16 + (tid & 7);
            qs[0] = __float2bfloat16_rn(q0);
            qs[8] = __float2bfloat16_rn(q1);
        }
        bar_sync(BAR_CONS, 256);
        if (tid == 96) scr->epoch[cta * 8] = epoch + 1;
        {
            uint32_t qf[8][4];
#pragma unroll
            for (int k2 = 0; k2 < 8; k2++) ldsm4(sb + SM_Q + (lane & 1) * 528 + k2 * 64 + (lane >> 3) * 16, qf[k2]);
            const int mt = warp & 1;
            const uint32_t aoff = (16 * mt + (lane & 15)) * 512 + ((lane >> 4) ^ (lane & 7)) * 16;
            float* sc = reinterpret_cast<float*>(smem + SM_S) + (t & 1) * SROW + (g >> 1) * 8 + (2 * mt + (t >> 1)) * 2 + (g & 1);
#pragma unroll 1
            for (int k = warp >> 1; k < NR; k += 4) {
                const int s = S_K + k;
                mbar_wait(full0 + s * 8);
                const uint32_t base = sb + SM_RING + (s >= NS ? s - NS : s) * SLOT + aoff;
                float c0[4] = {0.f, 0.f, 0.f, 0.f}, c1[4] = {0.f, 0.f, 0.f, 0.f};
#pragma unroll
                for (int k2 = 0; k2 < 8; k2++) {
                    uint32_t a0[4], a1[4];
                    ldsm4((base ^ ((k2 & 1) * 64)) + (k2 >> 1) * 128, a0);
                    ldsm4((base ^ ((k2 & 1) * 64 + 32)) + (k2 >> 1) * 128, a1);
                    mma16816(c0, a0, qf[k2][0], qf[k2][1]);
                    mma16816(c1, a1, qf[k2][2], qf[k2][3]);
                }
                __syncwarp();
                if (lane == 0) mbar_arrive(done0 + s * 8, 4);
                sc[k * 32] = rbf(sel4(c0, t) + sel4(c1, t));
            }
        }
        bar_sync(BAR_CONS, 256);
        {
            constexpr float C = SCALE_LOG2E;
            const float* sc = reinterpret_cast<const float*>(smem + SM_S);
            float* stat = reinterpret_cast<float*>(smem + SM_STAT);
            const bool two = tid < 48 && (tid >= 16 || extra >= 0);
            float2 s[2][2];
#pragma unroll
            for (int h = 0; h < 2; h++) {
                s[h][0] = *reinterpret_cast<const float2*>(sc + h * SROW + 96 + 2 * tid);
                s[h][1] = two ? *reinterpret_cast<const float2*>(sc + h * SROW + 2 * tid) : s[h][0];
            }
            float m0 = fmaxf(fmaxf(s[0][0].x, s[0][0].y), fmaxf(s[0][1].x, s[0][1].y));
            float m1 = fmaxf(fmaxf(s[1][0].x, s[1][0].y), fmaxf(s[1][1].x, s[1][1].y));
#pragma unroll
            for (int o = 16; o > 0; o >>= 1) {
                m0 = fmaxf(m0, __shfl_xor_sync(0xffffffffu, m0, o));
                m1 = fmaxf(m1, __shfl_xor_sync(0xffffffffu, m1, o));
            }
            if (lane == 0) *reinterpret_cast<float2*>(stat + warp * 2) = make_float2(m0, m1);
            bar_sync(BAR_CONS, 256);
#pragma unroll
            for (int w = 0; w < 8; w++) {
                const float2 mm = *reinterpret_cast<const float2*>(stat + w * 2);
                m0 = fmaxf(m0, mm.x); m1 = fmaxf(m1, mm.y);
            }
            uint32_t* ps = reinterpret_cast<uint32_t*>(smem + SM_P);
            float l[2];
#pragma unroll
            for (int h = 0; h < 2; h++) {
                const float m = h ? m1 : m0;
                const float pa = ex2((s[h][0].x - m) * C), pb = ex2((s[h][0].y - m) * C);
                const float pc = ex2((s[h][1].x - m) * C), pd = ex2((s[h][1].y - m) * C);
                ps[h * PROW + 48 + tid] = pack_bf(pa, pb);
                if (two) ps[h * PROW + tid] = pack_bf(pc, pd);
                l[h] = (pa + pb) + (two ? pc + pd : 0.f);
            }
#pragma unroll
            for (int o = 16; o > 0; o >>= 1) {
                l[0] += __shfl_xor_sync(0xffffffffu, l[0], o);
                l[1] += __shfl_xor_sync(0xffffffffu, l[1], o);
            }
            if (lane == 0) *reinterpret_cast<float2*>(stat + 16 + warp * 2) = make_float2(l[0], l[1]);
            bar_sync(BAR_CONS, 256);
            if (tid < 4) {
                float ls = 0.f;
#pragma unroll
                for (int w = 0; w < 8; w++) ls += stat[16 + w * 2 + (tid & 1)];
                st_pub2(scr->ml + cta * 4 + tid, tagf((tid & 1) ? m1 : m0, tag), tagf(ls, tag));
            }
        }
        {
            float own = 0.f;
            float o0[4] = {0.f, 0.f, 0.f, 0.f}, o1[4] = {0.f, 0.f, 0.f, 0.f};
            float o2[4] = {0.f, 0.f, 0.f, 0.f}, o3[4] = {0.f, 0.f, 0.f, 0.f};
            const uint4* ps = reinterpret_cast<const uint4*>(smem + SM_P + (g & 1) * PROW * 4) + t;
            uint2* dst = reinterpret_cast<uint2*>(scr->part) + ((size_t)(hkv * 16 + (t & 1) * 8 + warp) * 16 + bat * 8 + cl) * 8 + g;
#pragma unroll
            for (int k = 0; k < NR; k++) {
                if (k != 0 || extra >= 0) {
                    const uint4 pa = ps[k * 4];
                    mbar_wait(full0 + (S_V + k) * 8);
                    uint32_t a[4][4];
#pragma unroll
                    for (int i = 0; i < 4; i++) ldsm4t(sb + (voff ^ ((i & 1) * 16)) + slot_of(S_V + k) + (i >> 1) * 8192, a[i]);
                    mma16816(o0, a[0], pa.x, pa.y);
                    mma16816(o1, a[1], pa.x, pa.y);
                    mma16816(o2, a[2], pa.z, pa.w);
                    mma16816(o3, a[3], pa.z, pa.w);
                }
                if (S_V + k + NS < NSTAGE + 3) {
                    __syncwarp();
                    if (lane == 0) mbar_arrive(done0 + (S_V + k) * 8, 1);
                }
                if (k == FFN_ST && warp < 7) {
                    strip_partial(sb, SM_STRIP, smem, warp, lane);
                    bar_arrive(BAR_FF, 256);
                }
                if (k == FFN_ST && warp == 7) {
                    bar_sync(BAR_FF, 256);
                    own = rbf(strip_sum(smem, (cta & 1) * 32 + lane));
                    st_pub1(scr->gu + (cta ^ 1) * 32 + lane, (pack_bf(0.f, strip_sum(smem, (~cta & 1) * 32 + lane)) & 0xffff0000u) | tag);
                }
                if (k == HID_ST && warp == 7) {
                    const uint2* mlp = scr->ml + (min(g, 6) * 16 + (rk & ~1)) * 4 + (rk & 1);
                    uint2 a, b;
                    uint32_t other;
                    int it = 0;
                    do {
                        a = ld_poll2(mlp); b = ld_poll2(mlp + 4); other = ld_poll1(scr->gu + cta * 32 + lane);
                        if (++it > SPIN_LIMIT) __trap();
                    } while (warp_bad(bad2(a.x, a.y, tag) | bad2(b.x, b.y, tag) | (other ^ tag)));
                    float ga = (cta & 1) ? bf_hi(other) : own;
                    ga *= (ga > 0.f ? 1.f : 0.f);
                    const float hv = ga * ((cta & 1) ? own : bf_hi(other));
                    const uint32_t w = pack_bf(hv, __shfl_xor_sync(0xffffffffu, hv, 2));
                    if (!(t & 2)) st_pub64(reinterpret_cast<uint2*>(scr->hid) + cta * 16 + (t & 1) * 8 + (g & 3) * 2 + (g >> 2), tag, w);
                    const float m[2] = {bf_hi(a.x), bf_hi(b.x)};
                    const float l[2] = {__uint_as_float(a.y ^ tag), __uint_as_float(b.y ^ tag)};
#pragma unroll
                    for (int bb = 0; bb < 2; bb++) {
                        float M = m[bb];
                        M = fmaxf(M, __shfl_xor_sync(0xffffffffu, M, 4));
                        M = fmaxf(M, __shfl_xor_sync(0xffffffffu, M, 8));
                        M = fmaxf(M, __shfl_xor_sync(0xffffffffu, M, 16));
                        const float e = g < 7 ? ex2((m[bb] - M) * SCALE_LOG2E) : 0.f;
                        float L = e * l[bb];
                        L += __shfl_xor_sync(0xffffffffu, L, 4);
                        L += __shfl_xor_sync(0xffffffffu, L, 8);
                        L += __shfl_xor_sync(0xffffffffu, L, 16);
                        if (t == 0) reinterpret_cast<float*>(smem + SM_WGT)[bb * 8 + g] = __fdividef(e, L);
                    }
                }
                if (k == PRE_ST && t < 2) st_pub64(dst, tag ^ 1, 0);
            }
            const bool h1 = t & 1;
            const float va = h1 ? o0[1] + o2[1] : o0[0] + o2[0], vb = h1 ? o1[1] + o3[1] : o1[0] + o3[0];
            const float vc2 = h1 ? o0[3] + o2[3] : o0[2] + o2[2], vd = h1 ? o1[3] + o3[3] : o1[2] + o3[2];
            if (t < 2) st_pub64(dst, (__byte_perm(__float_as_uint(va) + 0x10000u, pack_bf(0.f, vb), 0x7632) & ~1u) | tag, pack_bf(vc2, vd));
        }
        {
            bar_sync(BAR_WGT, 256);
            const uint2* pp = pin(reinterpret_cast<const uint2*>(scr->part) + (size_t)(rk * 8 + warp) * 128 + lane);
            const uint2* pp2 = pin(reinterpret_cast<const uint2*>(scr->part) + (size_t)(rk * 8 + warp) * 128 + lane + (lane < 24 ? 32 : 24));
            const uint32_t obaddr = pin(sb + SM_OB + warp * 128 + (lane >> 4) * 64 + (lane & 3) * 16 + ((lane >> 3) & 1) * 8 + ((lane >> 2) & 1) * 4), ll = pin(lane);
            float w[4];
#pragma unroll
            for (int i = 0; i < 4; i++) w[i] = lds32(sb + SM_WGT + (i * 4 + (lane >> 3)) * 4);
            clk.wait_until(clk.base(sb, 2), E2_T);
            float f[2][4];
            poll4(f, pp, pp2, tag, w);
            const bool h16 = ll & 16, h8 = ll & 8;
            float r4[4], r2[2];
#pragma unroll
            for (int e = 0; e < 4; e++) r4[e] = (h16 ? f[1][e] : f[0][e]) + __shfl_xor_sync(0xffffffffu, h16 ? f[0][e] : f[1][e], 16);
#pragma unroll
            for (int e = 0; e < 2; e++) r2[e] = (h8 ? r4[2 + e] : r4[e]) + __shfl_xor_sync(0xffffffffu, h8 ? r4[e] : r4[2 + e], 8);
            sts32(obaddr, pack_bf(r2[0], r2[1]));
            bar_arrive(BAR_OB + (warp >> 1), 96);
        }
    } else if (warp < 12) {
        const int pt = tid - 256, pw = warp - 8;
        {
            const size_t kvoff = ((size_t)(bat * 8 + hkv) * SK + (SK - WIN)) * DH * 2 + pt * 16;
            const char* base = reinterpret_cast<const char*>(kc) + kvoff;
            const __nv_bfloat16* gu = ((cta & 1) ? wu : wg) + (cta >> 1) * 32 + (pt & 3) * 8 + (size_t)(pt >> 2) * FF;
            uint32_t sdst = sb + SM_STRIP + (pt >> 2) * 64 + ((pt & 3) ^ ((pt >> 3) & 3)) * 16;
            const uint32_t kvdst = (sb + pt * 16) ^ (pw * 16);
            int unit = extra, slot = 0;
            int kb = 3584;
#pragma unroll 1
            for (int s = 0; s < NSTAGE; s++) {
                if (s >= NS - 2) mbar_wait(s >= NS ? done0 + (s - NS) * 8 : full0 + B_W * 8);
                const char* src = base + unit * SLOT;
                const uint32_t dst = kvdst + slot * SLOT;
                const bool strip = (unsigned)(s - S_GU) < 14;
                clk.wait_base(sb, 0, (kb * PACE_DT >> 11) - PACE_LEAD);
                if (unit >= 0) {
#pragma unroll
                    for (int i = 0; i < 8; i++) cp_async16_stream((dst ^ ((i & 1) * 64)) + i * 2048, src + i * 2048);
                }
                if (strip) { cp_async16_strip(sdst, gu); sdst += 2048; gu += 32 * FF; kb += 224; }
                cp_async_arrive(full0 + s * 8);
                kb += unit < 2 ? 512 : 1792;
                unit = unit < 2 ? 2 + cl : unit + 7;
                if (s == S_V - 1) { unit = extra; base = reinterpret_cast<const char*>(vc) + kvoff; }
                slot = slot == NS - 1 ? 0 : slot + 1;
            }
        }
        mbar_wait(full0 + B_X * 8);
        const uint32_t tag = (*reinterpret_cast<const uint32_t*>(smem + SM_X + 1792) + 1) & 1;
        mbar_wait(done0 + (NSTAGE + 2 - NS) * 8);
        const char* pdn = reinterpret_cast<const char*>(wd) + (size_t)(rk * 112 + pw * 32 + (lane >> 3)) * 896 + cl * 128 + (lane & 7) * 16;
        const char* pwo = reinterpret_cast<const char*>(wo) + (size_t)(rk * 256 + pw * 64 + (lane >> 3)) * 896 + cl * 128 + (lane & 7) * 16;
        const uint4* hp = scr->hid + (rk * 7 + pw * 2) * 8 + (lane & 7);
        uint4 h0 = ld_poll2x64(hp), h1 = ld_poll2x64(hp + (pw < 3 ? 8 : 0));
        const uint32_t ta = LATE_T, td = LATE_DT;
        const uint32_t fdst = (sb + pw * 4096 + lane * 16) ^ ((lane >> 3) * 16);
        clk.wait_base(sb, 1, ta);
        fetch16(fdst + slot_of(NSTAGE), pdn);
        if (pw < 3) fetch16(fdst + slot_of(NSTAGE) + 2048, pdn + 16 * 896);
        asm volatile("cp.async.commit_group;" ::: "memory");
        clk.wait_base(sb, 1, ta + td);
        fetch16(fdst + slot_of(NSTAGE + 1), pwo);
        fetch16(fdst + slot_of(NSTAGE + 1) + 2048, pwo + 16 * 896);
        asm volatile("cp.async.commit_group;" ::: "memory");
        clk.wait_base(sb, 1, ta + 2 * td);
        fetch16(fdst + slot_of(NSTAGE + 2), pwo + 32 * 896);
        fetch16(fdst + slot_of(NSTAGE + 2) + 2048, pwo + 48 * 896);
        asm volatile("cp.async.commit_group;" ::: "memory");
        for (int it = 0; warp_bad(bad2(h0.x, h0.z, tag) | bad2(h1.x, h1.z, tag)); it++) {
            h0 = ld_poll2x64(hp); h1 = ld_poll2x64(hp + (pw < 3 ? 8 : 0));
            if (it > SPIN_LIMIT) __trap();
        }
        asm volatile("barrier.cluster.wait.aligned;" ::: "memory");
        uint32_t rdst, rbar;
        asm volatile("mapa.shared::cluster.u32 %0, %1, %2;" : "=r"(rdst) : "r"(sb + SM_IN + (rk * 4 + pw) * 64 + (t ^ (pw & 2)) * 16), "r"(g * 2));
        asm volatile("mapa.shared::cluster.u32 %0, %1, %2;" : "=r"(rbar) : "r"(full0 + B_FIN * 8), "r"(g * 2));
        rdst = pin(rdst); rbar = pin(rbar);
        float c[4][4];
#pragma unroll
        for (int m = 0; m < 4; m++)
#pragma unroll
            for (int e = 0; e < 4; e++) c[m][e] = 0.f;
        const int r7 = ((lane & 7) >> 1) + 4 * (lane >> 4);
        const uint32_t aoff = sb + pw * 4096 + (r7 + 8 * (lane & 1)) * 128 + (((lane >> 3) & 1) ^ r7 ^ ((lane & 1) << 2)) * 16;
        const uint32_t obaddr = pin(sb + SM_OB + pw * 256 + (g & 1) * 64 + t * 16), tt = pin(t);
        uint32_t a0[2][4][4], a1[2][4][4];
        frag32<2, slot_of(NSTAGE)>(a0, aoff);
#pragma unroll
        for (int m = 0; m < 4; m++) mma16816(c[m], a0[0][m], h0.y, h0.w);
        if (pw < 3) {
#pragma unroll
            for (int m = 0; m < 4; m++) mma16816(c[m], a0[1][m], h1.y, h1.w);
        }
        frag32<1, slot_of(NSTAGE + 1)>(a1, aoff);
        bar_sync(BAR_OB + pw, 96);
        const uint4 ob0 = lds128(obaddr), ob1 = lds128(obaddr + 128);
        mma32(c, a1, ob0);
        frag32<0, slot_of(NSTAGE + 2)>(a0, aoff);
        mma32(c, a0, ob1);
        asm volatile("st.async.weak.shared::cluster.mbarrier::complete_tx::bytes.v4.f32 [%0], {%1,%2,%3,%4}, [%5];"
                     :: "r"(rdst), "f"(sel4(c[0], tt)), "f"(sel4(c[1], tt)), "f"(sel4(c[2], tt)), "f"(sel4(c[3], tt)), "r"(rbar) : "memory");
    } else if (warp == 12) {
        mbar_wait(full0 + B_X * 8);
        layernorm(smem, lane);
        bar_arrive(BAR_LN, 288);
        const uint32_t tag = (*reinterpret_cast<const uint32_t*>(smem + SM_X + 1792) + 1) & 1;
        if ((cta & 3) == 0) {
#pragma unroll 1
            for (int i = 0; i < 4; i++) {
                uint32_t sum = 0;
#pragma unroll
                for (int k = 0; k < NM; k++) {
                    mbar_wait(full0 + (MEND - NM + 1 + k + 7 * i) * 8);
                    sum += clk.now() - t0;
                }
                if (lane < 4) st_pub2(&scr->prog[i * 128 + cta + lane], ((t0 + sum / NM) & ~1u) | tag, (t0 & ~1u) | tag);
            }
        }
    } else if (warp == 13) {
        mbar_wait(full0 + B_X * 8);
        const uint32_t tag = (*reinterpret_cast<const uint32_t*>(smem + SM_X + 1792) + 1) & 1;
#pragma unroll 1
        for (int i = 0; i < 4; i++) {
            mbar_wait(full0 + (MEND + MGAP + 7 * i) * 8);
            uint2 v;
            int it = 0;
            do {
                v = ld_poll2(&scr->prog[i * 128 + min(lane, 27) * 4]);
                if (++it > SPIN_LIMIT) __trap();
            } while (warp_bad(bad2(v.x, v.y, tag)));
            const int nom = i == 0 ? M_NOM0 : i == 1 ? M_NOM1 : i == 2 ? M_NOM2 : M_NOM3;
            int base = __reduce_add_sync(0xffffffffu, lane < 28 ? min(max((int)(v.x - t0), 0), 1 << 20) : 0) / 28 - nom;
            const int start = __reduce_add_sync(0xffffffffu, lane < 28 ? min(max((int)(v.y - t0), -(1 << 20)), 1 << 20) : 0) / 28;
            const int lag = max(lane == 0 ? base - start - SLACK : min(base - start, 2 * (base - start - DEAD)), 0);
            const int ahead = (lane == 0 ? nom : lane == 1 ? LATE_T : E2_T) - nom;
            const float rate = fminf(__fdividef((float)lag, (float)(nom - 500)), 0.045f);
            if (lane < 3) reinterpret_cast<volatile uint32_t*>(smem + SM_T0)[lane] = t0 + start + lag + (int)(rate * (float)ahead);
        }
    }
    if ((warp == 12 || warp == 13) && (rk & 1) == 0) {
        const int oidx = ((lane >> 2) & 1) * D_MODEL + cl * 64 + (lane & 3) * 16 + (rk >> 1) + (warp & 1) * 8;
        const float xv = __bfloat162float(reinterpret_cast<const __nv_bfloat16*>(smem + SM_X)[oidx]);
        __nv_bfloat16* optr = pin(out + oidx);
        const uint32_t in = pin(sb + SM_IN + (lane >> 3) * 64 + ((warp ^ (lane >> 4)) & 1) * 32 + (lane & 7) * 4);
        float v[16];
        mbar_wait(full0 + B_FIN * 8);
#pragma unroll
        for (int i = 0; i < 16; i++) v[i] = lds32(in + i * 256);
#pragma unroll
        for (int i = 0; i < 16; i += 4) v[i] = (v[i] + v[i + 1]) + (v[i + 2] + v[i + 3]);
        float r = (v[0] + v[4]) + (v[8] + v[12]);
        r += __shfl_xor_sync(0xffffffffu, r, 8);
        r += __shfl_xor_sync(0xffffffffu, r, 16);
        asm volatile("st.global.u16 [%0], %1;" :: "l"(optr), "h"(__bfloat16_as_ushort(__float2bfloat16_rn(xv + r))) : "memory");
    }
}

namespace flat {

constexpr int F_PACE_DT = 640, F_PACE_LEAD = 350, F_LATE_T = 22330, F_LATE_DT = 460, F_Q_T = 4000, F_E2_T = 24030, F_E3_T = 24800;
constexpr int F_NOM0 = 4595, F_NOM1 = 8450, F_NOM2 = 12800, F_NOM3 = 17010;
constexpr int F_MEND = 5, F_MGAP = 3;
constexpr int NCTA = 128, NFFN = 112, NRED = 56, NTHREADS = 512;
constexpr int S_K = 0, S_V = 16, NSTAGE = 32;
constexpr int S_GU = NS, FFN_ST = 8, HID_ST = 11, PRE_ST = 12;
constexpr int SM_H = SM_WGT;

__device__ __forceinline__ uint4 ld_poll4(const void* p) {
    uint4 v;
    asm volatile("ld.relaxed.gpu.global.v4.u32 {%0,%1,%2,%3}, [%4];" : "=r"(v.x), "=r"(v.y), "=r"(v.z), "=r"(v.w) : "l"(p) : "memory");
    return v;
}
__device__ __forceinline__ void st_pub2x64(void* p, uint32_t a, uint32_t b, uint32_t c, uint32_t d) {
    asm volatile("{\n.reg .b64 d, e;\nmov.b64 d, {%1,%2};\nmov.b64 e, {%3,%4};\nst.relaxed.gpu.global.v2.b64 [%0], {d,e};\n}"
                 :: "l"(p), "r"(a), "r"(b), "r"(c), "r"(d) : "memory");
}
#define POLL_HEAD(P, T, N)                                                                                        \
    ".reg .pred p0, p1, p2, p3, q;\n"                                                                             \
    ".reg .b32 a, m, it, y<16>;\n"                                                                                \
    ".reg .b64 d<8>;\n"                                                                                           \
    "setp.eq.u32 p0, 0, 0;\nsetp.eq.u32 p1, 0, 0;\nsetp.eq.u32 p2, 0, 0;\nsetp.eq.u32 p3, 0, 0;\n"                \
    "mov.u32 it, " N ";\n"                                                                                        \
    "POLL_LOOP:\n"                                                                                                \
    "@p0 ld.relaxed.gpu.global.v2.b64 {d0,d1}, [" P "];\n"                                                        \
    "@p1 ld.relaxed.gpu.global.v2.b64 {d2,d3}, [" P "+512];\n"                                                    \
    "@p2 ld.relaxed.gpu.global.v2.b64 {d4,d5}, [" P "+1024];\n"                                                   \
    "@p3 ld.relaxed.gpu.global.v2.b64 {d6,d7}, [" P "+1536];\n"                                                   \
    "sub.u32 it, it, 1;\n"                                                                                        \
    "min.u32 m, it, 1;\n"                                                        \
    "mov.b64 {y0,y1}, d0;\nmov.b64 {y2,y3}, d1;\nmov.b64 {y4,y5}, d2;\nmov.b64 {y6,y7}, d3;\n"                    \
    "mov.b64 {y8,y9}, d4;\nmov.b64 {y10,y11}, d5;\nmov.b64 {y12,y13}, d6;\nmov.b64 {y14,y15}, d7;\n"              \
    "xor.b32 y0, y0, " T ";\nxor.b32 y2, y2, " T ";\nlop3.b32 a, y0, y2, m, 0xA8;\nsetp.ne.u32 p0, a, 0;\n"       \
    "xor.b32 y4, y4, " T ";\nxor.b32 y6, y6, " T ";\nlop3.b32 a, y4, y6, m, 0xA8;\nsetp.ne.u32 p1, a, 0;\n"       \
    "xor.b32 y8, y8, " T ";\nxor.b32 y10, y10, " T ";\nlop3.b32 a, y8, y10, m, 0xA8;\nsetp.ne.u32 p2, a, 0;\n"    \
    "xor.b32 y12, y12, " T ";\nxor.b32 y14, y14, " T ";\nlop3.b32 a, y12, y14, m, 0xA8;\nsetp.ne.u32 p3, a, 0;\n" \
    "or.pred q, p0, p1;\nor.pred q, q, p2;\nor.pred q, q, p3;\nvote.sync.any.pred q, q, 0xffffffff;\n"
#define POLL_TAIL "@q bra POLL_LOOP;\n"

__device__ __forceinline__ void poll4(float (&f)[2][4], const uint4* p, uint32_t tag, const float (&w)[4]) {
    asm volatile("{\n" POLL_HEAD("%8", "%9", "%14") POLL_TAIL
                 "mul.f32 %0, y0, %10;\nmul.f32 %1, y1, %10;\nmul.f32 %2, y2, %10;\nmul.f32 %3, y3, %10;\n"
                 "mul.f32 %4, y8, %12;\nmul.f32 %5, y9, %12;\nmul.f32 %6, y10, %12;\nmul.f32 %7, y11, %12;\n"
                 "fma.rn.f32 %0, y4, %11, %0;\nfma.rn.f32 %1, y5, %11, %1;\nfma.rn.f32 %2, y6, %11, %2;\nfma.rn.f32 %3, y7, %11, %3;\n"
                 "fma.rn.f32 %4, y12, %13, %4;\nfma.rn.f32 %5, y13, %13, %5;\nfma.rn.f32 %6, y14, %13, %6;\nfma.rn.f32 %7, y15, %13, %7;\n"
                 "}"
                 : "=&f"(f[0][0]), "=&f"(f[0][1]), "=&f"(f[0][2]), "=&f"(f[0][3]), "=&f"(f[1][0]), "=&f"(f[1][1]), "=&f"(f[1][2]), "=&f"(f[1][3])
                 : "l"(p), "r"(tag), "f"(w[0]), "f"(w[1]), "f"(w[2]), "f"(w[3]), "n"(SPIN_LIMIT) : "memory");
}
__device__ __forceinline__ void poll4_sum(float (&keep)[2], float (&recv)[2], const uint4* p, uint32_t tag, uint32_t hi) {
    asm volatile("{\n.reg .pred h;\n.reg .f32 s<8>;\nsetp.ne.u32 h, %6, 0;\n" POLL_HEAD("%4", "%5", "%7")
                 "add.f32 s0, y0, y4;\nadd.f32 s1, y1, y5;\nadd.f32 s2, y2, y6;\nadd.f32 s3, y3, y7;\n"
                 "add.f32 s4, y8, y12;\nadd.f32 s5, y9, y13;\nadd.f32 s6, y10, y14;\nadd.f32 s7, y11, y15;\n"
                 "add.f32 s0, s0, s4;\nadd.f32 s1, s1, s5;\nadd.f32 s2, s2, s6;\nadd.f32 s3, s3, s7;\n"
                 "selp.f32 s4, s0, s2, h;\nselp.f32 s5, s1, s3, h;\nselp.f32 %0, s2, s0, h;\nselp.f32 %1, s3, s1, h;\n"
                 "shfl.sync.bfly.b32 %2, s4, 16, 0x1f, 0xffffffff;\nshfl.sync.bfly.b32 %3, s5, 16, 0x1f, 0xffffffff;\n"
                 POLL_TAIL "}"
                 : "=&f"(keep[0]), "=&f"(keep[1]), "=&f"(recv[0]), "=&f"(recv[1])
                 : "l"(p), "r"(tag), "r"(hi), "n"(SPIN_LIMIT) : "memory");
}

struct Prod {
    uint32_t sb, kvdst, sdst;
    const char *k, *v;
    const __nv_bfloat16* gu;
    bool ffn;
};
__host__ __device__ constexpr int bytes_before(int s) { return 28672 + s * 16384 + (s <= S_GU ? 0 : s < S_GU + 14 ? s - S_GU : 14) * 1792; }
__host__ __device__ constexpr int issue_time(int s) {
    return (int)((long long)bytes_before(s) * F_PACE_DT / 16384) - F_PACE_LEAD;
}

template <int S, class CLK>
__device__ __forceinline__ void produce(Prod& p, const CLK& clk) {
    if constexpr (S < NSTAGE) {
        if constexpr (S >= NS) mbar_wait(p.sb + SM_BAR + (NBAR + S - NS) * 8);
        clk.wait_base(p.sb, 0, issue_time(S));
        const char* src = (S < S_V ? p.k : p.v) + (S & 15) * (8 * SLOT);
#pragma unroll
        for (int i = 0; i < 8; i++) cp_async16_stream((p.kvdst ^ ((i & 1) * 64)) + slot_of(S) + i * 2048, src + i * 2048);
        if constexpr (S >= S_GU && S < S_GU + 14) {
            if (p.ffn) cp_async16_strip(p.sdst + (S - S_GU) * 2048, p.gu + (size_t)(S - S_GU) * 32 * FF);
        }
        cp_async_arrive(p.sb + SM_BAR + S * 8);
        produce<S + 1>(p, clk);
    }
}

template <int PENDING, int OFF>
__device__ __forceinline__ void frag16(uint32_t (&a)[4][4], uint32_t addr) {
    asm volatile("cp.async.wait_group %0;" :: "n"(PENDING) : "memory");
    __syncwarp();
#pragma unroll
    for (int m = 0; m < 4; m++) ldsm4t((addr ^ (m * 32)) + OFF, a[m]);
}

enum { BAR_OB = 1, BAR_CONS = 2, BAR_LN = 3, BAR_FF = 4, BAR_FIN = 5, BAR_H = 6 };

template <bool SCALED>
__global__ void __launch_bounds__(NTHREADS, 1)
flat_decode_kernel(const __nv_bfloat16* __restrict__ wq, const __nv_bfloat16* __restrict__ kc, const __nv_bfloat16* __restrict__ x,
                    Scratch* __restrict__ scr, const __nv_bfloat16* __restrict__ vc, const __nv_bfloat16* __restrict__ wo,
                    const __nv_bfloat16* __restrict__ wg, const __nv_bfloat16* __restrict__ wu, const __nv_bfloat16* __restrict__ wd,
                    __nv_bfloat16* __restrict__ out, const Clock<SCALED> clk) {
    extern __shared__ __align__(128) unsigned char smem[];
    const uint32_t sb = (uint32_t)__cvta_generic_to_shared(smem);
    const int tid = threadIdx.x, lane = tid & 31;
    const int cta = blockIdx.x;
    const uint32_t full0 = sb + SM_BAR, done0 = full0 + NBAR * 8;
    const uint32_t t0 = clk.now();
    if (tid < 224) {
        const int row = (tid >> 5) * 64 + (lane >> 2);
        const char* src = reinterpret_cast<const char*>(wq) + (uint32_t)(row * (QCOLS * 2) + cta * 64 + (lane & 3) * 16);
        const uint32_t dst = sb + SM_STRIP + row * 64 + ((lane & 3) ^ (lane >> 3)) * 16;
#pragma unroll
        for (int i = 0; i < 8; i++) cp_async16_strip(dst + i * 512, src + i * (8 * QCOLS * 2));
    }
    const int warp = __shfl_sync(0xffffffffu, tid >> 5, 0);
    const int hkv = cta >> 4, j = cta & 15, bat = j >> 3, sp = j & 7;
    const int g = lane >> 2, t = lane & 3;

    if (warp < 8) {
        if (tid == 224) load_x(sb, x, &scr->epoch[cta * 8]);
        __syncthreads();
        mbar_wait(full0 + B_X * 8);
        const uint32_t epoch = *reinterpret_cast<const uint32_t*>(smem + SM_X + 1792);
        const uint32_t tag = pin((epoch + 1) & 1);
        uint32_t* qdst = reinterpret_cast<uint32_t*>(scr->q) + (hkv * 2 + (t & 1)) * 512 + j * 32 + warp * 16 + g + 8 * (t >> 1);
        if (warp == 7) {
            layernorm(smem, lane);
            bar_arrive(BAR_LN, 256);
        } else {
            asm volatile("cp.async.wait_all;" ::: "memory");
            bar_sync(BAR_LN, 256);
            strip_partial(sb, SM_STRIP, smem, warp, lane);
        }
        bar_sync(BAR_CONS, 256);
        if (warp < 2) {
            st_pub1(qdst, (pack_bf(0.f, strip_sum(smem, tid)) & 0xffff0000u) | tag);
        } else if (warp >= 4) {
            const int i = tid - 128;
            const uint4* qp = reinterpret_cast<const uint4*>(scr->q) + (hkv * 2 + bat) * 128 + i;
            clk.wait_until(t0, F_Q_T);
            uint4 v;
            int it = 0;
            do {
                v = ld_poll4(qp);
                if (++it > SPIN_LIMIT) __trap();
            } while (warp_bad(bad4(v, tag)));
            *reinterpret_cast<uint2*>(smem + SM_Q + (i >> 6) * 528 + (i & 63) * 8) =
                make_uint2(__byte_perm(v.x, v.y, 0x7632), __byte_perm(v.z, v.w, 0x7632));
        }
        bar_sync(BAR_CONS, 256);
        if (tid == 96) scr->epoch[cta * 8] = epoch + 1;
        {
            uint32_t qf[8][4];
#pragma unroll
            for (int k2 = 0; k2 < 8; k2++) ldsm4(sb + SM_Q + (lane & 1) * 528 + k2 * 64 + (lane >> 3) * 16, qf[k2]);
            const int mt = warp & 1;
            const uint32_t aoff = (16 * mt + (lane & 15)) * 512 + ((lane >> 4) ^ (lane & 7)) * 16;
            float* sc = reinterpret_cast<float*>(smem + SM_S) + (t & 1) * SROW + (g >> 1) * 8 + (2 * mt + (t >> 1)) * 2 + (g & 1);
#pragma unroll 1
            for (int k = warp >> 1; k < 16; k += 4) {
                const int s = S_K + k;
                mbar_wait(full0 + s * 8);
                const uint32_t base = sb + SM_RING + (s >= NS ? s - NS : s) * SLOT + aoff;
                float c0[4] = {0.f, 0.f, 0.f, 0.f}, c1[4] = {0.f, 0.f, 0.f, 0.f};
#pragma unroll
                for (int k2 = 0; k2 < 8; k2++) {
                    uint32_t a0[4], a1[4];
                    ldsm4((base ^ ((k2 & 1) * 64)) + (k2 >> 1) * 128, a0);
                    ldsm4((base ^ ((k2 & 1) * 64 + 32)) + (k2 >> 1) * 128, a1);
                    mma16816(c0, a0, qf[k2][0], qf[k2][1]);
                    mma16816(c1, a1, qf[k2][2], qf[k2][3]);
                }
                __syncwarp();
                if (lane == 0) mbar_arrive(done0 + s * 8, 4);
                sc[k * 32] = rbf(sel4(c0, t) + sel4(c1, t));
            }
        }
        bar_sync(BAR_CONS, 256);
        {
            constexpr float C = SCALE_LOG2E;
            const float* sc = reinterpret_cast<const float*>(smem + SM_S);
            float* stat = reinterpret_cast<float*>(smem + SM_STAT);
            const float2 s0 = *reinterpret_cast<const float2*>(sc + 2 * tid);
            const float2 s1 = *reinterpret_cast<const float2*>(sc + SROW + 2 * tid);
            float m0 = fmaxf(s0.x, s0.y), m1 = fmaxf(s1.x, s1.y);
#pragma unroll
            for (int o = 16; o > 0; o >>= 1) {
                m0 = fmaxf(m0, __shfl_xor_sync(0xffffffffu, m0, o));
                m1 = fmaxf(m1, __shfl_xor_sync(0xffffffffu, m1, o));
            }
            if (lane == 0) *reinterpret_cast<float2*>(stat + warp * 2) = make_float2(m0, m1);
            bar_sync(BAR_CONS, 256);
#pragma unroll
            for (int w = 0; w < 8; w++) {
                const float2 mm = *reinterpret_cast<const float2*>(stat + w * 2);
                m0 = fmaxf(m0, mm.x); m1 = fmaxf(m1, mm.y);
            }
            const float p00 = ex2((s0.x - m0) * C), p01 = ex2((s0.y - m0) * C);
            const float p10 = ex2((s1.x - m1) * C), p11 = ex2((s1.y - m1) * C);
            uint32_t* ps = reinterpret_cast<uint32_t*>(smem + SM_P);
            ps[tid] = pack_bf(p00, p01);
            ps[PROW + tid] = pack_bf(p10, p11);
            float l0 = p00 + p01, l1 = p10 + p11;
#pragma unroll
            for (int o = 16; o > 0; o >>= 1) {
                l0 += __shfl_xor_sync(0xffffffffu, l0, o);
                l1 += __shfl_xor_sync(0xffffffffu, l1, o);
            }
            if (lane == 0) *reinterpret_cast<float2*>(stat + 16 + warp * 2) = make_float2(l0, l1);
            bar_sync(BAR_CONS, 256);
            if (tid < 4) {
                float l = 0.f;
#pragma unroll
                for (int w = 0; w < 8; w++) l += stat[16 + w * 2 + (tid & 1)];
                st_pub2(scr->ml + cta * 4 + tid, tagf((tid & 1) ? m1 : m0, tag), tagf(l, tag));
            }
        }
        float wgt[2] = {0.f, 0.f}, own = 0.f;
        {
            float o0[4] = {0.f, 0.f, 0.f, 0.f}, o1[4] = {0.f, 0.f, 0.f, 0.f};
            float o2[4] = {0.f, 0.f, 0.f, 0.f}, o3[4] = {0.f, 0.f, 0.f, 0.f};
            const uint32_t aoff = ((lane & 7) + (lane >> 4) * 8) * 512 + ((warp * 4 + ((lane >> 3) & 1) * 2) ^ (lane & 7)) * 16;
            const uint4* ps = reinterpret_cast<const uint4*>(smem + SM_P + (g & 1) * PROW * 4) + t;
            uint32_t* dst = reinterpret_cast<uint32_t*>(scr->part) + ((size_t)(hkv * 16 + (t & 1) * 8 + warp) * 16 + j) * 32 +
                            (4 * (g & 3) + (t & 2) + (g >> 2)) * 2;
#pragma unroll
            for (int k = 0; k < 16; k++) {
                const uint4 pa = ps[k * 4];
                mbar_wait(full0 + (S_V + k) * 8);
                uint32_t a[4][4];
#pragma unroll
                for (int i = 0; i < 4; i++) ldsm4t(sb + (aoff ^ ((i & 1) * 16)) + slot_of(S_V + k) + (i >> 1) * 8192, a[i]);
                mma16816(o0, a[0], pa.x, pa.y);
                mma16816(o1, a[1], pa.x, pa.y);
                mma16816(o2, a[2], pa.z, pa.w);
                mma16816(o3, a[3], pa.z, pa.w);
                if (S_V + k + NS < NSTAGE + 3) {
                    __syncwarp();
                    if (lane == 0) mbar_arrive(done0 + (S_V + k) * 8, 1);
                }
                if (k == FFN_ST && warp < 7) {
                    strip_partial(sb, SM_STRIP, smem, warp, lane);
                    bar_arrive(BAR_FF, 256);
                }
                if (k == FFN_ST && warp == 7) {
                    bar_sync(BAR_FF, 256);
                    own = rbf(strip_sum(smem, (cta & 1) * 32 + lane));
                    st_pub1(scr->gu + (cta ^ 1) * 32 + lane, (pack_bf(0.f, strip_sum(smem, (~cta & 1) * 32 + lane)) & 0xffff0000u) | tag);
                }
                if (k == HID_ST && warp == 7) {
                    const uint2* mlp = scr->ml + (hkv * 16 + g) * 4 + (j >> 3);
                    uint2 a, b;
                    uint32_t other;
                    int it = 0;
                    do {
                        a = ld_poll2(mlp); b = ld_poll2(mlp + 32); other = ld_poll1(scr->gu + cta * 32 + lane);
                        if (++it > SPIN_LIMIT) __trap();
                    } while (warp_bad(bad2(a.x, a.y, tag) | bad2(b.x, b.y, tag) | (other ^ tag)));
                    float m[2] = {bf_hi(a.x), bf_hi(b.x)};
                    float l[2] = {__uint_as_float(a.y ^ tag), __uint_as_float(b.y ^ tag)};
#pragma unroll
                    for (int bb = 0; bb < 2; bb++) {
                        float M = m[bb];
                        M = fmaxf(M, __shfl_xor_sync(0xffffffffu, M, 4));
                        M = fmaxf(M, __shfl_xor_sync(0xffffffffu, M, 8));
                        M = fmaxf(M, __shfl_xor_sync(0xffffffffu, M, 16));
                        const float e = ex2((m[bb] - M) * SCALE_LOG2E);
                        float L = e * l[bb];
                        L += __shfl_xor_sync(0xffffffffu, L, 4);
                        L += __shfl_xor_sync(0xffffffffu, L, 8);
                        L += __shfl_xor_sync(0xffffffffu, L, 16);
                        wgt[bb] = __fdividef(e, L);
                    }
                    float ga = (cta & 1) ? bf_hi(other) : own;
                    ga *= (ga > 0.f ? 1.f : 0.f);
                    const float hv = ga * ((cta & 1) ? own : bf_hi(other));
                    const uint32_t w = pack_bf(hv, __shfl_xor_sync(0xffffffffu, hv, 2));
                    if (!(t & 2)) reinterpret_cast<uint32_t*>(smem + SM_H)[(t & 1) * 8 + (g & 3) * 2 + (g >> 2)] = w;
                    bar_arrive(BAR_H, 256);
                }
                if (k == PRE_ST) st_pub64(dst, tag ^ 1, 0);
            }
            const float v0 = sel4(o0, t) + sel4(o2, t), v1 = sel4(o1, t) + sel4(o3, t);
            st_pub64(dst, tagf(v0, tag), __float_as_uint(v1));
        }
        if (warp == 7) {
            const uint4* pp = pin(scr->part + (size_t)cta * 128 + lane);
            const uint32_t obaddr = pin(sb + SM_OB + (lane >> 4) * 64 + (lane & 7) * 8 + ((lane >> 3) & 1) * 4), ll = pin(lane);
            float w[4];
#pragma unroll
            for (int i = 0; i < 4; i++) w[i] = __shfl_sync(0xffffffffu, wgt[i >> 1], ((i & 1) * 4 + (lane >> 3)) * 4);
            clk.wait_until(clk.base(sb, 2), F_E2_T);
            float f[2][4];
            poll4(f, pp, tag, w);
            const bool h16 = ll & 16, h8 = ll & 8;
            float r4[4], r2[2];
#pragma unroll
            for (int e = 0; e < 4; e++) r4[e] = (h16 ? f[1][e] : f[0][e]) + __shfl_xor_sync(0xffffffffu, h16 ? f[0][e] : f[1][e], 16);
#pragma unroll
            for (int e = 0; e < 2; e++) r2[e] = (h8 ? r4[2 + e] : r4[e]) + __shfl_xor_sync(0xffffffffu, h8 ? r4[e] : r4[2 + e], 8);
            sts32(obaddr, pack_bf(r2[0], r2[1]));
            bar_arrive(BAR_OB, 256);
        } else if (warp < 4 && (cta & 1) == 0 && cta < 2 * NRED) {
            const uint4* op = pin(scr->outp + (size_t)(cta >> 1) * (NCTA * 4) + warp * 128 + lane);
            const int oidx = (t & 1) * D_MODEL + hkv * 64 + (lane >> 3) * 16 + (j >> 1) + (t >> 1) * 8;
            const float xv = __bfloat162float(reinterpret_cast<const __nv_bfloat16*>(smem + SM_X)[oidx]);
            __nv_bfloat16* optr = pin(out + oidx);
            const uint32_t red = pin(sb + SM_S + tid * 4), ll = pin(lane);
            float r2[2], rcv[2];
            const bool h8 = ll & 8;
            clk.wait_until(clk.base(sb, 3), F_E3_T);
            poll4_sum(r2, rcv, op, tag, ll & 16);
            r2[0] += rcv[0]; r2[1] += rcv[1];
            float r = (h8 ? r2[1] : r2[0]) + __shfl_xor_sync(0xffffffffu, h8 ? r2[0] : r2[1], 8);
            r += __shfl_xor_sync(0xffffffffu, r, 4);
            if (warp != 0) {
                sts32(red, __float_as_uint(r));
                bar_arrive(BAR_FIN, 128);
            } else {
                bar_sync(BAR_FIN, 128);
                r = ((xv + r) + lds32(red + 128)) + (lds32(red + 256) + lds32(red + 384));
                asm volatile("st.global.u16 [%0], %1;" :: "l"(optr), "h"(__bfloat16_as_ushort(__float2bfloat16_rn(r))) : "memory");
            }
        }
    } else if (warp < 15) {
        const int pt = tid - 256, pw = warp - 8;
        const char* pdn = reinterpret_cast<const char*>(wd) + (size_t)cta * 14336 + (lane >> 3) * 896 + pw * 128 + (lane & 7) * 16;
        const char* pwo = reinterpret_cast<const char*>(wo) + (size_t)cta * 28672 + (lane >> 3) * 896 + pw * 128 + (lane & 7) * 16;
        if (pw < 4) {
            if (lane == 0) {
#pragma unroll
                for (int i = 0; i < 10; i++) {
                    if (pw * 10 + i != B_X) mbar_init(full0 + (pw * 10 + i) * 8, NPT);
                    mbar_init(done0 + (pw * 10 + i) * 8, 8);
                }
            }
            Prod p;
            const size_t kvoff = ((size_t)(bat * 8 + hkv) * SK + (SK - WIN)) * DH * 2 + sp * SLOT + pt * 16;
            p.sb = sb;
            p.kvdst = (sb + pt * 16) ^ (pw * 16);
            p.sdst = sb + SM_STRIP + (pt >> 2) * 64 + ((pt & 3) ^ ((pt >> 3) & 3)) * 16;
            p.k = reinterpret_cast<const char*>(kc) + kvoff;
            p.v = reinterpret_cast<const char*>(vc) + kvoff;
            p.gu = ((cta & 1) ? wu : wg) + (cta >> 1) * 32 + (pt & 3) * 8 + (size_t)(pt >> 2) * FF;
            p.ffn = cta < NFFN;
            __syncthreads();
            produce<0>(p, clk);
        } else {
            __syncthreads();
        }
        mbar_wait(full0 + B_X * 8);
        const uint32_t tag = pin((*reinterpret_cast<const uint32_t*>(smem + SM_X + 1792) + 1) & 1);
        if (pw == 4 && (cta & 3) == 0) {
#pragma unroll 1
            for (int i = 0; i < 4; i++) {
                uint32_t sum = 0;
#pragma unroll
                for (int k = 0; k < NM; k++) {
                    mbar_wait(full0 + (F_MEND - NM + 1 + k + 6 * i) * 8);
                    sum += clk.now() - t0;
                }
                if (lane < 4) st_pub2(&scr->prog[i * 128 + cta + lane], ((t0 + sum / NM) & ~1u) | tag, (t0 & ~1u) | tag);
            }
        }
        mbar_wait(done0 + (NSTAGE + 2 - NS) * 8);
        const uint32_t ta = F_LATE_T, td = F_LATE_DT;
        uint4* odst = scr->outp + ((size_t)(pt >> 2) * NCTA + cta) * 4 + t;
        st_pub2x64(odst, tag ^ 1, 0, tag ^ 1, 0);
        const uint32_t fdst = (sb + pw * 2048 + lane * 16) ^ ((lane >> 3) * 16);
        clk.wait_base(sb, 1, ta);
        if (cta < NFFN) fetch16(fdst + slot_of(NSTAGE), pdn);
        asm volatile("cp.async.commit_group;" ::: "memory");
        clk.wait_base(sb, 1, ta + td);
        fetch16(fdst + slot_of(NSTAGE + 1), pwo);
        asm volatile("cp.async.commit_group;" ::: "memory");
        clk.wait_base(sb, 1, ta + 2 * td);
        fetch16(fdst + slot_of(NSTAGE + 2), pwo + 14336);
        asm volatile("cp.async.commit_group;" ::: "memory");
        bar_sync(BAR_H, 256);
        const uint2 h = *reinterpret_cast<const uint2*>(smem + SM_H + (g & 1) * 32 + t * 8);
        float c[4][4];
#pragma unroll
        for (int m = 0; m < 4; m++)
#pragma unroll
            for (int e = 0; e < 4; e++) c[m][e] = 0.f;
        const int r7 = ((lane & 7) >> 1) + 4 * (lane >> 4);
        const uint32_t aoff = sb + pw * 2048 + (r7 + 8 * (lane & 1)) * 128 + (((lane >> 3) & 1) ^ r7 ^ ((lane & 1) << 2)) * 16;
        const uint32_t obaddr = pin(sb + SM_OB + (g & 1) * 64 + t * 16), tt = pin(t);
        uint32_t a0[4][4], a1[4][4];
        frag16<2, slot_of(NSTAGE)>(a0, aoff);
        if (cta < NFFN) {
#pragma unroll
            for (int m = 0; m < 4; m++) mma16816(c[m], a0[m], h.x, h.y);
        }
        frag16<1, slot_of(NSTAGE + 1)>(a1, aoff);
        bar_sync(BAR_OB, 256);
        const uint4 ob = lds128(obaddr);
#pragma unroll
        for (int m = 0; m < 4; m++) mma16816(c[m], a1[m], ob.x, ob.y);
        frag16<0, slot_of(NSTAGE + 2)>(a0, aoff);
#pragma unroll
        for (int m = 0; m < 4; m++) mma16816(c[m], a0[m], ob.z, ob.w);
        st_pub2x64(odst, tagf(sel4(c[0], tt), tag), __float_as_uint(sel4(c[1], tt)), tagf(sel4(c[2], tt), tag), __float_as_uint(sel4(c[3], tt)));
    } else if (warp == 15) {
        if (lane < 4) reinterpret_cast<uint32_t*>(smem + SM_T0)[lane] = t0;
        __syncthreads();
        mbar_wait(full0 + B_X * 8);
        const uint32_t tag = (*reinterpret_cast<const uint32_t*>(smem + SM_X + 1792) + 1) & 1;
#pragma unroll 1
        for (int i = 0; i < 4; i++) {
            mbar_wait(full0 + (F_MEND + F_MGAP + 6 * i) * 8);
            uint2 v;
            int it = 0;
            do {
                v = ld_poll2(&scr->prog[i * 128 + lane * 4]);
                if (++it > SPIN_LIMIT) __trap();
            } while (warp_bad(bad2(v.x, v.y, tag)));
            const int nom = i == 0 ? F_NOM0 : i == 1 ? F_NOM1 : i == 2 ? F_NOM2 : F_NOM3;
            int base = (__reduce_add_sync(0xffffffffu, min(max((int)(v.x - t0), 0), 1 << 20)) >> 5) - nom;
            const int start = __reduce_add_sync(0xffffffffu, min(max((int)(v.y - t0), -(1 << 20)), 1 << 20)) >> 5;
            const int lag = max(lane == 0 ? base - start - SLACK : min(base - start, 2 * (base - start - DEAD)), 0);
            const int ahead = (lane == 0 ? nom : lane == 1 ? F_LATE_T : lane == 2 ? F_E2_T : F_E3_T - 150) - nom;
            const float rate = fminf(__fdividef((float)lag, (float)(nom - 500)), 0.045f);
            if (lane < 4) reinterpret_cast<volatile uint32_t*>(smem + SM_T0)[lane] = t0 + start + lag + (int)(rate * (float)ahead);
        }
    }
}

}

}

extern "C" void kernel_launch(void* const* d_in, const int* in_sizes, int n_in, void* d_out, int out_size) {
    (void)in_sizes; (void)n_in; (void)out_size;
    cudaLaunchConfig_t cfg = {};
    cfg.gridDim = dim3(NCTA); cfg.blockDim = dim3(NTHREADS); cfg.dynamicSmemBytes = SM_TOTAL; cfg.stream = cudaStreamPerThread;
    cudaLaunchAttribute at[1];
    at[0].id = cudaLaunchAttributeClusterDimension;
    at[0].val.clusterDim.x = 16; at[0].val.clusterDim.y = 1; at[0].val.clusterDim.z = 1;
    cfg.attrs = at; cfg.numAttrs = 1;

    static Scratch* scr = nullptr;
    static uint32_t scale = 64;
    static int nclusters = 0;
    if (!scr) {
        int dev = 0, khz = 0, bits = 0;
        cudaGetDevice(&dev);
        cudaDeviceGetAttribute(&khz, cudaDevAttrMemoryClockRate, dev);
        cudaDeviceGetAttribute(&bits, cudaDevAttrGlobalMemoryBusWidth, dev);
        if (khz > 0 && bits > 0) scale = (uint32_t)(64.0 * khz * bits / (2619000.0 * 5120.0) + 0.5);
        cudaFuncSetAttribute(fused_decode_kernel<false>, cudaFuncAttributeMaxDynamicSharedMemorySize, SM_TOTAL);
        cudaFuncSetAttribute(fused_decode_kernel<true>, cudaFuncAttributeMaxDynamicSharedMemorySize, SM_TOTAL);
        cudaFuncSetAttribute(flat::flat_decode_kernel<true>, cudaFuncAttributeMaxDynamicSharedMemorySize, SM_TOTAL);
        cudaFuncSetAttribute(fused_decode_kernel<false>, cudaFuncAttributeNonPortableClusterSizeAllowed, 1);
        cudaFuncSetAttribute(fused_decode_kernel<true>, cudaFuncAttributeNonPortableClusterSizeAllowed, 1);
        if (cudaOccupancyMaxActiveClusters(&nclusters, fused_decode_kernel<true>, &cfg) != cudaSuccess) nclusters = 0;
        (void)cudaGetLastError();
        cudaGetSymbolAddress(reinterpret_cast<void**>(&scr), g_scratch);
    }
    typedef const __nv_bfloat16* P;
    const P wq = (P)d_in[3], kc = (P)d_in[1], x = (P)d_in[0], vc = (P)d_in[2], wo = (P)d_in[4], wg = (P)d_in[6], wu = (P)d_in[7], wd = (P)d_in[8];
    __nv_bfloat16* out = (__nv_bfloat16*)d_out;
    if (nclusters < NCTA / 16)
        flat::flat_decode_kernel<true><<<flat::NCTA, flat::NTHREADS, SM_TOTAL, cudaStreamPerThread>>>(wq, kc, x, scr, vc, wo, wg, wu, wd, out, Clock<true>{scale});
    else if (scale == 64)
        cudaLaunchKernelEx(&cfg, fused_decode_kernel<false>, wq, kc, x, scr, vc, wo, wg, wu, wd, out, Clock<false>{scale});
    else
        cudaLaunchKernelEx(&cfg, fused_decode_kernel<true>, wq, kc, x, scr, vc, wo, wg, wu, wd, out, Clock<true>{scale});
}
```

```cpp
#include <cuda_runtime.h>
#include <cuda_bf16.h>
#include <stdint.h>

namespace {

constexpr int PACE_DT = 641;
constexpr int PACE_LEAD = 540;
constexpr int LATE_T = 22180;
constexpr int LATE_DT = 420;
constexpr int Q_T = 3700;
constexpr int E2_T = 23790;
constexpr int M_NOM0 = 4875;
constexpr int M_NOM1 = 9210;
constexpr int M_NOM2 = 13320;
constexpr int M_NOM3 = 17265;
constexpr int DEAD = 100;
constexpr int SLACK = 200;
constexpr int NM = 4;
constexpr int MEND = 7;
constexpr int MGAP = 4;
constexpr int GU0 = 9;

constexpr int D_MODEL = 448;
constexpr int SK      = 32768;
constexpr int WIN     = 4096;
constexpr int DH      = 256;
constexpr int QCOLS   = 4096;
constexpr int FF      = 1792;
constexpr int NCTA    = 112;
constexpr int NPT     = 128;
constexpr int NTHREADS = 448;

constexpr int NS     = 11;
constexpr int SLOT   = 16384;
constexpr int XROW   = 912;
constexpr int NR     = 19;
constexpr int S_K = 0, S_V = NR, NSTAGE = 2 * NR;
constexpr int S_GU   = GU0;
constexpr int FFN_ST = S_GU + 13 - S_V;
constexpr int HID_ST = FFN_ST + 3;
constexpr int PRE_ST = 14;
constexpr int NBAR   = 40;
constexpr int B_X = NSTAGE, B_FIN = NSTAGE + 1, B_W = NBAR + NSTAGE;
constexpr int SROW = 616, PROW = 336;

constexpr int SM_RING  = 0;
constexpr int SM_WQ    = SM_RING + (NS - 2) * SLOT;
constexpr int SM_STRIP = SM_RING + NS * SLOT;
constexpr int SM_S    = SM_STRIP + 448 * 64;
constexpr int SM_P    = SM_S + 2 * SROW * 4;
constexpr int SM_Q    = SM_P + 2 * PROW * 4;
constexpr int SM_XN   = SM_Q + 2 * 264 * 2;
constexpr int SM_X    = SM_XN + 2 * XROW;
constexpr int SM_RED  = SM_X + 1792 + 32;
constexpr int SM_STAT = SM_RED + 7 * 64 * 4;
constexpr int SM_WGT  = SM_STAT + 2 * 8 * 2 * 4;
constexpr int SM_HID  = SM_WGT + 2 * 8 * 4;
constexpr int SM_OB   = SM_HID + 8 * 16 * 4;
constexpr int SM_IN   = (SM_OB + 8 * 2 * 16 * 4 + 127) / 128 * 128;
constexpr int SM_T0   = SM_IN + 4096;
constexpr int SM_BAR  = SM_T0 + 32;
constexpr int SM_TOTAL = SM_BAR + 2 * NBAR * 8;
static_assert(SM_Q % 16 == 0 && SM_XN % 16 == 0 && SM_X % 16 == 0 && SM_OB % 16 == 0 && SM_P % 16 == 0 && SM_IN % 16 == 0, "align");
static_assert(FFN_ST >= 1 && 2 * NS >= NR && NSTAGE % NS + 3 <= NS, "stage -> slot mapping");
static_assert(SM_TOTAL <= 232448 && B_X == 38 && B_FIN == 39, "shared memory");

constexpr int SPIN_LIMIT = 1 << 22;
constexpr float SCALE_LOG2E = 0.0625f * 1.4426950408889634f;

struct __align__(1024) Scratch {
    uint4    part[128 * 2 * 8 * 8];
    uint4    outp[56 * 128 * 4];
    uint2    q[16 * 2 * 7 * 128];
    uint4    hid[NCTA * 8];
    unsigned gu[128 * 32];
    uint2    ml[128 * 4];
    uint2    prog[4 * 32 * 4];
    unsigned epoch[128 * 8];
};
__device__ Scratch g_scratch;

__device__ __forceinline__ void mbar_init(uint32_t bar, uint32_t cnt) {
    asm volatile("mbarrier.init.shared::cta.b64 [%0], %1;" :: "r"(bar), "r"(cnt) : "memory");
}
__device__ __forceinline__ void mbar_arrive(uint32_t bar, uint32_t cnt) {
    asm volatile("mbarrier.arrive.shared::cta.b64 _, [%0], %1;" :: "r"(bar), "r"(cnt) : "memory");
}
template <bool SCALED>
struct Clock {
    uint32_t scale;
    __device__ __forceinline__ uint32_t now() const {
        if constexpr (SCALED) {
            uint64_t t;
            asm volatile("mov.u64 %0, %globaltimer;" : "=l"(t));
            return (uint32_t)((t * scale) >> 6);
        } else {
            uint32_t t;
            asm volatile("mov.u32 %0, %globaltimer_lo;" : "=r"(t));
            return t;
        }
    }
    __device__ __forceinline__ static uint32_t base(uint32_t sb, int i) {
        uint32_t t;
        asm volatile("ld.volatile.shared.u32 %0, [%1];" : "=r"(t) : "r"(sb + SM_T0 + 4 * i) : "memory");
        return t;
    }
    __device__ __forceinline__ void wait_until(uint32_t t0, uint32_t dt) const { while (now() - t0 < dt) {} }
    __device__ __forceinline__ void wait_base(uint32_t sb, int i, uint32_t dt) const { while (now() - base(sb, i) < dt) {} }
};
__device__ __forceinline__ void mbar_wait(uint32_t bar) {
    asm volatile("{\n.reg .pred p;\nWAIT_LOOP:\nmbarrier.try_wait.parity.shared::cta.b64 p, [%0], 0;\n@!p bra WAIT_LOOP;\n}" :: "r"(bar) : "memory");
}
__device__ __forceinline__ void cp_async16(uint32_t dst, const void* src) {
    asm volatile("cp.async.cg.shared.global [%0], [%1], 16;" :: "r"(dst), "l"(src) : "memory");
}
__device__ __forceinline__ void cp_async16_strip(uint32_t dst, const void* src) {
    asm volatile("cp.async.cg.shared.global.L2::128B [%0], [%1], 16;" :: "r"(dst), "l"(src) : "memory");
}
__device__ __forceinline__ void cp_async16_stream(uint32_t dst, const void* src) {
    asm volatile("{\n.reg .b64 pol;\ncreatepolicy.fractional.L2::evict_first.b64 pol, 1.0;\n"
                 "cp.async.cg.shared.global.L2::cache_hint [%0], [%1], 16, pol;\n}" :: "r"(dst), "l"(src) : "memory");
}
__device__ __forceinline__ void cp_async_arrive(uint32_t bar) {
    asm volatile("cp.async.mbarrier.arrive.noinc.shared::cta.b64 [%0];" :: "r"(bar) : "memory");
}
__device__ __forceinline__ void bar_sync(int id, int n)   { asm volatile("bar.sync %0, %1;" :: "r"(id), "r"(n) : "memory"); }
__device__ __forceinline__ void bar_arrive(int id, int n) { asm volatile("bar.arrive %0, %1;" :: "r"(id), "r"(n) : "memory"); }

__device__ __forceinline__ uint32_t ld_poll1(const void* p) {
    uint32_t v;
    asm volatile("ld.relaxed.gpu.global.u32 %0, [%1];" : "=r"(v) : "l"(p) : "memory");
    return v;
}
__device__ __forceinline__ uint2 ld_poll2(const void* p) {
    uint2 v;
    asm volatile("ld.relaxed.gpu.global.v2.u32 {%0,%1}, [%2];" : "=r"(v.x), "=r"(v.y) : "l"(p) : "memory");
    return v;
}
__device__ __forceinline__ uint2 ld_poll64(const void* p) {
    uint2 v;
    asm volatile("{\n.reg .b64 d;\nld.relaxed.gpu.global.b64 d, [%2];\nmov.b64 {%0,%1}, d;\n}" : "=r"(v.x), "=r"(v.y) : "l"(p) : "memory");
    return v;
}
__device__ __forceinline__ uint4 ld_poll2x64(const void* p) {
    uint4 v;
    asm volatile("{\n.reg .b64 d, e;\nld.relaxed.gpu.global.v2.b64 {d,e}, [%4];\nmov.b64 {%0,%1}, d;\nmov.b64 {%2,%3}, e;\n}"
                 : "=r"(v.x), "=r"(v.y), "=r"(v.z), "=r"(v.w) : "l"(p) : "memory");
    return v;
}
__device__ __forceinline__ void st_pub64(void* p, uint32_t a, uint32_t b) {
    asm volatile("{\n.reg .b64 d;\nmov.b64 d, {%1,%2};\nst.relaxed.gpu.global.b64 [%0], d;\n}" :: "l"(p), "r"(a), "r"(b) : "memory");
}
__device__ __forceinline__ void st_pub2(void* p, uint32_t a, uint32_t b) {
    asm volatile("st.relaxed.gpu.global.v2.u32 [%0], {%1,%2};" :: "l"(p), "r"(a), "r"(b) : "memory");
}
__device__ __forceinline__ void st_pub1(void* p, uint32_t a) {
    asm volatile("st.relaxed.gpu.global.u32 [%0], %1;" :: "l"(p), "r"(a) : "memory");
}
__device__ __forceinline__ uint32_t tagf(float v, uint32_t tag) {
    uint32_t r;
    asm("lop3.b32 %0, %1, 0xfffffffe, %2, 0xEA;" : "=r"(r) : "r"(__float_as_uint(v)), "r"(tag));
    return r;
}
__device__ __forceinline__ uint32_t pin(uint32_t v) {
    uint32_t r;
    asm volatile("shfl.sync.bfly.b32 %0, %1, 0, 0x1f, 0xffffffff;" : "=r"(r) : "r"(v));
    return r;
}
template <class T>
__device__ __forceinline__ T* pin(T* p) {
    const uint64_t u = reinterpret_cast<uint64_t>(p);
    return reinterpret_cast<T*>(((uint64_t)pin((uint32_t)(u >> 32)) << 32) | pin((uint32_t)u));
}
__device__ __forceinline__ void sts32(uint32_t addr, uint32_t v) { asm volatile("st.shared.u32 [%0], %1;" :: "r"(addr), "r"(v) : "memory"); }
__device__ __forceinline__ float lds32(uint32_t addr) { float v; asm volatile("ld.shared.f32 %0, [%1];" : "=f"(v) : "r"(addr) : "memory"); return v; }
__device__ __forceinline__ uint4 lds128(uint32_t addr) {
    uint4 v;
    asm volatile("ld.shared.v4.u32 {%0,%1,%2,%3}, [%4];" : "=r"(v.x), "=r"(v.y), "=r"(v.z), "=r"(v.w) : "r"(addr) : "memory");
    return v;
}
__device__ __forceinline__ uint32_t bad2(uint32_t a, uint32_t b, uint32_t tag) {
    uint32_t r;
    asm("lop3.b32 %0, %1, %2, %3, 0x7E;" : "=r"(r) : "r"(a), "r"(b), "r"(tag));
    return r;
}
__device__ __forceinline__ uint32_t bad4(const uint4& v, uint32_t tag) { return bad2(v.x, v.y, tag) | bad2(v.z, v.w, tag); }
__device__ __forceinline__ bool warp_bad(uint32_t bad) { return __any_sync(0xffffffffu, bad & 1u); }

__device__ __forceinline__ void poll4(float (&f)[2][4], const uint2* p, const uint2* p2, uint32_t tag, const float (&w)[4]) {
    uint32_t y[8];
    asm volatile("{\n.reg .pred p0, p1, p2, p3, q;\n.reg .b32 a, m, it;\n.reg .b64 d<4>;\n"
                 "setp.eq.u32 p0, 0, 0;\nsetp.eq.u32 p1, 0, 0;\nsetp.eq.u32 p2, 0, 0;\nsetp.eq.u32 p3, 0, 0;\n"
                 "mov.u32 it, %11;\n"
                 "POLL_LOOP:\n"
                 "@p0 ld.relaxed.gpu.global.b64 d0, [%8];\n"
                 "@p1 ld.relaxed.gpu.global.b64 d1, [%9];\n"
                 "@p2 ld.relaxed.gpu.global.b64 d2, [%8+512];\n"
                 "@p3 ld.relaxed.gpu.global.b64 d3, [%9+512];\n"
                 "sub.u32 it, it, 1;\n"
                 "min.u32 m, it, 1;\n"
                 "mov.b64 {%0,%1}, d0;\nmov.b64 {%2,%3}, d1;\nmov.b64 {%4,%5}, d2;\nmov.b64 {%6,%7}, d3;\n"
                 "lop3.b32 a, %0, %10, m, 0x28;\nsetp.ne.u32 p0, a, 0;\nlop3.b32 a, %2, %10, m, 0x28;\nsetp.ne.u32 p1, a, 0;\n"
                 "lop3.b32 a, %4, %10, m, 0x28;\nsetp.ne.u32 p2, a, 0;\nlop3.b32 a, %6, %10, m, 0x28;\nsetp.ne.u32 p3, a, 0;\n"
                 "or.pred q, p0, p1;\nor.pred q, q, p2;\nor.pred q, q, p3;\nvote.sync.any.pred q, q, 0xffffffff;\n"
                 "@q bra POLL_LOOP;\n}"
                 : "=&r"(y[0]), "=&r"(y[1]), "=&r"(y[2]), "=&r"(y[3]), "=&r"(y[4]), "=&r"(y[5]), "=&r"(y[6]), "=&r"(y[7])
                 : "l"(p), "l"(p2), "r"(tag), "n"(SPIN_LIMIT) : "memory");
#pragma unroll
    for (int b = 0; b < 2; b++) {
        const uint32_t* u = y + 4 * b;
        f[b][0] = fmaf(w[2 * b], __uint_as_float((u[0] ^ tag) << 16), w[2 * b + 1] * __uint_as_float((u[2] ^ tag) << 16));
        f[b][1] = fmaf(w[2 * b], __uint_as_float(u[0] & 0xffff0000u), w[2 * b + 1] * __uint_as_float(u[2] & 0xffff0000u));
        f[b][2] = fmaf(w[2 * b], __uint_as_float(u[1] << 16), w[2 * b + 1] * __uint_as_float(u[3] << 16));
        f[b][3] = fmaf(w[2 * b], __uint_as_float(u[1] & 0xffff0000u), w[2 * b + 1] * __uint_as_float(u[3] & 0xffff0000u));
    }
}

__device__ __forceinline__ void ldsm4(uint32_t addr, uint32_t (&a)[4]) {
    asm volatile("ldmatrix.sync.aligned.m8n8.x4.shared.b16 {%0,%1,%2,%3}, [%4];" : "=r"(a[0]), "=r"(a[1]), "=r"(a[2]), "=r"(a[3]) : "r"(addr) : "memory");
}
__device__ __forceinline__ void ldsm4t(uint32_t addr, uint32_t (&a)[4]) {
    asm volatile("ldmatrix.sync.aligned.m8n8.x4.trans.shared.b16 {%0,%1,%2,%3}, [%4];" : "=r"(a[0]), "=r"(a[1]), "=r"(a[2]), "=r"(a[3]) : "r"(addr) : "memory");
}
__device__ __forceinline__ void mma16816(float (&c)[4], const uint32_t (&a)[4], uint32_t b0, uint32_t b1) {
    asm volatile("mma.sync.aligned.m16n8k16.row.col.f32.bf16.bf16.f32 {%0,%1,%2,%3}, {%4,%5,%6,%7}, {%8,%9}, {%0,%1,%2,%3};"
                 : "+f"(c[0]), "+f"(c[1]), "+f"(c[2]), "+f"(c[3]) : "r"(a[0]), "r"(a[1]), "r"(a[2]), "r"(a[3]), "r"(b0), "r"(b1));
}
__device__ __forceinline__ float bf_lo(uint32_t u) { return __uint_as_float(u << 16); }
__device__ __forceinline__ float bf_hi(uint32_t u) { return __uint_as_float(u & 0xffff0000u); }
__device__ __forceinline__ float rbf(float v) { return __bfloat162float(__float2bfloat16_rn(v)); }
__device__ __forceinline__ uint32_t pack_bf(float lo, float hi) {
    uint32_t r;
    asm("cvt.rn.bf16x2.f32 %0, %1, %2;" : "=r"(r) : "f"(hi), "f"(lo));
    return r;
}
__device__ __forceinline__ float sel4(const float (&c)[4], int t) {
    float a = (t & 1) ? c[1] : c[0];
    float b = (t & 1) ? c[3] : c[2];
    return (t & 2) ? b : a;
}
__device__ __forceinline__ float ex2(float x) { float y; asm("ex2.approx.ftz.f32 %0, %1;" : "=f"(y) : "f"(x)); return y; }
__device__ __forceinline__ float sqrt_approx(float x) { float y; asm("sqrt.approx.f32 %0, %1;" : "=f"(y) : "f"(x)); return y; }

__host__ __device__ constexpr uint32_t slot_of(int s) { return SM_RING + (s % NS) * SLOT; }

__device__ __forceinline__ void layernorm(unsigned char* smem, int lane, int b0, int b1) {
#pragma unroll 1
    for (int b = b0; b < b1; b++) {
        uint32_t xs[7];
#pragma unroll
        for (int i = 0; i < 7; i++) xs[i] = reinterpret_cast<const uint32_t*>(smem + SM_X)[b * (D_MODEL / 2) + i * 32 + lane];
        float sum = 0.f;
#pragma unroll
        for (int i = 0; i < 7; i++) sum += bf_lo(xs[i]) + bf_hi(xs[i]);
#pragma unroll
        for (int o = 16; o > 0; o >>= 1) sum += __shfl_xor_sync(0xffffffffu, sum, o);
        const float mean = sum * (1.0f / D_MODEL);
        float sq = 0.f;
#pragma unroll
        for (int i = 0; i < 7; i++) {
            const float d0 = bf_lo(xs[i]) - mean, d1 = bf_hi(xs[i]) - mean;
            sq = fmaf(d0, d0, fmaf(d1, d1, sq));
        }
#pragma unroll
        for (int o = 16; o > 0; o >>= 1) sq += __shfl_xor_sync(0xffffffffu, sq, o);
        const float mb = rbf(mean);
        const float sd = rbf(sqrt_approx(rbf(rbf(sq * (1.0f / D_MODEL)) + 1e-5f)));
#pragma unroll
        for (int i = 0; i < 7; i++)
            reinterpret_cast<uint32_t*>(smem + SM_XN + b * XROW)[i * 32 + lane] =
                pack_bf(__fdividef(rbf(bf_lo(xs[i]) - mb), sd), __fdividef(rbf(bf_hi(xs[i]) - mb), sd));
    }
}

__device__ __forceinline__ void strip_partial(uint32_t sb, uint32_t strip, unsigned char* smem, int warp, int lane) {
    float c[2][2][4];
#pragma unroll
    for (int n = 0; n < 2; n++)
#pragma unroll
        for (int e = 0; e < 4; e++) c[n][0][e] = c[n][1][e] = 0.f;
    const uint32_t ba = sb + SM_XN + (lane & 1) * XROW + (lane >> 3) * 16 + warp * 128;
    const uint32_t aa = sb + strip + (warp * 64 + (lane & 7) + (lane >> 4) * 8) * 64 + (((lane >> 3) & 1) ^ ((lane & 7) >> 1)) * 16;
#pragma unroll
    for (int k2 = 0; k2 < 2; k2++) {
        uint32_t b[4];
        ldsm4(ba + k2 * 64, b);
#pragma unroll
        for (int n = 0; n < 2; n++) {
            uint32_t a0[4], a1[4];
            ldsm4t((aa ^ (n * 32)) + k2 * 2048, a0);
            ldsm4t((aa ^ (n * 32)) + k2 * 2048 + 1024, a1);
            mma16816(c[n][0], a0, b[0], b[1]);
            mma16816(c[n][1], a1, b[2], b[3]);
        }
    }
    float* red = reinterpret_cast<float*>(smem + SM_RED) + warp * 64 + lane;
#pragma unroll
    for (int n = 0; n < 2; n++) red[n * 32] = sel4(c[n][0], lane & 3) + sel4(c[n][1], lane & 3);
}
__device__ __forceinline__ float strip_sum(const unsigned char* smem, int idx) {
    const float* red = reinterpret_cast<const float*>(smem + SM_RED) + idx;
    return ((red[0] + red[64]) + (red[128] + red[192])) + ((red[256] + red[320]) + red[384]);
}

__device__ __forceinline__ void fetch16(uint32_t dst, const char* src) {
#pragma unroll
    for (int i = 0; i < 4; i++) cp_async16((dst ^ (((i & 1) ^ (i >> 1)) * 64)) + i * 512, src + i * (4 * 896));
}
template <int PENDING, int OFF>
__device__ __forceinline__ void frag32(uint32_t (&a)[2][4][4], uint32_t addr) {
    asm volatile("cp.async.wait_group %0;" :: "n"(PENDING) : "memory");
    __syncwarp();
#pragma unroll
    for (int h = 0; h < 2; h++)
#pragma unroll
        for (int m = 0; m < 4; m++) ldsm4t((addr ^ (m * 32)) + OFF + h * 2048, a[h][m]);
}
__device__ __forceinline__ void mma32(float (&c)[4][4], const uint32_t (&a)[2][4][4], const uint4& b) {
#pragma unroll
    for (int m = 0; m < 4; m++) mma16816(c[m], a[0][m], b.x, b.y);
#pragma unroll
    for (int m = 0; m < 4; m++) mma16816(c[m], a[1][m], b.z, b.w);
}

__device__ __forceinline__ void load_x(uint32_t sb, const void* x, const void* epoch) {
    const uint32_t full0 = sb + SM_BAR;
    mbar_init(full0 + B_X * 8, 1);
    asm volatile("fence.mbarrier_init.release.cluster;" ::: "memory");
    asm volatile("mbarrier.arrive.expect_tx.shared::cta.b64 _, [%0], %1;" :: "r"(full0 + B_X * 8), "r"(1792 + 16) : "memory");
    asm volatile("cp.async.bulk.shared::cluster.global.mbarrier::complete_tx::bytes [%0], [%1], %2, [%3];"
                 :: "r"(sb + SM_X), "l"(x), "r"(1792), "r"(full0 + B_X * 8) : "memory");
    asm volatile("cp.async.bulk.shared::cluster.global.mbarrier::complete_tx::bytes [%0], [%1], %2, [%3];"
                 :: "r"(sb + SM_X + 1792), "l"(epoch), "r"(16), "r"(full0 + B_X * 8) : "memory");
}

enum { BAR_CONS = 1, BAR_LN = 2, BAR_FF = 3, BAR_WGT = 4, BAR_H = 5, BAR_OB = 8   };

template <bool SCALED>
__global__ void __launch_bounds__(NTHREADS, 1)
fused_decode_kernel(const __nv_bfloat16* __restrict__ wq, const __nv_bfloat16* __restrict__ kc, const __nv_bfloat16* __restrict__ x,
                    Scratch* __restrict__ scr, const __nv_bfloat16* __restrict__ vc, const __nv_bfloat16* __restrict__ wo,
                    const __nv_bfloat16* __restrict__ wg, const __nv_bfloat16* __restrict__ wu, const __nv_bfloat16* __restrict__ wd,
                    __nv_bfloat16* __restrict__ out, const Clock<SCALED> clk) {
    extern __shared__ __align__(128) unsigned char smem[];
    const uint32_t sb = (uint32_t)__cvta_generic_to_shared(smem);
    const int tid = threadIdx.x, lane = tid & 31;
    const int cta = blockIdx.x;
    const int cl = cta >> 4, rk = cta & 15;
    const uint32_t full0 = sb + SM_BAR, done0 = full0 + NBAR * 8;
    if (tid < 256) {
        const char* src = reinterpret_cast<const char*>(wq) + (uint32_t)((cl * 64 + (tid >> 5)) * (QCOLS * 2) + rk * 512 + lane * 16);
        const uint32_t dst = (sb + SM_WQ + tid * 16) ^ ((tid >> 5) * 16);
#pragma unroll
        for (int i = 0; i < 8; i++) cp_async16(dst + i * 4096, src + i * (8 * QCOLS * 2));
        const uint32_t now = clk.now();
        if (tid < 4) sts32(sb + SM_T0 + tid * 4, now);
    }
    const int warp = __shfl_sync(0xffffffffu, tid >> 5, 0);
    const int hkv = rk >> 1, bat = rk & 1;
    const int e0 = (2 * rk) % 7;
    const int extra = cl == e0 ? 0 : cl == (e0 + 1) % 7 ? 1 : -1;
    const int g = lane >> 2, t = lane & 3;
    if (warp >= 8 && warp < 12 && lane == 0) {
        const uint32_t b0 = full0 + (warp - 8) * 80;
#pragma unroll
        for (int i = 0; i < 10; i++) mbar_init(b0 + (NBAR + i) * 8, 8);
#pragma unroll
        for (int i = 0; i < 8; i++) mbar_init(b0 + i * 8, NPT);
        if (warp < 11) {
            mbar_init(b0 + 64, NPT); mbar_init(b0 + 72, NPT);
        } else {
            mbar_init(full0 + B_FIN * 8, 1);
            asm volatile("mbarrier.arrive.expect_tx.shared::cta.b64 _, [%0], %1;" :: "r"(full0 + B_FIN * 8), "r"(4096) : "memory");
            asm volatile("fence.mbarrier_init.release.cluster;" ::: "memory");
        }
    }
    if (tid == 384) load_x(sb, x, &scr->epoch[cta * 8]);
    __syncthreads();
    const uint32_t t0 = clk.base(sb, 3);
    asm volatile("barrier.cluster.arrive.relaxed.aligned;" ::: "memory");
    if (warp == 12 || warp == 13) {
        if (warp == 13) asm volatile("barrier.cluster.wait.aligned;" ::: "memory");
        mbar_wait(full0 + B_X * 8);
        layernorm(smem, lane, warp - 12, warp - 11);
        bar_arrive(BAR_LN, 320);
    }

    if (warp < 8) {
        mbar_wait(full0 + B_X * 8);
        const uint32_t epoch = *reinterpret_cast<const uint32_t*>(smem + SM_X + 1792);
        const uint32_t tag = pin((epoch + 1) & 1);
        const uint32_t voff = ((lane & 7) + (lane >> 4) * 8) * 512 + ((warp * 4 + ((lane >> 3) & 1) * 2) ^ (lane & 7)) * 16;
        {
            asm volatile("cp.async.wait_all;" ::: "memory");
            bar_sync(BAR_LN, 320);
            float c0[4] = {0.f, 0.f, 0.f, 0.f}, c1[4] = {0.f, 0.f, 0.f, 0.f};
#pragma unroll
            for (int h = 0; h < 2; h++) {
                uint32_t b[4], a[4][4];
                ldsm4(sb + SM_XN + (lane & 1) * XROW + (lane >> 3) * 16 + cl * 128 + h * 64, b);
#pragma unroll
                for (int i = 0; i < 4; i++) ldsm4t(sb + (voff ^ ((i & 1) * 16)) + SM_WQ + h * SLOT + (i >> 1) * 8192, a[i]);
                mma16816(c0, a[0], b[0], b[1]);
                mma16816(c1, a[1], b[0], b[1]);
                mma16816(c0, a[2], b[2], b[3]);
                mma16816(c1, a[3], b[2], b[3]);
            }
            st_pub64(scr->q + ((rk * 2 + (t & 1)) * 7 + cl) * 128 + warp * 16 + (t >> 1) * 8 + g, tagf(sel4(c0, t), tag), __float_as_uint(sel4(c1, t)));
            __syncwarp();
            if (lane == 0) mbar_arrive(full0 + B_W * 8, 1);
            const uint2* qp = scr->q + ((hkv * 2 + (tid >> 7)) * 2 + bat) * (7 * 128) + (tid & 127);
            clk.wait_until(t0, Q_T);
            uint2 v[7];
            int it = 0;
            uint32_t bad;
            do {
                bad = 0;
#pragma unroll
                for (int i = 0; i < 7; i++) v[i] = ld_poll64(qp + i * 128);
#pragma unroll
                for (int i = 0; i < 7; i++) { v[i].x ^= tag; bad |= v[i].x; }
                if (++it > SPIN_LIMIT) __trap();
            } while (warp_bad(bad));
            float q0 = 0.f, q1 = 0.f;
#pragma unroll
            for (int i = 0; i < 7; i++) { q0 += __uint_as_float(v[i].x); q1 += __uint_as_float(v[i].y); }
            __nv_bfloat16* qs = reinterpret_cast<__nv_bfloat16*>(smem + SM_Q + (tid >> 7) * 528) + ((tid & 127) >> 3) * 16 + (tid & 7);
            qs[0] = __float2bfloat16_rn(q0);
            qs[8] = __float2bfloat16_rn(q1);
        }
        bar_sync(BAR_CONS, 256);
        if (tid == 96) scr->epoch[cta * 8] = epoch + 1;
        {
            uint32_t qf[8][4];
#pragma unroll
            for (int k2 = 0; k2 < 8; k2++) ldsm4(sb + SM_Q + (lane & 1) * 528 + k2 * 64 + (lane >> 3) * 16, qf[k2]);
            const int mt = warp & 1;
            const uint32_t aoff = (16 * mt + (lane & 15)) * 512 + ((lane >> 4) ^ (lane & 7)) * 16;
            float* sc = reinterpret_cast<float*>(smem + SM_S) + (t & 1) * SROW + (g >> 1) * 8 + (2 * mt + (t >> 1)) * 2 + (g & 1);
#pragma unroll 1
            for (int k = warp >> 1; k < NR; k += 4) {
                const int s = S_K + k;
                mbar_wait(full0 + s * 8);
                const uint32_t base = sb + SM_RING + (s >= NS ? s - NS : s) * SLOT + aoff;
                float c0[4] = {0.f, 0.f, 0.f, 0.f}, c1[4] = {0.f, 0.f, 0.f, 0.f};
#pragma unroll
                for (int k2 = 0; k2 < 8; k2++) {
                    uint32_t a0[4], a1[4];
                    ldsm4((base ^ ((k2 & 1) * 64)) + (k2 >> 1) * 128, a0);
                    ldsm4((base ^ ((k2 & 1) * 64 + 32)) + (k2 >> 1) * 128, a1);
                    mma16816(c0, a0, qf[k2][0], qf[k2][1]);
                    mma16816(c1, a1, qf[k2][2], qf[k2][3]);
                }
                __syncwarp();
                if (lane == 0) mbar_arrive(done0 + s * 8, 4);
                sc[k * 32] = rbf(sel4(c0, t) + sel4(c1, t));
            }
        }
        bar_sync(BAR_CONS, 256);
        {
            constexpr float C = SCALE_LOG2E;
            const float* sc = reinterpret_cast<const float*>(smem + SM_S);
            float* stat = reinterpret_cast<float*>(smem + SM_STAT);
            const bool two = tid < 48 && (tid >= 16 || extra >= 0);
            float2 s[2][2];
#pragma unroll
            for (int h = 0; h < 2; h++) {
                s[h][0] = *reinterpret_cast<const float2*>(sc + h * SROW + 96 + 2 * tid);
                s[h][1] = two ? *reinterpret_cast<const float2*>(sc + h * SROW + 2 * tid) : s[h][0];
            }
            float m0 = fmaxf(fmaxf(s[0][0].x, s[0][0].y), fmaxf(s[0][1].x, s[0][1].y));
            float m1 = fmaxf(fmaxf(s[1][0].x, s[1][0].y), fmaxf(s[1][1].x, s[1][1].y));
#pragma unroll
            for (int o = 16; o > 0; o >>= 1) {
                m0 = fmaxf(m0, __shfl_xor_sync(0xffffffffu, m0, o));
                m1 = fmaxf(m1, __shfl_xor_sync(0xffffffffu, m1, o));
            }
            if (lane == 0) *reinterpret_cast<float2*>(stat + warp * 2) = make_float2(m0, m1);
            bar_sync(BAR_CONS, 256);
#pragma unroll
            for (int w = 0; w < 8; w++) {
                const float2 mm = *reinterpret_cast<const float2*>(stat + w * 2);
                m0 = fmaxf(m0, mm.x); m1 = fmaxf(m1, mm.y);
            }
            uint32_t* ps = reinterpret_cast<uint32_t*>(smem + SM_P);
            float l[2];
#pragma unroll
            for (int h = 0; h < 2; h++) {
                const float m = h ? m1 : m0;
                const float pa = ex2((s[h][0].x - m) * C), pb = ex2((s[h][0].y - m) * C);
                const float pc = ex2((s[h][1].x - m) * C), pd = ex2((s[h][1].y - m) * C);
                ps[h * PROW + 48 + tid] = pack_bf(pa, pb);
                if (two) ps[h * PROW + tid] = pack_bf(pc, pd);
                l[h] = (pa + pb) + (two ? pc + pd : 0.f);
            }
#pragma unroll
            for (int o = 16; o > 0; o >>= 1) {
                l[0] += __shfl_xor_sync(0xffffffffu, l[0], o);
                l[1] += __shfl_xor_sync(0xffffffffu, l[1], o);
            }
            if (lane == 0) *reinterpret_cast<float2*>(stat + 16 + warp * 2) = make_float2(l[0], l[1]);
            bar_sync(BAR_CONS, 256);
            if (tid < 4) {
                float ls = 0.f;
#pragma unroll
                for (int w = 0; w < 8; w++) ls += stat[16 + w * 2 + (tid & 1)];
                st_pub2(scr->ml + cta * 4 + tid, tagf((tid & 1) ? m1 : m0, tag), tagf(ls, tag));
            }
        }
        {
            float own = 0.f;
            float o0[4] = {0.f, 0.f, 0.f, 0.f}, o1[4] = {0.f, 0.f, 0.f, 0.f};
            float o2[4] = {0.f, 0.f, 0.f, 0.f}, o3[4] = {0.f, 0.f, 0.f, 0.f};
            const uint4* ps = reinterpret_cast<const uint4*>(smem + SM_P + (g & 1) * PROW * 4) + t;
            uint2* dst = reinterpret_cast<uint2*>(scr->part) + ((size_t)(hkv * 16 + (t & 1) * 8 + warp) * 16 + bat * 8 + cl) * 8 + g;
#pragma unroll
            for (int k = 0; k < NR; k++) {
                if (k != 0 || extra >= 0) {
                    const uint4 pa = ps[k * 4];
                    mbar_wait(full0 + (S_V + k) * 8);
                    uint32_t a[4][4];
#pragma unroll
                    for (int i = 0; i < 4; i++) ldsm4t(sb + (voff ^ ((i & 1) * 16)) + slot_of(S_V + k) + (i >> 1) * 8192, a[i]);
                    mma16816(o0, a[0], pa.x, pa.y);
                    mma16816(o1, a[1], pa.x, pa.y);
                    mma16816(o2, a[2], pa.z, pa.w);
                    mma16816(o3, a[3], pa.z, pa.w);
                }
                if (S_V + k + NS < NSTAGE + 3) {
                    __syncwarp();
                    if (lane == 0) mbar_arrive(done0 + (S_V + k) * 8, 1);
                }
                if (k == FFN_ST && warp < 7) {
                    strip_partial(sb, SM_STRIP, smem, warp, lane);
                    bar_arrive(BAR_FF, 256);
                }
                if (k == FFN_ST && warp == 7) {
                    bar_sync(BAR_FF, 256);
                    own = rbf(strip_sum(smem, (cta & 1) * 32 + lane));
                    st_pub1(scr->gu + (cta ^ 1) * 32 + lane, (pack_bf(0.f, strip_sum(smem, (~cta & 1) * 32 + lane)) & 0xffff0000u) | tag);
                }
                if (k == HID_ST && warp == 7) {
                    const uint2* mlp = scr->ml + (min(g, 6) * 16 + (rk & ~1)) * 4 + (rk & 1);
                    uint2 a, b;
                    uint32_t other;
                    int it = 0;
                    do {
                        a = ld_poll2(mlp); b = ld_poll2(mlp + 4); other = ld_poll1(scr->gu + cta * 32 + lane);
                        if (++it > SPIN_LIMIT) __trap();
                    } while (warp_bad(bad2(a.x, a.y, tag) | bad2(b.x, b.y, tag) | (other ^ tag)));
                    float ga = (cta & 1) ? bf_hi(other) : own;
                    ga *= (ga > 0.f ? 1.f : 0.f);
                    const float hv = ga * ((cta & 1) ? own : bf_hi(other));
                    const uint32_t w = pack_bf(hv, __shfl_xor_sync(0xffffffffu, hv, 2));
                    if (!(t & 2)) st_pub64(reinterpret_cast<uint2*>(scr->hid) + cta * 16 + (t & 1) * 8 + (g & 3) * 2 + (g >> 2), tag, w);
                    const float m[2] = {bf_hi(a.x), bf_hi(b.x)};
                    const float l[2] = {__uint_as_float(a.y ^ tag), __uint_as_float(b.y ^ tag)};
#pragma unroll
                    for (int bb = 0; bb < 2; bb++) {
                        float M = m[bb];
                        M = fmaxf(M, __shfl_xor_sync(0xffffffffu, M, 4));
                        M = fmaxf(M, __shfl_xor_sync(0xffffffffu, M, 8));
                        M = fmaxf(M, __shfl_xor_sync(0xffffffffu, M, 16));
                        const float e = g < 7 ? ex2((m[bb] - M) * SCALE_LOG2E) : 0.f;
                        float L = e * l[bb];
                        L += __shfl_xor_sync(0xffffffffu, L, 4);
                        L += __shfl_xor_sync(0xffffffffu, L, 8);
                        L += __shfl_xor_sync(0xffffffffu, L, 16);
                        if (t == 0) reinterpret_cast<float*>(smem + SM_WGT)[bb * 8 + g] = __fdividef(e, L);
                    }
                }
                if (k == PRE_ST && t < 2) st_pub64(dst, tag ^ 1, 0);
            }
            const bool h1 = t & 1;
            const float va = h1 ? o0[1] + o2[1] : o0[0] + o2[0], vb = h1 ? o1[1] + o3[1] : o1[0] + o3[0];
            const float vc2 = h1 ? o0[3] + o2[3] : o0[2] + o2[2], vd = h1 ? o1[3] + o3[3] : o1[2] + o3[2];
            if (t < 2) st_pub64(dst, (__byte_perm(__float_as_uint(va) + 0x10000u, pack_bf(0.f, vb), 0x7632) & ~1u) | tag, pack_bf(vc2, vd));
        }
        {
            bar_sync(BAR_WGT, 256);
            const uint2* pp = pin(reinterpret_cast<const uint2*>(scr->part) + (size_t)(rk * 8 + warp) * 128 + lane);
            const uint2* pp2 = pin(reinterpret_cast<const uint2*>(scr->part) + (size_t)(rk * 8 + warp) * 128 + lane + (lane < 24 ? 32 : 24));
            const uint32_t obaddr = pin(sb + SM_OB + warp * 128 + (lane >> 4) * 64 + (lane & 3) * 16 + ((lane >> 3) & 1) * 8 + ((lane >> 2) & 1) * 4), ll = pin(lane);
            float w[4];
#pragma unroll
            for (int i = 0; i < 4; i++) w[i] = lds32(sb + SM_WGT + (i * 4 + (lane >> 3)) * 4);
            clk.wait_until(clk.base(sb, 2), E2_T);
            float f[2][4];
            poll4(f, pp, pp2, tag, w);
            const bool h16 = ll & 16, h8 = ll & 8;
            float r4[4], r2[2];
#pragma unroll
            for (int e = 0; e < 4; e++) r4[e] = (h16 ? f[1][e] : f[0][e]) + __shfl_xor_sync(0xffffffffu, h16 ? f[0][e] : f[1][e], 16);
#pragma unroll
            for (int e = 0; e < 2; e++) r2[e] = (h8 ? r4[2 + e] : r4[e]) + __shfl_xor_sync(0xffffffffu, h8 ? r4[e] : r4[2 + e], 8);
            sts32(obaddr, pack_bf(r2[0], r2[1]));
            bar_arrive(BAR_OB + (warp >> 1), 96);
        }
    } else if (warp < 12) {
        const int pt = tid - 256, pw = warp - 8;
        {
            const size_t kvoff = ((size_t)(bat * 8 + hkv) * SK + (SK - WIN)) * DH * 2 + pt * 16;
            const char* base = reinterpret_cast<const char*>(kc) + kvoff;
            const __nv_bfloat16* gu = ((cta & 1) ? wu : wg) + (cta >> 1) * 32 + (pt & 3) * 8 + (size_t)(pt >> 2) * FF;
            uint32_t sdst = sb + SM_STRIP + (pt >> 2) * 64 + ((pt & 3) ^ ((pt >> 3) & 3)) * 16;
            const uint32_t kvdst = (sb + pt * 16) ^ (pw * 16);
            int unit = extra, slot = 0;
            int kb = 3584;
#pragma unroll 1
            for (int s = 0; s < NSTAGE; s++) {
                if (s >= NS - 2) mbar_wait(s >= NS ? done0 + (s - NS) * 8 : full0 + B_W * 8);
                const char* src = base + unit * SLOT;
                const uint32_t dst = kvdst + slot * SLOT;
                const bool strip = (unsigned)(s - S_GU) < 14;
                clk.wait_base(sb, 0, (kb * PACE_DT >> 11) - PACE_LEAD);
                if (unit >= 0) {
#pragma unroll
                    for (int i = 0; i < 8; i++) cp_async16_stream((dst ^ ((i & 1) * 64)) + i * 2048, src + i * 2048);
                }
                if (strip) { cp_async16_strip(sdst, gu); sdst += 2048; gu += 32 * FF; kb += 224; }
                cp_async_arrive(full0 + s * 8);
                kb += unit < 2 ? 512 : 1792;
                unit = unit < 2 ? 2 + cl : unit + 7;
                if (s == S_V - 1) { unit = extra; base = reinterpret_cast<const char*>(vc) + kvoff; }
                slot = slot == NS - 1 ? 0 : slot + 1;
            }
        }
        mbar_wait(done0 + (NSTAGE + 2 - NS) * 8);
        const char* pdn = reinterpret_cast<const char*>(wd) + (size_t)(rk * 112 + pw * 32 + (lane >> 3)) * 896 + cl * 128 + (lane & 7) * 16;
        const char* pwo = reinterpret_cast<const char*>(wo) + (size_t)(rk * 256 + pw * 64 + (lane >> 3)) * 896 + cl * 128 + (lane & 7) * 16;
        const uint32_t ta = LATE_T, td = LATE_DT;
        const uint32_t fdst = (sb + pw * 4096 + lane * 16) ^ ((lane >> 3) * 16);
        clk.wait_base(sb, 1, ta);
        fetch16(fdst + slot_of(NSTAGE), pdn);
        if (pw < 3) fetch16(fdst + slot_of(NSTAGE) + 2048, pdn + 16 * 896);
        asm volatile("cp.async.commit_group;" ::: "memory");
        clk.wait_base(sb, 1, ta + td);
        fetch16(fdst + slot_of(NSTAGE + 1), pwo);
        fetch16(fdst + slot_of(NSTAGE + 1) + 2048, pwo + 16 * 896);
        asm volatile("cp.async.commit_group;" ::: "memory");
        clk.wait_base(sb, 1, ta + 2 * td);
        fetch16(fdst + slot_of(NSTAGE + 2), pwo + 32 * 896);
        fetch16(fdst + slot_of(NSTAGE + 2) + 2048, pwo + 48 * 896);
        asm volatile("cp.async.commit_group;" ::: "memory");
        bar_sync(BAR_H, 160);
        const uint2 h0 = *reinterpret_cast<const uint2*>(smem + SM_HID + pw * 128 + (lane & 7) * 8);
        const uint2 h1 = *reinterpret_cast<const uint2*>(smem + SM_HID + pw * 128 + 64 + (lane & 7) * 8);
        uint32_t rdst, rbar;
        asm volatile("mapa.shared::cluster.u32 %0, %1, %2;" : "=r"(rdst) : "r"(sb + SM_IN + (rk * 4 + pw) * 64 + (t ^ (pw & 2)) * 16), "r"(g * 2));
        asm volatile("mapa.shared::cluster.u32 %0, %1, %2;" : "=r"(rbar) : "r"(full0 + B_FIN * 8), "r"(g * 2));
        rdst = pin(rdst); rbar = pin(rbar);
        float c[4][4];
#pragma unroll
        for (int m = 0; m < 4; m++)
#pragma unroll
            for (int e = 0; e < 4; e++) c[m][e] = 0.f;
        const int r7 = ((lane & 7) >> 1) + 4 * (lane >> 4);
        const uint32_t aoff = sb + pw * 4096 + (r7 + 8 * (lane & 1)) * 128 + (((lane >> 3) & 1) ^ r7 ^ ((lane & 1) << 2)) * 16;
        const uint32_t obaddr = pin(sb + SM_OB + pw * 256 + (g & 1) * 64 + t * 16), tt = pin(t);
        uint32_t a0[2][4][4], a1[2][4][4];
        frag32<2, slot_of(NSTAGE)>(a0, aoff);
#pragma unroll
        for (int m = 0; m < 4; m++) mma16816(c[m], a0[0][m], h0.x, h0.y);
        if (pw < 3) {
#pragma unroll
            for (int m = 0; m < 4; m++) mma16816(c[m], a0[1][m], h1.x, h1.y);
        }
        frag32<1, slot_of(NSTAGE + 1)>(a1, aoff);
        bar_sync(BAR_OB + pw, 96);
        const uint4 ob0 = lds128(obaddr), ob1 = lds128(obaddr + 128);
        mma32(c, a1, ob0);
        frag32<0, slot_of(NSTAGE + 2)>(a0, aoff);
        mma32(c, a0, ob1);
        asm volatile("st.async.weak.shared::cluster.mbarrier::complete_tx::bytes.v4.f32 [%0], {%1,%2,%3,%4}, [%5];"
                     :: "r"(rdst), "f"(sel4(c[0], tt)), "f"(sel4(c[1], tt)), "f"(sel4(c[2], tt)), "f"(sel4(c[3], tt)), "r"(rbar) : "memory");
    } else if (warp == 12) {
        const uint32_t tag = (*reinterpret_cast<const uint32_t*>(smem + SM_X + 1792) + 1) & 1;
        if ((cta & 3) == 0) {
#pragma unroll 1
            for (int i = 0; i < 4; i++) {
                uint32_t sum = 0;
#pragma unroll
                for (int k = 0; k < NM; k++) {
                    mbar_wait(full0 + (MEND - NM + 1 + k + 7 * i) * 8);
                    sum += clk.now() - t0;
                }
                if (lane < 4) st_pub2(&scr->prog[i * 128 + cta + lane], ((t0 + sum / NM) & ~1u) | tag, (t0 & ~1u) | tag);
            }
        }
        mbar_wait(full0 + (S_V + HID_ST + 6) * 8);
        const uint4* hp = scr->hid + rk * 56 + lane;
        uint4 h0, h1;
        int it = 0;
        do {
            h0 = ld_poll2x64(hp); h1 = ld_poll2x64(hp + (lane < 24 ? 32 : 0));
            if (++it > SPIN_LIMIT) __trap();
        } while (warp_bad(bad2(h0.x, h0.z, tag) | bad2(h1.x, h1.z, tag)));
        *reinterpret_cast<uint2*>(smem + SM_HID + lane * 8) = make_uint2(h0.y, h0.w);
        *reinterpret_cast<uint2*>(smem + SM_HID + 256 + lane * 8) = make_uint2(h1.y, h1.w);
        bar_arrive(BAR_H, 160);
    } else if (warp == 13) {
        const uint32_t tag = (*reinterpret_cast<const uint32_t*>(smem + SM_X + 1792) + 1) & 1;
#pragma unroll 1
        for (int i = 0; i < 4; i++) {
            mbar_wait(full0 + (MEND + MGAP + 7 * i) * 8);
            uint2 v;
            int it = 0;
            do {
                v = ld_poll2(&scr->prog[i * 128 + min(lane, 27) * 4]);
                if (++it > SPIN_LIMIT) __trap();
            } while (warp_bad(bad2(v.x, v.y, tag)));
            const int nom = i == 0 ? M_NOM0 : i == 1 ? M_NOM1 : i == 2 ? M_NOM2 : M_NOM3;
            int base = __reduce_add_sync(0xffffffffu, lane < 28 ? min(max((int)(v.x - t0), 0), 1 << 20) : 0) / 28 - nom;
            const int start = __reduce_add_sync(0xffffffffu, lane < 28 ? min(max((int)(v.y - t0), -(1 << 20)), 1 << 20) : 0) / 28;
            const int lag = max(lane == 0 ? base - start - SLACK : min(base - start, 2 * (base - start - DEAD)), 0);
            const int ahead = (lane == 0 ? nom : lane == 1 ? LATE_T : E2_T) - nom;
            const float rate = fminf(__fdividef((float)lag, (float)(nom - 500)), 0.045f);
            if (lane < 3) reinterpret_cast<volatile uint32_t*>(smem + SM_T0)[lane] = t0 + start + lag + (int)(rate * (float)ahead);
        }
    }
    if ((warp == 12 || warp == 13) && (rk & 1) == 0) {
        const int oidx = ((lane >> 2) & 1) * D_MODEL + cl * 64 + (lane & 3) * 16 + (rk >> 1) + (warp & 1) * 8;
        const float xv = __bfloat162float(reinterpret_cast<const __nv_bfloat16*>(smem + SM_X)[oidx]);
        __nv_bfloat16* optr = pin(out + oidx);
        const uint32_t in = pin(sb + SM_IN + (lane >> 3) * 64 + ((warp ^ (lane >> 4)) & 1) * 32 + (lane & 7) * 4);
#pragma unroll 1
        for (int pass = 0; pass < 2; pass++) {
            float v[16];
            mbar_wait(full0 + (pass ? B_FIN : B_X) * 8);
#pragma unroll
            for (int i = 0; i < 16; i++) v[i] = lds32(in + i * 256);
#pragma unroll
            for (int i = 0; i < 16; i += 4) v[i] = (v[i] + v[i + 1]) + (v[i + 2] + v[i + 3]);
            float r = (v[0] + v[4]) + (v[8] + v[12]);
            r += __shfl_xor_sync(0xffffffffu, r, 8);
            r += __shfl_xor_sync(0xffffffffu, r, 16);
            asm volatile("{\n.reg .pred p;\nsetp.ne.u32 p, %2, 0;\n@p st.global.u16 [%0], %1;\n}"
                         :: "l"(optr), "h"(__bfloat16_as_ushort(__float2bfloat16_rn(xv + r))), "r"(pass) : "memory");
        }
    }
}

namespace flat {

constexpr int F_PACE_DT = 640, F_PACE_LEAD = 350, F_LATE_T = 22330, F_LATE_DT = 460, F_Q_T = 4000, F_E2_T = 24030, F_E3_T = 24800;
constexpr int F_NOM0 = 4595, F_NOM1 = 8450, F_NOM2 = 12800, F_NOM3 = 17010;
constexpr int F_MEND = 5, F_MGAP = 3;
constexpr int NCTA = 128, NFFN = 112, NRED = 56, NTHREADS = 512;
constexpr int S_K = 0, S_V = 16, NSTAGE = 32;
constexpr int S_GU = NS, FFN_ST = 8, HID_ST = 11, PRE_ST = 12;
constexpr int SM_H = SM_WGT;

__device__ __forceinline__ uint4 ld_poll4(const void* p) {
    uint4 v;
    asm volatile("ld.relaxed.gpu.global.v4.u32 {%0,%1,%2,%3}, [%4];" : "=r"(v.x), "=r"(v.y), "=r"(v.z), "=r"(v.w) : "l"(p) : "memory");
    return v;
}
__device__ __forceinline__ void st_pub2x64(void* p, uint32_t a, uint32_t b, uint32_t c, uint32_t d) {
    asm volatile("{\n.reg .b64 d, e;\nmov.b64 d, {%1,%2};\nmov.b64 e, {%3,%4};\nst.relaxed.gpu.global.v2.b64 [%0], {d,e};\n}"
                 :: "l"(p), "r"(a), "r"(b), "r"(c), "r"(d) : "memory");
}
#define POLL_HEAD(P, T, N)                                                                                        \
    ".reg .pred p0, p1, p2, p3, q;\n"                                                                             \
    ".reg .b32 a, m, it, y<16>;\n"                                                                                \
    ".reg .b64 d<8>;\n"                                                                                           \
    "setp.eq.u32 p0, 0, 0;\nsetp.eq.u32 p1, 0, 0;\nsetp.eq.u32 p2, 0, 0;\nsetp.eq.u32 p3, 0, 0;\n"                \
    "mov.u32 it, " N ";\n"                                                                                        \
    "POLL_LOOP:\n"                                                                                                \
    "@p0 ld.relaxed.gpu.global.v2.b64 {d0,d1}, [" P "];\n"                                                        \
    "@p1 ld.relaxed.gpu.global.v2.b64 {d2,d3}, [" P "+512];\n"                                                    \
    "@p2 ld.relaxed.gpu.global.v2.b64 {d4,d5}, [" P "+1024];\n"                                                   \
    "@p3 ld.relaxed.gpu.global.v2.b64 {d6,d7}, [" P "+1536];\n"                                                   \
    "sub.u32 it, it, 1;\n"                                                                                        \
    "min.u32 m, it, 1;\n"                                                        \
    "mov.b64 {y0,y1}, d0;\nmov.b64 {y2,y3}, d1;\nmov.b64 {y4,y5}, d2;\nmov.b64 {y6,y7}, d3;\n"                    \
    "mov.b64 {y8,y9}, d4;\nmov.b64 {y10,y11}, d5;\nmov.b64 {y12,y13}, d6;\nmov.b64 {y14,y15}, d7;\n"              \
    "xor.b32 y0, y0, " T ";\nxor.b32 y2, y2, " T ";\nlop3.b32 a, y0, y2, m, 0xA8;\nsetp.ne.u32 p0, a, 0;\n"       \
    "xor.b32 y4, y4, " T ";\nxor.b32 y6, y6, " T ";\nlop3.b32 a, y4, y6, m, 0xA8;\nsetp.ne.u32 p1, a, 0;\n"       \
    "xor.b32 y8, y8, " T ";\nxor.b32 y10, y10, " T ";\nlop3.b32 a, y8, y10, m, 0xA8;\nsetp.ne.u32 p2, a, 0;\n"    \
    "xor.b32 y12, y12, " T ";\nxor.b32 y14, y14, " T ";\nlop3.b32 a, y12, y14, m, 0xA8;\nsetp.ne.u32 p3, a, 0;\n" \
    "or.pred q, p0, p1;\nor.pred q, q, p2;\nor.pred q, q, p3;\nvote.sync.any.pred q, q, 0xffffffff;\n"
#define POLL_TAIL "@q bra POLL_LOOP;\n"

__device__ __forceinline__ void poll4(float (&f)[2][4], const uint4* p, uint32_t tag, const float (&w)[4]) {
    asm volatile("{\n" POLL_HEAD("%8", "%9", "%14") POLL_TAIL
                 "mul.f32 %0, y0, %10;\nmul.f32 %1, y1, %10;\nmul.f32 %2, y2, %10;\nmul.f32 %3, y3, %10;\n"
                 "mul.f32 %4, y8, %12;\nmul.f32 %5, y9, %12;\nmul.f32 %6, y10, %12;\nmul.f32 %7, y11, %12;\n"
                 "fma.rn.f32 %0, y4, %11, %0;\nfma.rn.f32 %1, y5, %11, %1;\nfma.rn.f32 %2, y6, %11, %2;\nfma.rn.f32 %3, y7, %11, %3;\n"
                 "fma.rn.f32 %4, y12, %13, %4;\nfma.rn.f32 %5, y13, %13, %5;\nfma.rn.f32 %6, y14, %13, %6;\nfma.rn.f32 %7, y15, %13, %7;\n"
                 "}"
                 : "=&f"(f[0][0]), "=&f"(f[0][1]), "=&f"(f[0][2]), "=&f"(f[0][3]), "=&f"(f[1][0]), "=&f"(f[1][1]), "=&f"(f[1][2]), "=&f"(f[1][3])
                 : "l"(p), "r"(tag), "f"(w[0]), "f"(w[1]), "f"(w[2]), "f"(w[3]), "n"(SPIN_LIMIT) : "memory");
}
__device__ __forceinline__ void poll4_sum(float (&keep)[2], float (&recv)[2], const uint4* p, uint32_t tag, uint32_t hi) {
    asm volatile("{\n.reg .pred h;\n.reg .f32 s<8>;\nsetp.ne.u32 h, %6, 0;\n" POLL_HEAD("%4", "%5", "%7")
                 "add.f32 s0, y0, y4;\nadd.f32 s1, y1, y5;\nadd.f32 s2, y2, y6;\nadd.f32 s3, y3, y7;\n"
                 "add.f32 s4, y8, y12;\nadd.f32 s5, y9, y13;\nadd.f32 s6, y10, y14;\nadd.f32 s7, y11, y15;\n"
                 "add.f32 s0, s0, s4;\nadd.f32 s1, s1, s5;\nadd.f32 s2, s2, s6;\nadd.f32 s3, s3, s7;\n"
                 "selp.f32 s4, s0, s2, h;\nselp.f32 s5, s1, s3, h;\nselp.f32 %0, s2, s0, h;\nselp.f32 %1, s3, s1, h;\n"
                 "shfl.sync.bfly.b32 %2, s4, 16, 0x1f, 0xffffffff;\nshfl.sync.bfly.b32 %3, s5, 16, 0x1f, 0xffffffff;\n"
                 POLL_TAIL "}"
                 : "=&f"(keep[0]), "=&f"(keep[1]), "=&f"(recv[0]), "=&f"(recv[1])
                 : "l"(p), "r"(tag), "r"(hi), "n"(SPIN_LIMIT) : "memory");
}

struct Prod {
    uint32_t sb, kvdst, sdst;
    const char *k, *v;
    const __nv_bfloat16* gu;
    bool ffn;
};
__host__ __device__ constexpr int bytes_before(int s) { return 28672 + s * 16384 + (s <= S_GU ? 0 : s < S_GU + 14 ? s - S_GU : 14) * 1792; }
__host__ __device__ constexpr int issue_time(int s) {
    return (int)((long long)bytes_before(s) * F_PACE_DT / 16384) - F_PACE_LEAD;
}

template <int S, class CLK>
__device__ __forceinline__ void produce(Prod& p, const CLK& clk) {
    if constexpr (S < NSTAGE) {
        if constexpr (S >= NS) mbar_wait(p.sb + SM_BAR + (NBAR + S - NS) * 8);
        clk.wait_base(p.sb, 0, issue_time(S));
        const char* src = (S < S_V ? p.k : p.v) + (S & 15) * (8 * SLOT);
#pragma unroll
        for (int i = 0; i < 8; i++) cp_async16_stream((p.kvdst ^ ((i & 1) * 64)) + slot_of(S) + i * 2048, src + i * 2048);
        if constexpr (S >= S_GU && S < S_GU + 14) {
            if (p.ffn) cp_async16_strip(p.sdst + (S - S_GU) * 2048, p.gu + (size_t)(S - S_GU) * 32 * FF);
        }
        cp_async_arrive(p.sb + SM_BAR + S * 8);
        produce<S + 1>(p, clk);
    }
}

template <int PENDING, int OFF>
__device__ __forceinline__ void frag16(uint32_t (&a)[4][4], uint32_t addr) {
    asm volatile("cp.async.wait_group %0;" :: "n"(PENDING) : "memory");
    __syncwarp();
#pragma unroll
    for (int m = 0; m < 4; m++) ldsm4t((addr ^ (m * 32)) + OFF, a[m]);
}

enum { BAR_OB = 1, BAR_CONS = 2, BAR_LN = 3, BAR_FF = 4, BAR_FIN = 5, BAR_H = 6 };

template <bool SCALED>
__global__ void __launch_bounds__(NTHREADS, 1)
flat_decode_kernel(const __nv_bfloat16* __restrict__ wq, const __nv_bfloat16* __restrict__ kc, const __nv_bfloat16* __restrict__ x,
                    Scratch* __restrict__ scr, const __nv_bfloat16* __restrict__ vc, const __nv_bfloat16* __restrict__ wo,
                    const __nv_bfloat16* __restrict__ wg, const __nv_bfloat16* __restrict__ wu, const __nv_bfloat16* __restrict__ wd,
                    __nv_bfloat16* __restrict__ out, const Clock<SCALED> clk) {
    extern __shared__ __align__(128) unsigned char smem[];
    const uint32_t sb = (uint32_t)__cvta_generic_to_shared(smem);
    const int tid = threadIdx.x, lane = tid & 31;
    const int cta = blockIdx.x;
    const uint32_t full0 = sb + SM_BAR, done0 = full0 + NBAR * 8;
    const uint32_t t0 = clk.now();
    if (tid < 224) {
        const int row = (tid >> 5) * 64 + (lane >> 2);
        const char* src = reinterpret_cast<const char*>(wq) + (uint32_t)(row * (QCOLS * 2) + cta * 64 + (lane & 3) * 16);
        const uint32_t dst = sb + SM_STRIP + row * 64 + ((lane & 3) ^ (lane >> 3)) * 16;
#pragma unroll
        for (int i = 0; i < 8; i++) cp_async16_strip(dst + i * 512, src + i * (8 * QCOLS * 2));
    }
    const int warp = __shfl_sync(0xffffffffu, tid >> 5, 0);
    const int hkv = cta >> 4, j = cta & 15, bat = j >> 3, sp = j & 7;
    const int g = lane >> 2, t = lane & 3;

    if (warp < 8) {
        if (tid == 224) load_x(sb, x, &scr->epoch[cta * 8]);
        __syncthreads();
        mbar_wait(full0 + B_X * 8);
        const uint32_t epoch = *reinterpret_cast<const uint32_t*>(smem + SM_X + 1792);
        const uint32_t tag = pin((epoch + 1) & 1);
        uint32_t* qdst = reinterpret_cast<uint32_t*>(scr->q) + (hkv * 2 + (t & 1)) * 512 + j * 32 + warp * 16 + g + 8 * (t >> 1);
        if (warp == 7) {
            layernorm(smem, lane, 0, 2);
            bar_arrive(BAR_LN, 256);
        } else {
            asm volatile("cp.async.wait_all;" ::: "memory");
            bar_sync(BAR_LN, 256);
            strip_partial(sb, SM_STRIP, smem, warp, lane);
        }
        bar_sync(BAR_CONS, 256);
        if (warp < 2) {
            st_pub1(qdst, (pack_bf(0.f, strip_sum(smem, tid)) & 0xffff0000u) | tag);
        } else if (warp >= 4) {
            const int i = tid - 128;
            const uint4* qp = reinterpret_cast<const uint4*>(scr->q) + (hkv * 2 + bat) * 128 + i;
            clk.wait_until(t0, F_Q_T);
            uint4 v;
            int it = 0;
            do {
                v = ld_poll4(qp);
                if (++it > SPIN_LIMIT) __trap();
            } while (warp_bad(bad4(v, tag)));
            *reinterpret_cast<uint2*>(smem + SM_Q + (i >> 6) * 528 + (i & 63) * 8) =
                make_uint2(__byte_perm(v.x, v.y, 0x7632), __byte_perm(v.z, v.w, 0x7632));
        }
        bar_sync(BAR_CONS, 256);
        if (tid == 96) scr->epoch[cta * 8] = epoch + 1;
        {
            uint32_t qf[8][4];
#pragma unroll
            for (int k2 = 0; k2 < 8; k2++) ldsm4(sb + SM_Q + (lane & 1) * 528 + k2 * 64 + (lane >> 3) * 16, qf[k2]);
            const int mt = warp & 1;
            const uint32_t aoff = (16 * mt + (lane & 15)) * 512 + ((lane >> 4) ^ (lane & 7)) * 16;
            float* sc = reinterpret_cast<float*>(smem + SM_S) + (t & 1) * SROW + (g >> 1) * 8 + (2 * mt + (t >> 1)) * 2 + (g & 1);
#pragma unroll 1
            for (int k = warp >> 1; k < 16; k += 4) {
                const int s = S_K + k;
                mbar_wait(full0 + s * 8);
                const uint32_t base = sb + SM_RING + (s >= NS ? s - NS : s) * SLOT + aoff;
                float c0[4] = {0.f, 0.f, 0.f, 0.f}, c1[4] = {0.f, 0.f, 0.f, 0.f};
#pragma unroll
                for (int k2 = 0; k2 < 8; k2++) {
                    uint32_t a0[4], a1[4];
                    ldsm4((base ^ ((k2 & 1) * 64)) + (k2 >> 1) * 128, a0);
                    ldsm4((base ^ ((k2 & 1) * 64 + 32)) + (k2 >> 1) * 128, a1);
                    mma16816(c0, a0, qf[k2][0], qf[k2][1]);
                    mma16816(c1, a1, qf[k2][2], qf[k2][3]);
                }
                __syncwarp();
                if (lane == 0) mbar_arrive(done0 + s * 8, 4);
                sc[k * 32] = rbf(sel4(c0, t) + sel4(c1, t));
            }
        }
        bar_sync(BAR_CONS, 256);
        {
            constexpr float C = SCALE_LOG2E;
            const float* sc = reinterpret_cast<const float*>(smem + SM_S);
            float* stat = reinterpret_cast<float*>(smem + SM_STAT);
            const float2 s0 = *reinterpret_cast<const float2*>(sc + 2 * tid);
            const float2 s1 = *reinterpret_cast<const float2*>(sc + SROW + 2 * tid);
            float m0 = fmaxf(s0.x, s0.y), m1 = fmaxf(s1.x, s1.y);
#pragma unroll
            for (int o = 16; o > 0; o >>= 1) {
                m0 = fmaxf(m0, __shfl_xor_sync(0xffffffffu, m0, o));
                m1 = fmaxf(m1, __shfl_xor_sync(0xffffffffu, m1, o));
            }
            if (lane == 0) *reinterpret_cast<float2*>(stat + warp * 2) = make_float2(m0, m1);
            bar_sync(BAR_CONS, 256);
#pragma unroll
            for (int w = 0; w < 8; w++) {
                const float2 mm = *reinterpret_cast<const float2*>(stat + w * 2);
                m0 = fmaxf(m0, mm.x); m1 = fmaxf(m1, mm.y);
            }
            const float p00 = ex2((s0.x - m0) * C), p01 = ex2((s0.y - m0) * C);
            const float p10 = ex2((s1.x - m1) * C), p11 = ex2((s1.y - m1) * C);
            uint32_t* ps = reinterpret_cast<uint32_t*>(smem + SM_P);
            ps[tid] = pack_bf(p00, p01);
            ps[PROW + tid] = pack_bf(p10, p11);
            float l0 = p00 + p01, l1 = p10 + p11;
#pragma unroll
            for (int o = 16; o > 0; o >>= 1) {
                l0 += __shfl_xor_sync(0xffffffffu, l0, o);
                l1 += __shfl_xor_sync(0xffffffffu, l1, o);
            }
            if (lane == 0) *reinterpret_cast<float2*>(stat + 16 + warp * 2) = make_float2(l0, l1);
            bar_sync(BAR_CONS, 256);
            if (tid < 4) {
                float l = 0.f;
#pragma unroll
                for (int w = 0; w < 8; w++) l += stat[16 + w * 2 + (tid & 1)];
                st_pub2(scr->ml + cta * 4 + tid, tagf((tid & 1) ? m1 : m0, tag), tagf(l, tag));
            }
        }
        float wgt[2] = {0.f, 0.f}, own = 0.f;
        {
            float o0[4] = {0.f, 0.f, 0.f, 0.f}, o1[4] = {0.f, 0.f, 0.f, 0.f};
            float o2[4] = {0.f, 0.f, 0.f, 0.f}, o3[4] = {0.f, 0.f, 0.f, 0.f};
            const uint32_t aoff = ((lane & 7) + (lane >> 4) * 8) * 512 + ((warp * 4 + ((lane >> 3) & 1) * 2) ^ (lane & 7)) * 16;
            const uint4* ps = reinterpret_cast<const uint4*>(smem + SM_P + (g & 1) * PROW * 4) + t;
            uint32_t* dst = reinterpret_cast<uint32_t*>(scr->part) + ((size_t)(hkv * 16 + (t & 1) * 8 + warp) * 16 + j) * 32 +
                            (4 * (g & 3) + (t & 2) + (g >> 2)) * 2;
#pragma unroll
            for (int k = 0; k < 16; k++) {
                const uint4 pa = ps[k * 4];
                mbar_wait(full0 + (S_V + k) * 8);
                uint32_t a[4][4];
#pragma unroll
                for (int i = 0; i < 4; i++) ldsm4t(sb + (aoff ^ ((i & 1) * 16)) + slot_of(S_V + k) + (i >> 1) * 8192, a[i]);
                mma16816(o0, a[0], pa.x, pa.y);
                mma16816(o1, a[1], pa.x, pa.y);
                mma16816(o2, a[2], pa.z, pa.w);
                mma16816(o3, a[3], pa.z, pa.w);
                if (S_V + k + NS < NSTAGE + 3) {
                    __syncwarp();
                    if (lane == 0) mbar_arrive(done0 + (S_V + k) * 8, 1);
                }
                if (k == FFN_ST && warp < 7) {
                    strip_partial(sb, SM_STRIP, smem, warp, lane);
                    bar_arrive(BAR_FF, 256);
                }
                if (k == FFN_ST && warp == 7) {
                    bar_sync(BAR_FF, 256);
                    own = rbf(strip_sum(smem, (cta & 1) * 32 + lane));
                    st_pub1(scr->gu + (cta ^ 1) * 32 + lane, (pack_bf(0.f, strip_sum(smem, (~cta & 1) * 32 + lane)) & 0xffff0000u) | tag);
                }
                if (k == HID_ST && warp == 7) {
                    const uint2* mlp = scr->ml + (hkv * 16 + g) * 4 + (j >> 3);
                    uint2 a, b;
                    uint32_t other;
                    int it = 0;
                    do {
                        a = ld_poll2(mlp); b = ld_poll2(mlp + 32); other = ld_poll1(scr->gu + cta * 32 + lane);
                        if (++it > SPIN_LIMIT) __trap();
                    } while (warp_bad(bad2(a.x, a.y, tag) | bad2(b.x, b.y, tag) | (other ^ tag)));
                    float m[2] = {bf_hi(a.x), bf_hi(b.x)};
                    float l[2] = {__uint_as_float(a.y ^ tag), __uint_as_float(b.y ^ tag)};
#pragma unroll
                    for (int bb = 0; bb < 2; bb++) {
                        float M = m[bb];
                        M = fmaxf(M, __shfl_xor_sync(0xffffffffu, M, 4));
                        M = fmaxf(M, __shfl_xor_sync(0xffffffffu, M, 8));
                        M = fmaxf(M, __shfl_xor_sync(0xffffffffu, M, 16));
                        const float e = ex2((m[bb] - M) * SCALE_LOG2E);
                        float L = e * l[bb];
                        L += __shfl_xor_sync(0xffffffffu, L, 4);
                        L += __shfl_xor_sync(0xffffffffu, L, 8);
                        L += __shfl_xor_sync(0xffffffffu, L, 16);
                        wgt[bb] = __fdividef(e, L);
                    }
                    float ga = (cta & 1) ? bf_hi(other) : own;
                    ga *= (ga > 0.f ? 1.f : 0.f);
                    const float hv = ga * ((cta & 1) ? own : bf_hi(other));
                    const uint32_t w = pack_bf(hv, __shfl_xor_sync(0xffffffffu, hv, 2));
                    if (!(t & 2)) reinterpret_cast<uint32_t*>(smem + SM_H)[(t & 1) * 8 + (g & 3) * 2 + (g >> 2)] = w;
                    bar_arrive(BAR_H, 256);
                }
                if (k == PRE_ST) st_pub64(dst, tag ^ 1, 0);
            }
            const float v0 = sel4(o0, t) + sel4(o2, t), v1 = sel4(o1, t) + sel4(o3, t);
            st_pub64(dst, tagf(v0, tag), __float_as_uint(v1));
        }
        if (warp == 7) {
            const uint4* pp = pin(scr->part + (size_t)cta * 128 + lane);
            const uint32_t obaddr = pin(sb + SM_OB + (lane >> 4) * 64 + (lane & 7) * 8 + ((lane >> 3) & 1) * 4), ll = pin(lane);
            float w[4];
#pragma unroll
            for (int i = 0; i < 4; i++) w[i] = __shfl_sync(0xffffffffu, wgt[i >> 1], ((i & 1) * 4 + (lane >> 3)) * 4);
            clk.wait_until(clk.base(sb, 2), F_E2_T);
            float f[2][4];
            poll4(f, pp, tag, w);
            const bool h16 = ll & 16, h8 = ll & 8;
            float r4[4], r2[2];
#pragma unroll
            for (int e = 0; e < 4; e++) r4[e] = (h16 ? f[1][e] : f[0][e]) + __shfl_xor_sync(0xffffffffu, h16 ? f[0][e] : f[1][e], 16);
#pragma unroll
            for (int e = 0; e < 2; e++) r2[e] = (h8 ? r4[2 + e] : r4[e]) + __shfl_xor_sync(0xffffffffu, h8 ? r4[e] : r4[2 + e], 8);
            sts32(obaddr, pack_bf(r2[0], r2[1]));
            bar_arrive(BAR_OB, 256);
        } else if (warp < 4 && (cta & 1) == 0 && cta < 2 * NRED) {
            const uint4* op = pin(scr->outp + (size_t)(cta >> 1) * (NCTA * 4) + warp * 128 + lane);
            const int oidx = (t & 1) * D_MODEL + hkv * 64 + (lane >> 3) * 16 + (j >> 1) + (t >> 1) * 8;
            const float xv = __bfloat162float(reinterpret_cast<const __nv_bfloat16*>(smem + SM_X)[oidx]);
            __nv_bfloat16* optr = pin(out + oidx);
            const uint32_t red = pin(sb + SM_S + tid * 4), ll = pin(lane);
            float r2[2], rcv[2];
            const bool h8 = ll & 8;
            clk.wait_until(clk.base(sb, 3), F_E3_T);
            poll4_sum(r2, rcv, op, tag, ll & 16);
            r2[0] += rcv[0]; r2[1] += rcv[1];
            float r = (h8 ? r2[1] : r2[0]) + __shfl_xor_sync(0xffffffffu, h8 ? r2[0] : r2[1], 8);
            r += __shfl_xor_sync(0xffffffffu, r, 4);
            if (warp != 0) {
                sts32(red, __float_as_uint(r));
                bar_arrive(BAR_FIN, 128);
            } else {
                bar_sync(BAR_FIN, 128);
                r = ((xv + r) + lds32(red + 128)) + (lds32(red + 256) + lds32(red + 384));
                asm volatile("st.global.u16 [%0], %1;" :: "l"(optr), "h"(__bfloat16_as_ushort(__float2bfloat16_rn(r))) : "memory");
            }
        }
    } else if (warp < 15) {
        const int pt = tid - 256, pw = warp - 8;
        const char* pdn = reinterpret_cast<const char*>(wd) + (size_t)cta * 14336 + (lane >> 3) * 896 + pw * 128 + (lane & 7) * 16;
        const char* pwo = reinterpret_cast<const char*>(wo) + (size_t)cta * 28672 + (lane >> 3) * 896 + pw * 128 + (lane & 7) * 16;
        if (pw < 4) {
            if (lane == 0) {
#pragma unroll
                for (int i = 0; i < 10; i++) {
                    if (pw * 10 + i != B_X) mbar_init(full0 + (pw * 10 + i) * 8, NPT);
                    mbar_init(done0 + (pw * 10 + i) * 8, 8);
                }
            }
            Prod p;
            const size_t kvoff = ((size_t)(bat * 8 + hkv) * SK + (SK - WIN)) * DH * 2 + sp * SLOT + pt * 16;
            p.sb = sb;
            p.kvdst = (sb + pt * 16) ^ (pw * 16);
            p.sdst = sb + SM_STRIP + (pt >> 2) * 64 + ((pt & 3) ^ ((pt >> 3) & 3)) * 16;
            p.k = reinterpret_cast<const char*>(kc) + kvoff;
            p.v = reinterpret_cast<const char*>(vc) + kvoff;
            p.gu = ((cta & 1) ? wu : wg) + (cta >> 1) * 32 + (pt & 3) * 8 + (size_t)(pt >> 2) * FF;
            p.ffn = cta < NFFN;
            __syncthreads();
            produce<0>(p, clk);
        } else {
            __syncthreads();
        }
        mbar_wait(full0 + B_X * 8);
        const uint32_t tag = pin((*reinterpret_cast<const uint32_t*>(smem + SM_X + 1792) + 1) & 1);
        if (pw == 4 && (cta & 3) == 0) {
#pragma unroll 1
            for (int i = 0; i < 4; i++) {
                uint32_t sum = 0;
#pragma unroll
                for (int k = 0; k < NM; k++) {
                    mbar_wait(full0 + (F_MEND - NM + 1 + k + 6 * i) * 8);
                    sum += clk.now() - t0;
                }
                if (lane < 4) st_pub2(&scr->prog[i * 128 + cta + lane], ((t0 + sum / NM) & ~1u) | tag, (t0 & ~1u) | tag);
            }
        }
        mbar_wait(done0 + (NSTAGE + 2 - NS) * 8);
        const uint32_t ta = F_LATE_T, td = F_LATE_DT;
        uint4* odst = scr->outp + ((size_t)(pt >> 2) * NCTA + cta) * 4 + t;
        st_pub2x64(odst, tag ^ 1, 0, tag ^ 1, 0);
        const uint32_t fdst = (sb + pw * 2048 + lane * 16) ^ ((lane >> 3) * 16);
        clk.wait_base(sb, 1, ta);
        if (cta < NFFN) fetch16(fdst + slot_of(NSTAGE), pdn);
        asm volatile("cp.async.commit_group;" ::: "memory");
        clk.wait_base(sb, 1, ta + td);
        fetch16(fdst + slot_of(NSTAGE + 1), pwo);
        asm volatile("cp.async.commit_group;" ::: "memory");
        clk.wait_base(sb, 1, ta + 2 * td);
        fetch16(fdst + slot_of(NSTAGE + 2), pwo + 14336);
        asm volatile("cp.async.commit_group;" ::: "memory");
        bar_sync(BAR_H, 256);
        const uint2 h = *reinterpret_cast<const uint2*>(smem + SM_H + (g & 1) * 32 + t * 8);
        float c[4][4];
#pragma unroll
        for (int m = 0; m < 4; m++)
#pragma unroll
            for (int e = 0; e < 4; e++) c[m][e] = 0.f;
        const int r7 = ((lane & 7) >> 1) + 4 * (lane >> 4);
        const uint32_t aoff = sb + pw * 2048 + (r7 + 8 * (lane & 1)) * 128 + (((lane >> 3) & 1) ^ r7 ^ ((lane & 1) << 2)) * 16;
        const uint32_t obaddr = pin(sb + SM_OB + (g & 1) * 64 + t * 16), tt = pin(t);
        uint32_t a0[4][4], a1[4][4];
        frag16<2, slot_of(NSTAGE)>(a0, aoff);
        if (cta < NFFN) {
#pragma unroll
            for (int m = 0; m < 4; m++) mma16816(c[m], a0[m], h.x, h.y);
        }
        frag16<1, slot_of(NSTAGE + 1)>(a1, aoff);
        bar_sync(BAR_OB, 256);
        const uint4 ob = lds128(obaddr);
#pragma unroll
        for (int m = 0; m < 4; m++) mma16816(c[m], a1[m], ob.x, ob.y);
        frag16<0, slot_of(NSTAGE + 2)>(a0, aoff);
#pragma unroll
        for (int m = 0; m < 4; m++) mma16816(c[m], a0[m], ob.z, ob.w);
        st_pub2x64(odst, tagf(sel4(c[0], tt), tag), __float_as_uint(sel4(c[1], tt)), tagf(sel4(c[2], tt), tag), __float_as_uint(sel4(c[3], tt)));
    } else if (warp == 15) {
        if (lane < 4) reinterpret_cast<uint32_t*>(smem + SM_T0)[lane] = t0;
        __syncthreads();
        mbar_wait(full0 + B_X * 8);
        const uint32_t tag = (*reinterpret_cast<const uint32_t*>(smem + SM_X + 1792) + 1) & 1;
#pragma unroll 1
        for (int i = 0; i < 4; i++) {
            mbar_wait(full0 + (F_MEND + F_MGAP + 6 * i) * 8);
            uint2 v;
            int it = 0;
            do {
                v = ld_poll2(&scr->prog[i * 128 + lane * 4]);
                if (++it > SPIN_LIMIT) __trap();
            } while (warp_bad(bad2(v.x, v.y, tag)));
            const int nom = i == 0 ? F_NOM0 : i == 1 ? F_NOM1 : i == 2 ? F_NOM2 : F_NOM3;
            int base = (__reduce_add_sync(0xffffffffu, min(max((int)(v.x - t0), 0), 1 << 20)) >> 5) - nom;
            const int start = __reduce_add_sync(0xffffffffu, min(max((int)(v.y - t0), -(1 << 20)), 1 << 20)) >> 5;
            const int lag = max(lane == 0 ? base - start - SLACK : min(base - start, 2 * (base - start - DEAD)), 0);
            const int ahead = (lane == 0 ? nom : lane == 1 ? F_LATE_T : lane == 2 ? F_E2_T : F_E3_T - 150) - nom;
            const float rate = fminf(__fdividef((float)lag, (float)(nom - 500)), 0.045f);
            if (lane < 4) reinterpret_cast<volatile uint32_t*>(smem + SM_T0)[lane] = t0 + start + lag + (int)(rate * (float)ahead);
        }
    }
}

}

}

extern "C" void kernel_launch(void* const* d_in, const int* in_sizes, int n_in, void* d_out, int out_size) {
    (void)in_sizes; (void)n_in; (void)out_size;
    cudaLaunchConfig_t cfg = {};
    cfg.gridDim = dim3(NCTA); cfg.blockDim = dim3(NTHREADS); cfg.dynamicSmemBytes = SM_TOTAL; cfg.stream = cudaStreamPerThread;
    cudaLaunchAttribute at[1];
    at[0].id = cudaLaunchAttributeClusterDimension;
    at[0].val.clusterDim.x = 16; at[0].val.clusterDim.y = 1; at[0].val.clusterDim.z = 1;
    cfg.attrs = at; cfg.numAttrs = 1;

    static Scratch* scr = nullptr;
    static uint32_t scale = 64;
    static int nclusters = 0;
    if (!scr) {
        int dev = 0, khz = 0, bits = 0;
        cudaGetDevice(&dev);
        cudaDeviceGetAttribute(&khz, cudaDevAttrMemoryClockRate, dev);
        cudaDeviceGetAttribute(&bits, cudaDevAttrGlobalMemoryBusWidth, dev);
        if (khz > 0 && bits > 0) scale = (uint32_t)(64.0 * khz * bits / (2619000.0 * 5120.0) + 0.5);
        cudaFuncSetAttribute(fused_decode_kernel<false>, cudaFuncAttributeMaxDynamicSharedMemorySize, SM_TOTAL);
        cudaFuncSetAttribute(fused_decode_kernel<true>, cudaFuncAttributeMaxDynamicSharedMemorySize, SM_TOTAL);
        cudaFuncSetAttribute(flat::flat_decode_kernel<true>, cudaFuncAttributeMaxDynamicSharedMemorySize, SM_TOTAL);
        cudaFuncSetAttribute(fused_decode_kernel<false>, cudaFuncAttributeNonPortableClusterSizeAllowed, 1);
        cudaFuncSetAttribute(fused_decode_kernel<true>, cudaFuncAttributeNonPortableClusterSizeAllowed, 1);
        if (cudaOccupancyMaxActiveClusters(&nclusters, fused_decode_kernel<true>, &cfg) != cudaSuccess) nclusters = 0;
        (void)cudaGetLastError();
        cudaGetSymbolAddress(reinterpret_cast<void**>(&scr), g_scratch);
    }
    typedef const __nv_bfloat16* P;
    const P wq = (P)d_in[3], kc = (P)d_in[1], x = (P)d_in[0], vc = (P)d_in[2], wo = (P)d_in[4], wg = (P)d_in[6], wu = (P)d_in[7], wd = (P)d_in[8];
    __nv_bfloat16* out = (__nv_bfloat16*)d_out;
    if (nclusters < NCTA / 16)
        flat::flat_decode_kernel<true><<<flat::NCTA, flat::NTHREADS, SM_TOTAL, cudaStreamPerThread>>>(wq, kc, x, scr, vc, wo, wg, wu, wd, out, Clock<true>{scale});
    else if (scale == 64)
        cudaLaunchKernelEx(&cfg, fused_decode_kernel<false>, wq, kc, x, scr, vc, wo, wg, wu, wd, out, Clock<false>{scale});
    else
        cudaLaunchKernelEx(&cfg, fused_decode_kernel<true>, wq, kc, x, scr, vc, wo, wg, wu, wd, out, Clock<true>{scale});
}
```

```cpp
#include <cuda_runtime.h>
#include <cuda_bf16.h>
#include <stdint.h>

namespace {

constexpr int PACE_DT = 640;
constexpr int PACE_LEAD = 640;
constexpr int LATE_T = 22080;
constexpr int LATE_DT = 420;
constexpr int Q_T = 3650;
constexpr int E2_T = 23710;
constexpr int M_NOM0 = 4775;
constexpr int M_NOM1 = 9110;
constexpr int M_NOM2 = 13235;
constexpr int M_NOM3 = 17165;
constexpr int DEAD = 100;
constexpr int SLACK = 200;
constexpr int NM = 4;
constexpr int MEND = 7;
constexpr int MGAP = 4;
constexpr int LAST_DT = 100;

constexpr int D_MODEL = 448;
constexpr int SK      = 32768;
constexpr int WIN     = 4096;
constexpr int DH      = 256;
constexpr int QCOLS   = 4096;
constexpr int FF      = 1792;
constexpr int NCTA    = 112;
constexpr int NPT     = 128;
constexpr int NTHREADS = 448;

constexpr int NS     = 11;
constexpr int SLOT   = 16384;
constexpr int XROW   = 912;
constexpr int NR     = 19;
constexpr int S_K = 0, S_V = NR, NSTAGE = 2 * NR;
constexpr int S_GU   = 9;
constexpr int FFN_ST = S_GU + 13 - S_V;
constexpr int HID_ST = FFN_ST + 3;
constexpr int NBAR   = 40;
constexpr int B_X = NSTAGE, B_FIN = NSTAGE + 1, B_W = NBAR + NSTAGE;
constexpr int SROW = 616, PROW = 336;

constexpr int SM_RING  = 0;
constexpr int SM_WQ    = SM_RING + (NS - 2) * SLOT;
constexpr int SM_STRIP = SM_RING + NS * SLOT;
constexpr int SM_S    = SM_STRIP + 448 * 64;
constexpr int SM_P    = SM_S + 2 * SROW * 4;
constexpr int SM_Q    = SM_P + 2 * PROW * 4;
constexpr int SM_XN   = SM_Q + 2 * 264 * 2;
constexpr int SM_X    = SM_XN + 2 * XROW;
constexpr int SM_RED  = SM_X + 1792 + 32;
constexpr int SM_STAT = SM_RED + 7 * 64 * 4;
constexpr int SM_WGT  = SM_STAT + 2 * 8 * 2 * 4;
constexpr int SM_HID  = SM_WGT + 2 * 8 * 4;
constexpr int SM_OB   = SM_HID + 8 * 16 * 4;
constexpr int SM_IN   = (SM_OB + 8 * 2 * 16 * 4 + 127) / 128 * 128;
constexpr int SM_T0   = SM_IN + 4096;
constexpr int SM_BAR  = SM_T0 + 32;
constexpr int SM_TOTAL = SM_BAR + 2 * NBAR * 8;
static_assert(SM_Q % 16 == 0 && SM_XN % 16 == 0 && SM_X % 16 == 0 && SM_OB % 16 == 0 && SM_P % 16 == 0 && SM_IN % 16 == 0, "align");
static_assert(FFN_ST >= 1 && 2 * NS >= NR && NSTAGE % NS + 3 <= NS, "stage -> slot mapping");
static_assert(SM_TOTAL <= 232448 && B_X == 38 && B_FIN == 39, "shared memory");

constexpr int SPIN_LIMIT = 1 << 22;
constexpr float SCALE_LOG2E = 0.0625f * 1.4426950408889634f;

struct __align__(1024) Scratch {
    uint4    part[128 * 2 * 8 * 8];
    uint4    outp[56 * 128 * 4];
    uint2    q[16 * 2 * 7 * 128];
    uint4    hid[NCTA * 8];
    unsigned gu[128 * 32];
    uint2    ml[128 * 4];
    uint2    prog[4 * 32 * 4];
    unsigned epoch[128 * 8];
};
__device__ Scratch g_scratch;

__device__ __forceinline__ void mbar_init(uint32_t bar, uint32_t cnt) {
    asm volatile("mbarrier.init.shared::cta.b64 [%0], %1;" :: "r"(bar), "r"(cnt) : "memory");
}
__device__ __forceinline__ void mbar_arrive(uint32_t bar, uint32_t cnt) {
    asm volatile("mbarrier.arrive.shared::cta.b64 _, [%0], %1;" :: "r"(bar), "r"(cnt) : "memory");
}
template <bool SCALED>
struct Clock {
    uint32_t scale;
    __device__ __forceinline__ uint32_t now() const {
        if constexpr (SCALED) {
            uint64_t t;
            asm volatile("mov.u64 %0, %globaltimer;" : "=l"(t));
            return (uint32_t)((t * scale) >> 6);
        } else {
            uint32_t t;
            asm volatile("mov.u32 %0, %globaltimer_lo;" : "=r"(t));
            return t;
        }
    }
    __device__ __forceinline__ static uint32_t base(uint32_t sb, int i) {
        uint32_t t;
        asm volatile("ld.volatile.shared.u32 %0, [%1];" : "=r"(t) : "r"(sb + SM_T0 + 4 * i) : "memory");
        return t;
    }
    __device__ __forceinline__ void wait_until(uint32_t t0, uint32_t dt) const { while (now() - t0 < dt) {} }
    __device__ __forceinline__ void wait_base(uint32_t sb, int i, uint32_t dt) const { while (now() - base(sb, i) < dt) {} }
};
__device__ __forceinline__ void mbar_wait(uint32_t bar) {
    asm volatile("{\n.reg .pred p;\nWAIT_LOOP:\nmbarrier.try_wait.parity.shared::cta.b64 p, [%0], 0;\n@!p bra WAIT_LOOP;\n}" :: "r"(bar) : "memory");
}
__device__ __forceinline__ void cp_async16(uint32_t dst, const void* src) {
    asm volatile("{\n.reg .b64 pol;\ncreatepolicy.fractional.L2::evict_first.b64 pol, 1.0;\n"
                 "cp.async.cg.shared.global.L2::cache_hint [%0], [%1], 16, pol;\n}" :: "r"(dst), "l"(src) : "memory");
}
__device__ __forceinline__ void cp_async16_strip(uint32_t dst, const void* src) {
    asm volatile("{\n.reg .b64 pol;\ncreatepolicy.fractional.L2::evict_first.b64 pol, 1.0;\n"
                 "cp.async.cg.shared.global.L2::cache_hint.L2::128B [%0], [%1], 16, pol;\n}" :: "r"(dst), "l"(src) : "memory");
}
__device__ __forceinline__ void cp_async_arrive(uint32_t bar) {
    asm volatile("cp.async.mbarrier.arrive.noinc.shared::cta.b64 [%0];" :: "r"(bar) : "memory");
}
__device__ __forceinline__ void bar_sync(int id, int n)   { asm volatile("bar.sync %0, %1;" :: "r"(id), "r"(n) : "memory"); }
__device__ __forceinline__ void bar_arrive(int id, int n) { asm volatile("bar.arrive %0, %1;" :: "r"(id), "r"(n) : "memory"); }

__device__ __forceinline__ uint32_t ld_poll1(const void* p) {
    uint32_t v;
    asm volatile("ld.relaxed.gpu.global.u32 %0, [%1];" : "=r"(v) : "l"(p) : "memory");
    return v;
}
__device__ __forceinline__ uint2 ld_poll2(const void* p) {
    uint2 v;
    asm volatile("ld.relaxed.gpu.global.v2.u32 {%0,%1}, [%2];" : "=r"(v.x), "=r"(v.y) : "l"(p) : "memory");
    return v;
}
__device__ __forceinline__ uint2 ld_poll64(const void* p) {
    uint2 v;
    asm volatile("{\n.reg .b64 d;\nld.relaxed.gpu.global.b64 d, [%2];\nmov.b64 {%0,%1}, d;\n}" : "=r"(v.x), "=r"(v.y) : "l"(p) : "memory");
    return v;
}
__device__ __forceinline__ uint4 ld_poll2x64(const void* p) {
    uint4 v;
    asm volatile("{\n.reg .b64 d, e;\nld.relaxed.gpu.global.v2.b64 {d,e}, [%4];\nmov.b64 {%0,%1}, d;\nmov.b64 {%2,%3}, e;\n}"
                 : "=r"(v.x), "=r"(v.y), "=r"(v.z), "=r"(v.w) : "l"(p) : "memory");
    return v;
}
__device__ __forceinline__ void st_pub64(void* p, uint32_t a, uint32_t b) {
    asm volatile("{\n.reg .b64 d;\nmov.b64 d, {%1,%2};\nst.relaxed.gpu.global.b64 [%0], d;\n}" :: "l"(p), "r"(a), "r"(b) : "memory");
}
__device__ __forceinline__ void st_pub2(void* p, uint32_t a, uint32_t b) {
    asm volatile("st.relaxed.gpu.global.v2.u32 [%0], {%1,%2};" :: "l"(p), "r"(a), "r"(b) : "memory");
}
__device__ __forceinline__ void st_pub1(void* p, uint32_t a) {
    asm volatile("st.relaxed.gpu.global.u32 [%0], %1;" :: "l"(p), "r"(a) : "memory");
}
__device__ __forceinline__ uint32_t tagf(float v, uint32_t tag) {
    uint32_t r;
    asm("lop3.b32 %0, %1, 0xfffffffe, %2, 0xEA;" : "=r"(r) : "r"(__float_as_uint(v)), "r"(tag));
    return r;
}
__device__ __forceinline__ uint32_t pin(uint32_t v) {
    uint32_t r;
    asm volatile("shfl.sync.bfly.b32 %0, %1, 0, 0x1f, 0xffffffff;" : "=r"(r) : "r"(v));
    return r;
}
template <class T>
__device__ __forceinline__ T* pin(T* p) {
    const uint64_t u = reinterpret_cast<uint64_t>(p);
    return reinterpret_cast<T*>(((uint64_t)pin((uint32_t)(u >> 32)) << 32) | pin((uint32_t)u));
}
__device__ __forceinline__ void sts32(uint32_t addr, uint32_t v) { asm volatile("st.shared.u32 [%0], %1;" :: "r"(addr), "r"(v) : "memory"); }
__device__ __forceinline__ float lds32(uint32_t addr) { float v; asm volatile("ld.shared.f32 %0, [%1];" : "=f"(v) : "r"(addr) : "memory"); return v; }
__device__ __forceinline__ uint4 lds128(uint32_t addr) {
    uint4 v;
    asm volatile("ld.shared.v4.u32 {%0,%1,%2,%3}, [%4];" : "=r"(v.x), "=r"(v.y), "=r"(v.z), "=r"(v.w) : "r"(addr) : "memory");
    return v;
}
__device__ __forceinline__ uint32_t bad2(uint32_t a, uint32_t b, uint32_t tag) {
    uint32_t r;
    asm("lop3.b32 %0, %1, %2, %3, 0x7E;" : "=r"(r) : "r"(a), "r"(b), "r"(tag));
    return r;
}
__device__ __forceinline__ uint32_t bad4(const uint4& v, uint32_t tag) { return bad2(v.x, v.y, tag) | bad2(v.z, v.w, tag); }
__device__ __forceinline__ bool warp_bad(uint32_t bad) { return __any_sync(0xffffffffu, bad & 1u); }

__device__ __forceinline__ void poll4(float (&f)[2][4], const uint2* p, const uint2* p2, uint32_t tag, const float (&w)[4]) {
    uint32_t y[8];
    asm volatile("{\n.reg .pred p0, p1, p2, p3, q;\n.reg .b32 a, m, it;\n.reg .b64 d<4>;\n"
                 "setp.eq.u32 p0, 0, 0;\nsetp.eq.u32 p1, 0, 0;\nsetp.eq.u32 p2, 0, 0;\nsetp.eq.u32 p3, 0, 0;\n"
                 "mov.u32 it, %11;\n"
                 "POLL_LOOP:\n"
                 "@p0 ld.relaxed.gpu.global.b64 d0, [%8];\n"
                 "@p1 ld.relaxed.gpu.global.b64 d1, [%9];\n"
                 "@p2 ld.relaxed.gpu.global.b64 d2, [%8+512];\n"
                 "@p3 ld.relaxed.gpu.global.b64 d3, [%9+512];\n"
                 "sub.u32 it, it, 1;\n"
                 "min.u32 m, it, 1;\n"
                 "mov.b64 {%0,%1}, d0;\nmov.b64 {%2,%3}, d1;\nmov.b64 {%4,%5}, d2;\nmov.b64 {%6,%7}, d3;\n"
                 "lop3.b32 a, %0, %10, m, 0x28;\nsetp.ne.u32 p0, a, 0;\nlop3.b32 a, %2, %10, m, 0x28;\nsetp.ne.u32 p1, a, 0;\n"
                 "lop3.b32 a, %4, %10, m, 0x28;\nsetp.ne.u32 p2, a, 0;\nlop3.b32 a, %6, %10, m, 0x28;\nsetp.ne.u32 p3, a, 0;\n"
                 "or.pred q, p0, p1;\nor.pred q, q, p2;\nor.pred q, q, p3;\nvote.sync.any.pred q, q, 0xffffffff;\n"
                 "@q bra POLL_LOOP;\n}"
                 : "=&r"(y[0]), "=&r"(y[1]), "=&r"(y[2]), "=&r"(y[3]), "=&r"(y[4]), "=&r"(y[5]), "=&r"(y[6]), "=&r"(y[7])
                 : "l"(p), "l"(p2), "r"(tag), "n"(SPIN_LIMIT) : "memory");
#pragma unroll
    for (int b = 0; b < 2; b++) {
        const uint32_t* u = y + 4 * b;
        f[b][0] = fmaf(w[2 * b], __uint_as_float((u[0] ^ tag) << 16), w[2 * b + 1] * __uint_as_float((u[2] ^ tag) << 16));
        f[b][1] = fmaf(w[2 * b], __uint_as_float(u[0] & 0xffff0000u), w[2 * b + 1] * __uint_as_float(u[2] & 0xffff0000u));
        f[b][2] = fmaf(w[2 * b], __uint_as_float(u[1] << 16), w[2 * b + 1] * __uint_as_float(u[3] << 16));
        f[b][3] = fmaf(w[2 * b], __uint_as_float(u[1] & 0xffff0000u), w[2 * b + 1] * __uint_as_float(u[3] & 0xffff0000u));
    }
}

__device__ __forceinline__ void ldsm4(uint32_t addr, uint32_t (&a)[4]) {
    asm volatile("ldmatrix.sync.aligned.m8n8.x4.shared.b16 {%0,%1,%2,%3}, [%4];" : "=r"(a[0]), "=r"(a[1]), "=r"(a[2]), "=r"(a[3]) : "r"(addr) : "memory");
}
__device__ __forceinline__ void ldsm4t(uint32_t addr, uint32_t (&a)[4]) {
    asm volatile("ldmatrix.sync.aligned.m8n8.x4.trans.shared.b16 {%0,%1,%2,%3}, [%4];" : "=r"(a[0]), "=r"(a[1]), "=r"(a[2]), "=r"(a[3]) : "r"(addr) : "memory");
}
__device__ __forceinline__ void mma16816(float (&c)[4], const uint32_t (&a)[4], uint32_t b0, uint32_t b1) {
    asm volatile("mma.sync.aligned.m16n8k16.row.col.f32.bf16.bf16.f32 {%0,%1,%2,%3}, {%4,%5,%6,%7}, {%8,%9}, {%0,%1,%2,%3};"
                 : "+f"(c[0]), "+f"(c[1]), "+f"(c[2]), "+f"(c[3]) : "r"(a[0]), "r"(a[1]), "r"(a[2]), "r"(a[3]), "r"(b0), "r"(b1));
}
__device__ __forceinline__ float bf_lo(uint32_t u) { return __uint_as_float(u << 16); }
__device__ __forceinline__ float bf_hi(uint32_t u) { return __uint_as_float(u & 0xffff0000u); }
__device__ __forceinline__ float rbf(float v) { return __bfloat162float(__float2bfloat16_rn(v)); }
__device__ __forceinline__ uint32_t pack_bf(float lo, float hi) {
    uint32_t r;
    asm("cvt.rn.bf16x2.f32 %0, %1, %2;" : "=r"(r) : "f"(hi), "f"(lo));
    return r;
}
__device__ __forceinline__ float sel4(const float (&c)[4], int t) {
    float a = (t & 1) ? c[1] : c[0];
    float b = (t & 1) ? c[3] : c[2];
    return (t & 2) ? b : a;
}
__device__ __forceinline__ float ex2(float x) { float y; asm("ex2.approx.ftz.f32 %0, %1;" : "=f"(y) : "f"(x)); return y; }
__device__ __forceinline__ float sqrt_approx(float x) { float y; asm("sqrt.approx.f32 %0, %1;" : "=f"(y) : "f"(x)); return y; }

__host__ __device__ constexpr uint32_t slot_of(int s) { return SM_RING + (s % NS) * SLOT; }

__device__ __forceinline__ void layernorm(unsigned char* smem, int lane, int b0, int b1) {
#pragma unroll 1
    for (int b = b0; b < b1; b++) {
        uint32_t xs[7];
#pragma unroll
        for (int i = 0; i < 7; i++) xs[i] = reinterpret_cast<const uint32_t*>(smem + SM_X)[b * (D_MODEL / 2) + i * 32 + lane];
        float sum = 0.f;
#pragma unroll
        for (int i = 0; i < 7; i++) sum += bf_lo(xs[i]) + bf_hi(xs[i]);
#pragma unroll
        for (int o = 16; o > 0; o >>= 1) sum += __shfl_xor_sync(0xffffffffu, sum, o);
        const float mean = sum * (1.0f / D_MODEL);
        float sq = 0.f;
#pragma unroll
        for (int i = 0; i < 7; i++) {
            const float d0 = bf_lo(xs[i]) - mean, d1 = bf_hi(xs[i]) - mean;
            sq = fmaf(d0, d0, fmaf(d1, d1, sq));
        }
#pragma unroll
        for (int o = 16; o > 0; o >>= 1) sq += __shfl_xor_sync(0xffffffffu, sq, o);
        const float mb = rbf(mean);
        const float sd = rbf(sqrt_approx(rbf(rbf(sq * (1.0f / D_MODEL)) + 1e-5f)));
#pragma unroll
        for (int i = 0; i < 7; i++)
            reinterpret_cast<uint32_t*>(smem + SM_XN + b * XROW)[i * 32 + lane] =
                pack_bf(__fdividef(rbf(bf_lo(xs[i]) - mb), sd), __fdividef(rbf(bf_hi(xs[i]) - mb), sd));
    }
}

__device__ __forceinline__ void strip_partial(uint32_t sb, uint32_t strip, unsigned char* smem, int warp, int lane) {
    float c[2][2][4];
#pragma unroll
    for (int n = 0; n < 2; n++)
#pragma unroll
        for (int e = 0; e < 4; e++) c[n][0][e] = c[n][1][e] = 0.f;
    const uint32_t ba = sb + SM_XN + (lane & 1) * XROW + (lane >> 3) * 16 + warp * 128;
    const uint32_t aa = sb + strip + (warp * 64 + (lane & 7) + (lane >> 4) * 8) * 64 + (((lane >> 3) & 1) ^ ((lane & 7) >> 1)) * 16;
#pragma unroll
    for (int k2 = 0; k2 < 2; k2++) {
        uint32_t b[4];
        ldsm4(ba + k2 * 64, b);
#pragma unroll
        for (int n = 0; n < 2; n++) {
            uint32_t a0[4], a1[4];
            ldsm4t((aa ^ (n * 32)) + k2 * 2048, a0);
            ldsm4t((aa ^ (n * 32)) + k2 * 2048 + 1024, a1);
            mma16816(c[n][0], a0, b[0], b[1]);
            mma16816(c[n][1], a1, b[2], b[3]);
        }
    }
    float* red = reinterpret_cast<float*>(smem + SM_RED) + warp * 64 + lane;
#pragma unroll
    for (int n = 0; n < 2; n++) red[n * 32] = sel4(c[n][0], lane & 3) + sel4(c[n][1], lane & 3);
}
__device__ __forceinline__ float strip_sum(const unsigned char* smem, int idx) {
    const float* red = reinterpret_cast<const float*>(smem + SM_RED) + idx;
    return ((red[0] + red[64]) + (red[128] + red[192])) + ((red[256] + red[320]) + red[384]);
}

__device__ __forceinline__ void fetch16(uint32_t dst, const char* src) {
#pragma unroll
    for (int i = 0; i < 4; i++) cp_async16((dst ^ (((i & 1) ^ (i >> 1)) * 64)) + i * 512, src + i * (4 * 896));
}
template <int PENDING, int OFF>
__device__ __forceinline__ void frag32(uint32_t (&a)[2][4][4], uint32_t addr) {
    asm volatile("cp.async.wait_group %0;" :: "n"(PENDING) : "memory");
    __syncwarp();
#pragma unroll
    for (int h = 0; h < 2; h++)
#pragma unroll
        for (int m = 0; m < 4; m++) ldsm4t((addr ^ (m * 32)) + OFF + h * 2048, a[h][m]);
}
__device__ __forceinline__ void mma32(float (&c)[4][4], const uint32_t (&a)[2][4][4], const uint4& b) {
#pragma unroll
    for (int m = 0; m < 4; m++) mma16816(c[m], a[0][m], b.x, b.y);
#pragma unroll
    for (int m = 0; m < 4; m++) mma16816(c[m], a[1][m], b.z, b.w);
}

__device__ __forceinline__ void load_x(uint32_t sb, const void* x, const void* epoch) {
    const uint32_t full0 = sb + SM_BAR;
    mbar_init(full0 + B_X * 8, 1);
    asm volatile("fence.mbarrier_init.release.cluster;" ::: "memory");
    asm volatile("mbarrier.arrive.expect_tx.shared::cta.b64 _, [%0], %1;" :: "r"(full0 + B_X * 8), "r"(1792 + 16) : "memory");
    asm volatile("cp.async.bulk.shared::cluster.global.mbarrier::complete_tx::bytes [%0], [%1], %2, [%3];"
                 :: "r"(sb + SM_X), "l"(x), "r"(1792), "r"(full0 + B_X * 8) : "memory");
    asm volatile("cp.async.bulk.shared::cluster.global.mbarrier::complete_tx::bytes [%0], [%1], %2, [%3];"
                 :: "r"(sb + SM_X + 1792), "l"(epoch), "r"(16), "r"(full0 + B_X * 8) : "memory");
}

enum { BAR_CONS = 1, BAR_LN = 2, BAR_FF = 3, BAR_WGT = 4, BAR_H = 5, BAR_OB = 8   };

template <bool SCALED>
__global__ void __launch_bounds__(NTHREADS, 1)
fused_decode_kernel(const __nv_bfloat16* __restrict__ wq, const __nv_bfloat16* __restrict__ kc, const __nv_bfloat16* __restrict__ x,
                    Scratch* __restrict__ scr, const __nv_bfloat16* __restrict__ vc, const __nv_bfloat16* __restrict__ wo,
                    const __nv_bfloat16* __restrict__ wg, const __nv_bfloat16* __restrict__ wu, const __nv_bfloat16* __restrict__ wd,
                    __nv_bfloat16* __restrict__ out, const Clock<SCALED> clk) {
    extern __shared__ __align__(128) unsigned char smem[];
    const uint32_t sb = (uint32_t)__cvta_generic_to_shared(smem);
    const int tid = threadIdx.x, lane = tid & 31;
    const int cta = blockIdx.x;
    const int cl = cta >> 4, rk = cta & 15;
    const uint32_t full0 = sb + SM_BAR, done0 = full0 + NBAR * 8;
    asm volatile("{\n.reg .pred p;\nsetp.lt.u32 p, %1, 128;\n@p prefetch.global.L2 [%0];\n}"
                 :: "l"(reinterpret_cast<const char*>(wq) + cta * 32768 + (uint32_t)tid * 128), "r"(tid));
    if (tid < 256) {
        const char* src = reinterpret_cast<const char*>(wq) + (uint32_t)((cl * 64 + (tid >> 5)) * (QCOLS * 2) + rk * 512 + lane * 16);
        const uint32_t dst = (sb + SM_WQ + tid * 16) ^ ((tid >> 5) * 16);
#pragma unroll
        for (int i = 0; i < 8; i++) cp_async16(dst + i * 4096, src + i * (8 * QCOLS * 2));
        const uint32_t now = clk.now();
        if (tid < 4) sts32(sb + SM_T0 + tid * 4, now);
    }
    const int warp = __shfl_sync(0xffffffffu, tid >> 5, 0);
    const int hkv = rk >> 1, bat = rk & 1;
    const int e0 = (2 * rk) % 7;
    const int extra = cl == e0 ? 0 : cl == (e0 + 1) % 7 ? 1 : -1;
    const int g = lane >> 2, t = lane & 3;
    if (warp >= 8 && warp < 12 && lane == 0) {
        const uint32_t b0 = full0 + (warp - 8) * 80;
#pragma unroll
        for (int i = 0; i < 10; i++) mbar_init(b0 + (NBAR + i) * 8, 8);
#pragma unroll
        for (int i = 0; i < 8; i++) mbar_init(b0 + i * 8, NPT);
        if (warp < 11) {
            mbar_init(b0 + 64, NPT); mbar_init(b0 + 72, NPT);
        } else {
            mbar_init(full0 + B_FIN * 8, 1);
            asm volatile("mbarrier.arrive.expect_tx.shared::cta.b64 _, [%0], %1;" :: "r"(full0 + B_FIN * 8), "r"(4096) : "memory");
            asm volatile("fence.mbarrier_init.release.cluster;" ::: "memory");
        }
    }
    if (tid == 384) load_x(sb, x, &scr->epoch[cta * 8]);
    __syncthreads();
    const uint32_t t0 = clk.base(sb, 3);
    asm volatile("barrier.cluster.arrive.relaxed.aligned;" ::: "memory");
    if (warp == 12 || warp == 13) {
        if (warp == 13) asm volatile("barrier.cluster.wait.aligned;" ::: "memory");
        mbar_wait(full0 + B_X * 8);
        layernorm(smem, lane, warp - 12, warp - 11);
        bar_arrive(BAR_LN, 320);
    }

    if (warp < 8) {
        mbar_wait(full0 + B_X * 8);
        const uint32_t epoch = *reinterpret_cast<const uint32_t*>(smem + SM_X + 1792);
        const uint32_t tag = pin((epoch + 1) & 1);
        const uint32_t voff = ((lane & 7) + (lane >> 4) * 8) * 512 + ((warp * 4 + ((lane >> 3) & 1) * 2) ^ (lane & 7)) * 16;
        {
            asm volatile("cp.async.wait_all;" ::: "memory");
            bar_sync(BAR_LN, 320);
            float c0[4] = {0.f, 0.f, 0.f, 0.f}, c1[4] = {0.f, 0.f, 0.f, 0.f};
#pragma unroll
            for (int h = 0; h < 2; h++) {
                uint32_t b[4], a[4][4];
                ldsm4(sb + SM_XN + (lane & 1) * XROW + (lane >> 3) * 16 + cl * 128 + h * 64, b);
#pragma unroll
                for (int i = 0; i < 4; i++) ldsm4t(sb + (voff ^ ((i & 1) * 16)) + SM_WQ + h * SLOT + (i >> 1) * 8192, a[i]);
                mma16816(c0, a[0], b[0], b[1]);
                mma16816(c1, a[1], b[0], b[1]);
                mma16816(c0, a[2], b[2], b[3]);
                mma16816(c1, a[3], b[2], b[3]);
            }
            st_pub64(scr->q + ((rk * 2 + (t & 1)) * 7 + cl) * 128 + warp * 16 + (t >> 1) * 8 + g, tagf(sel4(c0, t), tag), __float_as_uint(sel4(c1, t)));
            __syncwarp();
            if (lane == 0) mbar_arrive(full0 + B_W * 8, 1);
            const uint2* qp = scr->q + ((hkv * 2 + (tid >> 7)) * 2 + bat) * (7 * 128) + (tid & 127);
            clk.wait_until(t0, Q_T);
            uint2 v[7];
            int it = 0;
            uint32_t bad;
            do {
                bad = 0;
#pragma unroll
                for (int i = 0; i < 7; i++) v[i] = ld_poll64(qp + i * 128);
#pragma unroll
                for (int i = 0; i < 7; i++) { v[i].x ^= tag; bad |= v[i].x; }
                if (++it > SPIN_LIMIT) __trap();
            } while (warp_bad(bad));
            float q0 = 0.f, q1 = 0.f;
#pragma unroll
            for (int i = 0; i < 7; i++) { q0 += __uint_as_float(v[i].x); q1 += __uint_as_float(v[i].y); }
            __nv_bfloat16* qs = reinterpret_cast<__nv_bfloat16*>(smem + SM_Q + (tid >> 7) * 528) + ((tid & 127) >> 3) * 16 + (tid & 7);
            qs[0] = __float2bfloat16_rn(q0);
            qs[8] = __float2bfloat16_rn(q1);
        }
        bar_sync(BAR_CONS, 256);
        if (tid == 96) scr->epoch[cta * 8] = epoch + 1;
        {
            uint32_t qf[8][4];
#pragma unroll
            for (int k2 = 0; k2 < 8; k2++) ldsm4(sb + SM_Q + (lane & 1) * 528 + k2 * 64 + (lane >> 3) * 16, qf[k2]);
            const int mt = warp & 1;
            const uint32_t aoff = (16 * mt + (lane & 15)) * 512 + ((lane >> 4) ^ (lane & 7)) * 16;
            float* sc = reinterpret_cast<float*>(smem + SM_S) + (t & 1) * SROW + (g >> 1) * 8 + (2 * mt + (t >> 1)) * 2 + (g & 1);
#pragma unroll 1
            for (int k = warp >> 1; k < NR; k += 4) {
                const int s = S_K + k;
                mbar_wait(full0 + s * 8);
                const uint32_t base = sb + SM_RING + (s >= NS ? s - NS : s) * SLOT + aoff;
                float c0[4] = {0.f, 0.f, 0.f, 0.f}, c1[4] = {0.f, 0.f, 0.f, 0.f};
#pragma unroll
                for (int k2 = 0; k2 < 8; k2++) {
                    uint32_t a0[4], a1[4];
                    ldsm4((base ^ ((k2 & 1) * 64)) + (k2 >> 1) * 128, a0);
                    ldsm4((base ^ ((k2 & 1) * 64 + 32)) + (k2 >> 1) * 128, a1);
                    mma16816(c0, a0, qf[k2][0], qf[k2][1]);
                    mma16816(c1, a1, qf[k2][2], qf[k2][3]);
                }
                __syncwarp();
                if (lane == 0) mbar_arrive(done0 + s * 8, 4);
                sc[k * 32] = rbf(sel4(c0, t) + sel4(c1, t));
            }
        }
        bar_sync(BAR_CONS, 256);
        {
            constexpr float C = SCALE_LOG2E;
            const float* sc = reinterpret_cast<const float*>(smem + SM_S);
            float* stat = reinterpret_cast<float*>(smem + SM_STAT);
            const bool two = tid < 48 && (tid >= 16 || extra >= 0);
            float2 s[2][2];
#pragma unroll
            for (int h = 0; h < 2; h++) {
                s[h][0] = *reinterpret_cast<const float2*>(sc + h * SROW + 96 + 2 * tid);
                s[h][1] = two ? *reinterpret_cast<const float2*>(sc + h * SROW + 2 * tid) : s[h][0];
            }
            float m0 = fmaxf(fmaxf(s[0][0].x, s[0][0].y), fmaxf(s[0][1].x, s[0][1].y));
            float m1 = fmaxf(fmaxf(s[1][0].x, s[1][0].y), fmaxf(s[1][1].x, s[1][1].y));
#pragma unroll
            for (int o = 16; o > 0; o >>= 1) {
                m0 = fmaxf(m0, __shfl_xor_sync(0xffffffffu, m0, o));
                m1 = fmaxf(m1, __shfl_xor_sync(0xffffffffu, m1, o));
            }
            if (lane == 0) *reinterpret_cast<float2*>(stat + warp * 2) = make_float2(m0, m1);
            bar_sync(BAR_CONS, 256);
#pragma unroll
            for (int w = 0; w < 8; w++) {
                const float2 mm = *reinterpret_cast<const float2*>(stat + w * 2);
                m0 = fmaxf(m0, mm.x); m1 = fmaxf(m1, mm.y);
            }
            uint32_t* ps = reinterpret_cast<uint32_t*>(smem + SM_P);
            float l[2];
#pragma unroll
            for (int h = 0; h < 2; h++) {
                const float m = h ? m1 : m0;
                const float pa = ex2((s[h][0].x - m) * C), pb = ex2((s[h][0].y - m) * C);
                const float pc = ex2((s[h][1].x - m) * C), pd = ex2((s[h][1].y - m) * C);
                ps[h * PROW + 48 + tid] = pack_bf(pa, pb);
                if (two) ps[h * PROW + tid] = pack_bf(pc, pd);
                l[h] = (pa + pb) + (two ? pc + pd : 0.f);
            }
#pragma unroll
            for (int o = 16; o > 0; o >>= 1) {
                l[0] += __shfl_xor_sync(0xffffffffu, l[0], o);
                l[1] += __shfl_xor_sync(0xffffffffu, l[1], o);
            }
            if (lane == 0) *reinterpret_cast<float2*>(stat + 16 + warp * 2) = make_float2(l[0], l[1]);
            bar_sync(BAR_CONS, 256);
            if (tid < 4) {
                float ls = 0.f;
#pragma unroll
                for (int w = 0; w < 8; w++) ls += stat[16 + w * 2 + (tid & 1)];
                st_pub2(scr->ml + cta * 4 + tid, tagf((tid & 1) ? m1 : m0, tag), tagf(ls, tag));
            }
        }
        {
            float own = 0.f;
            float o0[4] = {0.f, 0.f, 0.f, 0.f}, o1[4] = {0.f, 0.f, 0.f, 0.f};
            float o2[4] = {0.f, 0.f, 0.f, 0.f}, o3[4] = {0.f, 0.f, 0.f, 0.f};
            const uint4* ps = reinterpret_cast<const uint4*>(smem + SM_P + (g & 1) * PROW * 4) + t;
            uint2* dst = reinterpret_cast<uint2*>(scr->part) + ((size_t)(hkv * 16 + (t & 1) * 8 + warp) * 16 + bat * 8 + cl) * 8 + g;
#pragma unroll
            for (int k = 0; k < NR; k++) {
                if (k != 0 || extra >= 0) {
                    const uint4 pa = ps[k * 4];
                    mbar_wait(full0 + (S_V + k) * 8);
                    uint32_t a[4][4];
#pragma unroll
                    for (int i = 0; i < 4; i++) ldsm4t(sb + (voff ^ ((i & 1) * 16)) + slot_of(S_V + k) + (i >> 1) * 8192, a[i]);
                    mma16816(o0, a[0], pa.x, pa.y);
                    mma16816(o1, a[1], pa.x, pa.y);
                    mma16816(o2, a[2], pa.z, pa.w);
                    mma16816(o3, a[3], pa.z, pa.w);
                }
                if (S_V + k + NS < NSTAGE + 3) {
                    __syncwarp();
                    if (lane == 0) mbar_arrive(done0 + (S_V + k) * 8, 1);
                }
                if (k == FFN_ST && warp < 7) {
                    strip_partial(sb, SM_STRIP, smem, warp, lane);
                    bar_arrive(BAR_FF, 256);
                }
                if (k == FFN_ST && warp == 7) {
                    bar_sync(BAR_FF, 256);
                    own = rbf(strip_sum(smem, (cta & 1) * 32 + lane));
                    st_pub1(scr->gu + (cta ^ 1) * 32 + lane, (pack_bf(0.f, strip_sum(smem, (~cta & 1) * 32 + lane)) & 0xffff0000u) | tag);
                }
                if (k == HID_ST && warp == 7) {
                    const uint2* mlp = scr->ml + (min(g, 6) * 16 + (rk & ~1)) * 4 + (rk & 1);
                    uint2 a, b;
                    uint32_t other;
                    int it = 0;
                    do {
                        a = ld_poll2(mlp); b = ld_poll2(mlp + 4); other = ld_poll1(scr->gu + cta * 32 + lane);
                        if (++it > SPIN_LIMIT) __trap();
                    } while (warp_bad(bad2(a.x, a.y, tag) | bad2(b.x, b.y, tag) | (other ^ tag)));
                    float ga = (cta & 1) ? bf_hi(other) : own;
                    ga *= (ga > 0.f ? 1.f : 0.f);
                    const float hv = ga * ((cta & 1) ? own : bf_hi(other));
                    const uint32_t w = pack_bf(hv, __shfl_xor_sync(0xffffffffu, hv, 2));
                    if (!(t & 2)) st_pub64(reinterpret_cast<uint2*>(scr->hid) + cta * 16 + (t & 1) * 8 + (g & 3) * 2 + (g >> 2), tag, w);
                    const float m[2] = {bf_hi(a.x), bf_hi(b.x)};
                    const float l[2] = {__uint_as_float(a.y ^ tag), __uint_as_float(b.y ^ tag)};
#pragma unroll
                    for (int bb = 0; bb < 2; bb++) {
                        float M = m[bb];
                        M = fmaxf(M, __shfl_xor_sync(0xffffffffu, M, 4));
                        M = fmaxf(M, __shfl_xor_sync(0xffffffffu, M, 8));
                        M = fmaxf(M, __shfl_xor_sync(0xffffffffu, M, 16));
                        const float e = g < 7 ? ex2((m[bb] - M) * SCALE_LOG2E) : 0.f;
                        float L = e * l[bb];
                        L += __shfl_xor_sync(0xffffffffu, L, 4);
                        L += __shfl_xor_sync(0xffffffffu, L, 8);
                        L += __shfl_xor_sync(0xffffffffu, L, 16);
                        if (t == 0) reinterpret_cast<float*>(smem + SM_WGT)[bb * 8 + g] = __fdividef(e, L);
                    }
                }
            }
            const bool h1 = t & 1;
            const float va = h1 ? o0[1] + o2[1] : o0[0] + o2[0], vb = h1 ? o1[1] + o3[1] : o1[0] + o3[0];
            const float vc2 = h1 ? o0[3] + o2[3] : o0[2] + o2[2], vd = h1 ? o1[3] + o3[3] : o1[2] + o3[2];
            if (t < 2) st_pub64(dst, (__byte_perm(__float_as_uint(va) + 0x10000u, pack_bf(0.f, vb), 0x7632) & ~1u) | tag, pack_bf(vc2, vd));
        }
        {
            bar_sync(BAR_WGT, 256);
            const uint2* pp = pin(reinterpret_cast<const uint2*>(scr->part) + (size_t)(rk * 8 + warp) * 128 + lane);
            const uint2* pp2 = pin(reinterpret_cast<const uint2*>(scr->part) + (size_t)(rk * 8 + warp) * 128 + lane + (lane < 24 ? 32 : 24));
            const uint32_t obaddr = pin(sb + SM_OB + warp * 128 + (lane >> 4) * 64 + (lane & 3) * 16 + ((lane >> 3) & 1) * 8 + ((lane >> 2) & 1) * 4), ll = pin(lane);
            float w[4];
#pragma unroll
            for (int i = 0; i < 4; i++) w[i] = lds32(sb + SM_WGT + (i * 4 + (lane >> 3)) * 4);
            clk.wait_until(clk.base(sb, 2), E2_T);
            float f[2][4];
            poll4(f, pp, pp2, tag, w);
            const bool h16 = ll & 16, h8 = ll & 8;
            float r4[4], r2[2];
#pragma unroll
            for (int e = 0; e < 4; e++) r4[e] = (h16 ? f[1][e] : f[0][e]) + __shfl_xor_sync(0xffffffffu, h16 ? f[0][e] : f[1][e], 16);
#pragma unroll
            for (int e = 0; e < 2; e++) r2[e] = (h8 ? r4[2 + e] : r4[e]) + __shfl_xor_sync(0xffffffffu, h8 ? r4[e] : r4[2 + e], 8);
            sts32(obaddr, pack_bf(r2[0], r2[1]));
            bar_arrive(BAR_OB + (warp >> 1), 96);
        }
    } else if (warp < 12) {
        const int pt = tid - 256, pw = warp - 8;
        {
            const size_t kvoff = ((size_t)(bat * 8 + hkv) * SK + (SK - WIN)) * DH * 2 + pt * 16;
            const char* base = reinterpret_cast<const char*>(kc) + kvoff;
            const __nv_bfloat16* gu = ((cta & 1) ? wu : wg) + (cta >> 1) * 32 + (pt & 3) * 8 + (size_t)(pt >> 2) * FF;
            uint32_t sdst = sb + SM_STRIP + (pt >> 2) * 64 + ((pt & 3) ^ ((pt >> 3) & 3)) * 16;
            const uint32_t kvdst = (sb + pt * 16) ^ (pw * 16);
            int unit = extra, slot = 0;
            int kb = 3584;
#pragma unroll 1
            for (int s = 0; s < NSTAGE; s++) {
                if (s >= NS - 2) mbar_wait(s >= NS ? done0 + (s - NS) * 8 : full0 + B_W * 8);
                const char* src = base + unit * SLOT;
                const uint32_t dst = kvdst + slot * SLOT;
                const bool strip = (unsigned)(s - S_GU) < 14;
                clk.wait_base(sb, 0, (kb * PACE_DT >> 11) - PACE_LEAD);
                if (unit >= 0) {
#pragma unroll
                    for (int i = 0; i < 8; i++) cp_async16((dst ^ ((i & 1) * 64)) + i * 2048, src + i * 2048);
                }
                if (strip) { cp_async16_strip(sdst, gu); sdst += 2048; gu += 32 * FF; kb += 224; }
                cp_async_arrive(full0 + s * 8);
                kb += unit < 2 ? 512 : 1792;
                unit = unit < 2 ? 2 + cl : unit + 7;
                if (s == S_V - 1) { unit = extra; base = reinterpret_cast<const char*>(vc) + kvoff; }
                slot = slot == NS - 1 ? 0 : slot + 1;
            }
        }
        mbar_wait(done0 + (NSTAGE + 2 - NS) * 8);
        const char* pdn = reinterpret_cast<const char*>(wd) + (size_t)(rk * 112 + pw * 32 + (lane >> 3)) * 896 + cl * 128 + (lane & 7) * 16;
        const char* pwo = reinterpret_cast<const char*>(wo) + (size_t)(rk * 256 + pw * 64 + (lane >> 3)) * 896 + cl * 128 + (lane & 7) * 16;
        const uint32_t ta = LATE_T, td = LATE_DT;
        const uint32_t fdst = (sb + pw * 4096 + lane * 16) ^ ((lane >> 3) * 16);
        clk.wait_base(sb, 1, ta);
        fetch16(fdst + slot_of(NSTAGE), pdn);
        if (pw < 3) fetch16(fdst + slot_of(NSTAGE) + 2048, pdn + 16 * 896);
        asm volatile("cp.async.commit_group;" ::: "memory");
        clk.wait_base(sb, 1, ta + td);
        fetch16(fdst + slot_of(NSTAGE + 1), pwo);
        fetch16(fdst + slot_of(NSTAGE + 1) + 2048, pwo + 16 * 896);
        asm volatile("cp.async.commit_group;" ::: "memory");
        clk.wait_base(sb, 1, ta + 2 * td);
        fetch16(fdst + slot_of(NSTAGE + 2), pwo + 32 * 896);
        asm volatile("cp.async.commit_group;" ::: "memory");
        clk.wait_base(sb, 1, ta + 2 * td + LAST_DT);
        fetch16(fdst + slot_of(NSTAGE + 2) + 2048, pwo + 48 * 896);
        asm volatile("cp.async.commit_group;" ::: "memory");
        bar_sync(BAR_H, 160);
        const uint2 h0 = *reinterpret_cast<const uint2*>(smem + SM_HID + pw * 128 + (lane & 7) * 8);
        const uint2 h1 = *reinterpret_cast<const uint2*>(smem + SM_HID + pw * 128 + 64 + (lane & 7) * 8);
        uint32_t rdst, rbar;
        asm volatile("mapa.shared::cluster.u32 %0, %1, %2;" : "=r"(rdst) : "r"(sb + SM_IN + (rk * 4 + pw) * 64 + (t ^ (pw & 2)) * 16), "r"(g * 2));
        asm volatile("mapa.shared::cluster.u32 %0, %1, %2;" : "=r"(rbar) : "r"(full0 + B_FIN * 8), "r"(g * 2));
        rdst = pin(rdst); rbar = pin(rbar);
        float c[4][4];
#pragma unroll
        for (int m = 0; m < 4; m++)
#pragma unroll
            for (int e = 0; e < 4; e++) c[m][e] = 0.f;
        const int r7 = ((lane & 7) >> 1) + 4 * (lane >> 4);
        const uint32_t aoff = sb + pw * 4096 + (r7 + 8 * (lane & 1)) * 128 + (((lane >> 3) & 1) ^ r7 ^ ((lane & 1) << 2)) * 16;
        const uint32_t obaddr = pin(sb + SM_OB + pw * 256 + (g & 1) * 64 + t * 16), tt = pin(t);
        uint32_t a0[2][4][4], a1[2][4][4];
        frag32<3, slot_of(NSTAGE)>(a0, aoff);
#pragma unroll
        for (int m = 0; m < 4; m++) mma16816(c[m], a0[0][m], h0.x, h0.y);
        if (pw < 3) {
#pragma unroll
            for (int m = 0; m < 4; m++) mma16816(c[m], a0[1][m], h1.x, h1.y);
        }
        frag32<2, slot_of(NSTAGE + 1)>(a1, aoff);
        bar_sync(BAR_OB + pw, 96);
        const uint4 ob0 = lds128(obaddr), ob1 = lds128(obaddr + 128);
        mma32(c, a1, ob0);
        asm volatile("cp.async.wait_group 1;" ::: "memory");
        __syncwarp();
#pragma unroll
        for (int m = 0; m < 4; m++) ldsm4t((aoff ^ (m * 32)) + slot_of(NSTAGE + 2), a0[0][m]);
#pragma unroll
        for (int m = 0; m < 4; m++) mma16816(c[m], a0[0][m], ob1.x, ob1.y);
        asm volatile("cp.async.wait_group 0;" ::: "memory");
        __syncwarp();
#pragma unroll
        for (int m = 0; m < 4; m++) ldsm4t((aoff ^ (m * 32)) + slot_of(NSTAGE + 2) + 2048, a0[1][m]);
#pragma unroll
        for (int m = 0; m < 4; m++) mma16816(c[m], a0[1][m], ob1.z, ob1.w);
        asm volatile("st.async.weak.shared::cluster.mbarrier::complete_tx::bytes.v4.f32 [%0], {%1,%2,%3,%4}, [%5];"
                     :: "r"(rdst), "f"(sel4(c[0], tt)), "f"(sel4(c[1], tt)), "f"(sel4(c[2], tt)), "f"(sel4(c[3], tt)), "r"(rbar) : "memory");
    } else if (warp == 12) {
        const uint32_t tag = (*reinterpret_cast<const uint32_t*>(smem + SM_X + 1792) + 1) & 1;
        if ((cta & 3) == 0) {
#pragma unroll 1
            for (int i = 0; i < 4; i++) {
                uint32_t sum = 0;
#pragma unroll
                for (int k = 0; k < NM; k++) {
                    mbar_wait(full0 + (MEND - NM + 1 + k + 7 * i) * 8);
                    sum += clk.now() - t0;
                }
                if (lane < 4) st_pub2(&scr->prog[i * 128 + cta + lane], ((t0 + sum / NM) & ~1u) | tag, (t0 & ~1u) | tag);
            }
        }
        mbar_wait(full0 + (S_V + HID_ST + 6) * 8);
        const uint4* hp = scr->hid + rk * 56 + lane;
        uint4 h0, h1;
        int it = 0;
        do {
            h0 = ld_poll2x64(hp); h1 = ld_poll2x64(hp + (lane < 24 ? 32 : 0));
            if (++it > SPIN_LIMIT) __trap();
        } while (warp_bad(bad2(h0.x, h0.z, tag) | bad2(h1.x, h1.z, tag)));
        *reinterpret_cast<uint2*>(smem + SM_HID + lane * 8) = make_uint2(h0.y, h0.w);
        *reinterpret_cast<uint2*>(smem + SM_HID + 256 + lane * 8) = make_uint2(h1.y, h1.w);
        bar_arrive(BAR_H, 160);
    } else if (warp == 13) {
        const uint32_t tag = (*reinterpret_cast<const uint32_t*>(smem + SM_X + 1792) + 1) & 1;
#pragma unroll 1
        for (int i = 0; i < 4; i++) {
            mbar_wait(full0 + (MEND + MGAP + 7 * i) * 8);
            uint2 v;
            int it = 0;
            do {
                v = ld_poll2(&scr->prog[i * 128 + min(lane, 27) * 4]);
                if (++it > SPIN_LIMIT) __trap();
            } while (warp_bad(bad2(v.x, v.y, tag)));
            const int nom = i == 0 ? M_NOM0 : i == 1 ? M_NOM1 : i == 2 ? M_NOM2 : M_NOM3;
            int base = __reduce_add_sync(0xffffffffu, lane < 28 ? min(max((int)(v.x - t0), 0), 1 << 20) : 0) / 28 - nom;
            const int start = __reduce_add_sync(0xffffffffu, lane < 28 ? min(max((int)(v.y - t0), -(1 << 20)), 1 << 20) : 0) / 28;
            const int lag = max(lane == 0 ? base - start - SLACK : min(base - start, 2 * (base - start - DEAD)), 0);
            const int ahead = (lane == 0 ? nom : lane == 1 ? LATE_T : E2_T) - nom;
            const float rate = fminf(__fdividef((float)lag, (float)(nom - 500)), 0.045f);
            if (lane < 3) reinterpret_cast<volatile uint32_t*>(smem + SM_T0)[lane] = t0 + start + lag + (int)(rate * (float)ahead);
        }
    }
    if ((warp == 12 || warp == 13) && (rk & 1) == 0) {
        const int oidx = ((lane >> 2) & 1) * D_MODEL + cl * 64 + (lane & 3) * 16 + (rk >> 1) + (warp & 1) * 8;
        const float xv = __bfloat162float(reinterpret_cast<const __nv_bfloat16*>(smem + SM_X)[oidx]);
        __nv_bfloat16* optr = pin(out + oidx);
        const uint32_t in = pin(sb + SM_IN + (lane >> 3) * 64 + ((warp ^ (lane >> 4)) & 1) * 32 + (lane & 7) * 4);
#pragma unroll 1
        for (int pass = 0; pass < 2; pass++) {
            float v[16];
            mbar_wait(full0 + (pass ? B_FIN : B_X) * 8);
#pragma unroll
            for (int i = 0; i < 16; i++) v[i] = lds32(in + i * 256);
#pragma unroll
            for (int i = 0; i < 16; i += 4) v[i] = (v[i] + v[i + 1]) + (v[i + 2] + v[i + 3]);
            float r = (v[0] + v[4]) + (v[8] + v[12]);
            r += __shfl_xor_sync(0xffffffffu, r, 8);
            r += __shfl_xor_sync(0xffffffffu, r, 16);
            asm volatile("{\n.reg .pred p;\nsetp.ne.u32 p, %2, 0;\n@p st.global.u16 [%0], %1;\n}"
                         :: "l"(optr), "h"(__bfloat16_as_ushort(__float2bfloat16_rn(xv + r))), "r"(pass) : "memory");
        }
    }
}

namespace flat {

constexpr int F_PACE_DT = 640, F_PACE_LEAD = 350, F_LATE_T = 22330, F_LATE_DT = 460, F_Q_T = 4000, F_E2_T = 24130, F_E3_T = 24860;
constexpr int F_NOM0 = 4595, F_NOM1 = 8450, F_NOM2 = 12800, F_NOM3 = 17010;
constexpr int F_MEND = 5, F_MGAP = 3;
constexpr int NCTA = 128, NFFN = 112, NRED = 56, NTHREADS = 512;
constexpr int S_K = 0, S_V = 16, NSTAGE = 32;
constexpr int S_GU = NS, FFN_ST = 8, HID_ST = 11;
constexpr int SM_H = SM_WGT;

__device__ __forceinline__ uint4 ld_poll4(const void* p) {
    uint4 v;
    asm volatile("ld.relaxed.gpu.global.v4.u32 {%0,%1,%2,%3}, [%4];" : "=r"(v.x), "=r"(v.y), "=r"(v.z), "=r"(v.w) : "l"(p) : "memory");
    return v;
}
__device__ __forceinline__ void st_pub2x64(void* p, uint32_t a, uint32_t b, uint32_t c, uint32_t d) {
    asm volatile("{\n.reg .b64 d, e;\nmov.b64 d, {%1,%2};\nmov.b64 e, {%3,%4};\nst.relaxed.gpu.global.v2.b64 [%0], {d,e};\n}"
                 :: "l"(p), "r"(a), "r"(b), "r"(c), "r"(d) : "memory");
}
#define POLL_HEAD(P, T, N)                                                                                        \
    ".reg .pred p0, p1, p2, p3, q;\n"                                                                             \
    ".reg .b32 a, m, it, y<16>;\n"                                                                                \
    ".reg .b64 d<8>;\n"                                                                                           \
    "setp.eq.u32 p0, 0, 0;\nsetp.eq.u32 p1, 0, 0;\nsetp.eq.u32 p2, 0, 0;\nsetp.eq.u32 p3, 0, 0;\n"                \
    "mov.u32 it, " N ";\n"                                                                                        \
    "POLL_LOOP:\n"                                                                                                \
    "@p0 ld.relaxed.gpu.global.v2.b64 {d0,d1}, [" P "];\n"                                                        \
    "@p1 ld.relaxed.gpu.global.v2.b64 {d2,d3}, [" P "+512];\n"                                                    \
    "@p2 ld.relaxed.gpu.global.v2.b64 {d4,d5}, [" P "+1024];\n"                                                   \
    "@p3 ld.relaxed.gpu.global.v2.b64 {d6,d7}, [" P "+1536];\n"                                                   \
    "sub.u32 it, it, 1;\n"                                                                                        \
    "min.u32 m, it, 1;\n"                                                        \
    "mov.b64 {y0,y1}, d0;\nmov.b64 {y2,y3}, d1;\nmov.b64 {y4,y5}, d2;\nmov.b64 {y6,y7}, d3;\n"                    \
    "mov.b64 {y8,y9}, d4;\nmov.b64 {y10,y11}, d5;\nmov.b64 {y12,y13}, d6;\nmov.b64 {y14,y15}, d7;\n"              \
    "xor.b32 y0, y0, " T ";\nxor.b32 y2, y2, " T ";\nlop3.b32 a, y0, y2, m, 0xA8;\nsetp.ne.u32 p0, a, 0;\n"       \
    "xor.b32 y4, y4, " T ";\nxor.b32 y6, y6, " T ";\nlop3.b32 a, y4, y6, m, 0xA8;\nsetp.ne.u32 p1, a, 0;\n"       \
    "xor.b32 y8, y8, " T ";\nxor.b32 y10, y10, " T ";\nlop3.b32 a, y8, y10, m, 0xA8;\nsetp.ne.u32 p2, a, 0;\n"    \
    "xor.b32 y12, y12, " T ";\nxor.b32 y14, y14, " T ";\nlop3.b32 a, y12, y14, m, 0xA8;\nsetp.ne.u32 p3, a, 0;\n" \
    "or.pred q, p0, p1;\nor.pred q, q, p2;\nor.pred q, q, p3;\nvote.sync.any.pred q, q, 0xffffffff;\n"
#define POLL_TAIL "@q bra POLL_LOOP;\n"

__device__ __forceinline__ void poll4(float (&f)[2][4], const uint4* p, uint32_t tag, const float (&w)[4]) {
    asm volatile("{\n" POLL_HEAD("%8", "%9", "%14") POLL_TAIL
                 "mul.f32 %0, y0, %10;\nmul.f32 %1, y1, %10;\nmul.f32 %2, y2, %10;\nmul.f32 %3, y3, %10;\n"
                 "mul.f32 %4, y8, %12;\nmul.f32 %5, y9, %12;\nmul.f32 %6, y10, %12;\nmul.f32 %7, y11, %12;\n"
                 "fma.rn.f32 %0, y4, %11, %0;\nfma.rn.f32 %1, y5, %11, %1;\nfma.rn.f32 %2, y6, %11, %2;\nfma.rn.f32 %3, y7, %11, %3;\n"
                 "fma.rn.f32 %4, y12, %13, %4;\nfma.rn.f32 %5, y13, %13, %5;\nfma.rn.f32 %6, y14, %13, %6;\nfma.rn.f32 %7, y15, %13, %7;\n"
                 "}"
                 : "=&f"(f[0][0]), "=&f"(f[0][1]), "=&f"(f[0][2]), "=&f"(f[0][3]), "=&f"(f[1][0]), "=&f"(f[1][1]), "=&f"(f[1][2]), "=&f"(f[1][3])
                 : "l"(p), "r"(tag), "f"(w[0]), "f"(w[1]), "f"(w[2]), "f"(w[3]), "n"(SPIN_LIMIT) : "memory");
}
__device__ __forceinline__ void poll4_sum(float (&keep)[2], float (&recv)[2], const uint4* p, uint32_t tag, uint32_t hi) {
    asm volatile("{\n.reg .pred h;\n.reg .f32 s<8>;\nsetp.ne.u32 h, %6, 0;\n" POLL_HEAD("%4", "%5", "%7")
                 "add.f32 s0, y0, y4;\nadd.f32 s1, y1, y5;\nadd.f32 s2, y2, y6;\nadd.f32 s3, y3, y7;\n"
                 "add.f32 s4, y8, y12;\nadd.f32 s5, y9, y13;\nadd.f32 s6, y10, y14;\nadd.f32 s7, y11, y15;\n"
                 "add.f32 s0, s0, s4;\nadd.f32 s1, s1, s5;\nadd.f32 s2, s2, s6;\nadd.f32 s3, s3, s7;\n"
                 "selp.f32 s4, s0, s2, h;\nselp.f32 s5, s1, s3, h;\nselp.f32 %0, s2, s0, h;\nselp.f32 %1, s3, s1, h;\n"
                 "shfl.sync.bfly.b32 %2, s4, 16, 0x1f, 0xffffffff;\nshfl.sync.bfly.b32 %3, s5, 16, 0x1f, 0xffffffff;\n"
                 POLL_TAIL "}"
                 : "=&f"(keep[0]), "=&f"(keep[1]), "=&f"(recv[0]), "=&f"(recv[1])
                 : "l"(p), "r"(tag), "r"(hi), "n"(SPIN_LIMIT) : "memory");
}

struct Prod {
    uint32_t sb, kvdst, sdst;
    const char *k, *v;
    const __nv_bfloat16* gu;
    bool ffn;
};
__host__ __device__ constexpr int bytes_before(int s) { return 28672 + s * 16384 + (s <= S_GU ? 0 : s < S_GU + 14 ? s - S_GU : 14) * 1792; }
__host__ __device__ constexpr int issue_time(int s) {
    return (int)((long long)bytes_before(s) * F_PACE_DT / 16384) - F_PACE_LEAD;
}

template <int S, class CLK>
__device__ __forceinline__ void produce(Prod& p, const CLK& clk) {
    if constexpr (S < NSTAGE) {
        if constexpr (S >= NS) mbar_wait(p.sb + SM_BAR + (NBAR + S - NS) * 8);
        clk.wait_base(p.sb, 0, issue_time(S));
        const char* src = (S < S_V ? p.k : p.v) + (S & 15) * (8 * SLOT);
#pragma unroll
        for (int i = 0; i < 8; i++) cp_async16((p.kvdst ^ ((i & 1) * 64)) + slot_of(S) + i * 2048, src + i * 2048);
        if constexpr (S >= S_GU && S < S_GU + 14) {
            if (p.ffn) cp_async16_strip(p.sdst + (S - S_GU) * 2048, p.gu + (size_t)(S - S_GU) * 32 * FF);
        }
        cp_async_arrive(p.sb + SM_BAR + S * 8);
        produce<S + 1>(p, clk);
    }
}

template <int PENDING, int OFF>
__device__ __forceinline__ void frag16(uint32_t (&a)[4][4], uint32_t addr) {
    asm volatile("cp.async.wait_group %0;" :: "n"(PENDING) : "memory");
    __syncwarp();
#pragma unroll
    for (int m = 0; m < 4; m++) ldsm4t((addr ^ (m * 32)) + OFF, a[m]);
}

enum { BAR_OB = 1, BAR_CONS = 2, BAR_LN = 3, BAR_FF = 4, BAR_FIN = 5, BAR_H = 6 };

template <bool SCALED>
__global__ void __launch_bounds__(NTHREADS, 1)
flat_decode_kernel(const __nv_bfloat16* __restrict__ wq, const __nv_bfloat16* __restrict__ kc, const __nv_bfloat16* __restrict__ x,
                    Scratch* __restrict__ scr, const __nv_bfloat16* __restrict__ vc, const __nv_bfloat16* __restrict__ wo,
                    const __nv_bfloat16* __restrict__ wg, const __nv_bfloat16* __restrict__ wu, const __nv_bfloat16* __restrict__ wd,
                    __nv_bfloat16* __restrict__ out, const Clock<SCALED> clk) {
    extern __shared__ __align__(128) unsigned char smem[];
    const uint32_t sb = (uint32_t)__cvta_generic_to_shared(smem);
    const int tid = threadIdx.x, lane = tid & 31;
    const int cta = blockIdx.x;
    const uint32_t full0 = sb + SM_BAR, done0 = full0 + NBAR * 8;
    const uint32_t t0 = clk.now();
    if (tid < 224) {
        const int row = (tid >> 5) * 64 + (lane >> 2);
        const char* src = reinterpret_cast<const char*>(wq) + (uint32_t)(row * (QCOLS * 2) + cta * 64 + (lane & 3) * 16);
        const uint32_t dst = sb + SM_STRIP + row * 64 + ((lane & 3) ^ (lane >> 3)) * 16;
#pragma unroll
        for (int i = 0; i < 8; i++) cp_async16_strip(dst + i * 512, src + i * (8 * QCOLS * 2));
    }
    const int warp = __shfl_sync(0xffffffffu, tid >> 5, 0);
    const int hkv = cta >> 4, j = cta & 15, bat = j >> 3, sp = j & 7;
    const int g = lane >> 2, t = lane & 3;

    if (warp < 8) {
        if (tid == 224) load_x(sb, x, &scr->epoch[cta * 8]);
        __syncthreads();
        mbar_wait(full0 + B_X * 8);
        const uint32_t epoch = *reinterpret_cast<const uint32_t*>(smem + SM_X + 1792);
        const uint32_t tag = pin((epoch + 1) & 1);
        uint32_t* qdst = reinterpret_cast<uint32_t*>(scr->q) + (hkv * 2 + (t & 1)) * 512 + j * 32 + warp * 16 + g + 8 * (t >> 1);
        if (warp == 7) {
            layernorm(smem, lane, 0, 2);
            bar_arrive(BAR_LN, 256);
        } else {
            asm volatile("cp.async.wait_all;" ::: "memory");
            bar_sync(BAR_LN, 256);
            strip_partial(sb, SM_STRIP, smem, warp, lane);
        }
        bar_sync(BAR_CONS, 256);
        if (warp < 2) {
            st_pub1(qdst, (pack_bf(0.f, strip_sum(smem, tid)) & 0xffff0000u) | tag);
        } else if (warp >= 4) {
            const int i = tid - 128;
            const uint4* qp = reinterpret_cast<const uint4*>(scr->q) + (hkv * 2 + bat) * 128 + i;
            clk.wait_until(t0, F_Q_T);
            uint4 v;
            int it = 0;
            do {
                v = ld_poll4(qp);
                if (++it > SPIN_LIMIT) __trap();
            } while (warp_bad(bad4(v, tag)));
            *reinterpret_cast<uint2*>(smem + SM_Q + (i >> 6) * 528 + (i & 63) * 8) =
                make_uint2(__byte_perm(v.x, v.y, 0x7632), __byte_perm(v.z, v.w, 0x7632));
        }
        bar_sync(BAR_CONS, 256);
        if (tid == 96) scr->epoch[cta * 8] = epoch + 1;
        {
            uint32_t qf[8][4];
#pragma unroll
            for (int k2 = 0; k2 < 8; k2++) ldsm4(sb + SM_Q + (lane & 1) * 528 + k2 * 64 + (lane >> 3) * 16, qf[k2]);
            const int mt = warp & 1;
            const uint32_t aoff = (16 * mt + (lane & 15)) * 512 + ((lane >> 4) ^ (lane & 7)) * 16;
            float* sc = reinterpret_cast<float*>(smem + SM_S) + (t & 1) * SROW + (g >> 1) * 8 + (2 * mt + (t >> 1)) * 2 + (g & 1);
#pragma unroll 1
            for (int k = warp >> 1; k < 16; k += 4) {
                const int s = S_K + k;
                mbar_wait(full0 + s * 8);
                const uint32_t base = sb + SM_RING + (s >= NS ? s - NS : s) * SLOT + aoff;
                float c0[4] = {0.f, 0.f, 0.f, 0.f}, c1[4] = {0.f, 0.f, 0.f, 0.f};
#pragma unroll
                for (int k2 = 0; k2 < 8; k2++) {
                    uint32_t a0[4], a1[4];
                    ldsm4((base ^ ((k2 & 1) * 64)) + (k2 >> 1) * 128, a0);
                    ldsm4((base ^ ((k2 & 1) * 64 + 32)) + (k2 >> 1) * 128, a1);
                    mma16816(c0, a0, qf[k2][0], qf[k2][1]);
                    mma16816(c1, a1, qf[k2][2], qf[k2][3]);
                }
                __syncwarp();
                if (lane == 0) mbar_arrive(done0 + s * 8, 4);
                sc[k * 32] = rbf(sel4(c0, t) + sel4(c1, t));
            }
        }
        bar_sync(BAR_CONS, 256);
        {
            constexpr float C = SCALE_LOG2E;
            const float* sc = reinterpret_cast<const float*>(smem + SM_S);
            float* stat = reinterpret_cast<float*>(smem + SM_STAT);
            const float2 s0 = *reinterpret_cast<const float2*>(sc + 2 * tid);
            const float2 s1 = *reinterpret_cast<const float2*>(sc + SROW + 2 * tid);
            float m0 = fmaxf(s0.x, s0.y), m1 = fmaxf(s1.x, s1.y);
#pragma unroll
            for (int o = 16; o > 0; o >>= 1) {
                m0 = fmaxf(m0, __shfl_xor_sync(0xffffffffu, m0, o));
                m1 = fmaxf(m1, __shfl_xor_sync(0xffffffffu, m1, o));
            }
            if (lane == 0) *reinterpret_cast<float2*>(stat + warp * 2) = make_float2(m0, m1);
            bar_sync(BAR_CONS, 256);
#pragma unroll
            for (int w = 0; w < 8; w++) {
                const float2 mm = *reinterpret_cast<const float2*>(stat + w * 2);
                m0 = fmaxf(m0, mm.x); m1 = fmaxf(m1, mm.y);
            }
            const float p00 = ex2((s0.x - m0) * C), p01 = ex2((s0.y - m0) * C);
            const float p10 = ex2((s1.x - m1) * C), p11 = ex2((s1.y - m1) * C);
            uint32_t* ps = reinterpret_cast<uint32_t*>(smem + SM_P);
            ps[tid] = pack_bf(p00, p01);
            ps[PROW + tid] = pack_bf(p10, p11);
            float l0 = p00 + p01, l1 = p10 + p11;
#pragma unroll
            for (int o = 16; o > 0; o >>= 1) {
                l0 += __shfl_xor_sync(0xffffffffu, l0, o);
                l1 += __shfl_xor_sync(0xffffffffu, l1, o);
            }
            if (lane == 0) *reinterpret_cast<float2*>(stat + 16 + warp * 2) = make_float2(l0, l1);
            bar_sync(BAR_CONS, 256);
            if (tid < 4) {
                float l = 0.f;
#pragma unroll
                for (int w = 0; w < 8; w++) l += stat[16 + w * 2 + (tid & 1)];
                st_pub2(scr->ml + cta * 4 + tid, tagf((tid & 1) ? m1 : m0, tag), tagf(l, tag));
            }
        }
        float wgt[2] = {0.f, 0.f}, own = 0.f;
        {
            float o0[4] = {0.f, 0.f, 0.f, 0.f}, o1[4] = {0.f, 0.f, 0.f, 0.f};
            float o2[4] = {0.f, 0.f, 0.f, 0.f}, o3[4] = {0.f, 0.f, 0.f, 0.f};
            const uint32_t aoff = ((lane & 7) + (lane >> 4) * 8) * 512 + ((warp * 4 + ((lane >> 3) & 1) * 2) ^ (lane & 7)) * 16;
            const uint4* ps = reinterpret_cast<const uint4*>(smem + SM_P + (g & 1) * PROW * 4) + t;
            uint32_t* dst = reinterpret_cast<uint32_t*>(scr->part) + ((size_t)(hkv * 16 + (t & 1) * 8 + warp) * 16 + j) * 32 +
                            (4 * (g & 3) + (t & 2) + (g >> 2)) * 2;
#pragma unroll
            for (int k = 0; k < 16; k++) {
                const uint4 pa = ps[k * 4];
                mbar_wait(full0 + (S_V + k) * 8);
                uint32_t a[4][4];
#pragma unroll
                for (int i = 0; i < 4; i++) ldsm4t(sb + (aoff ^ ((i & 1) * 16)) + slot_of(S_V + k) + (i >> 1) * 8192, a[i]);
                mma16816(o0, a[0], pa.x, pa.y);
                mma16816(o1, a[1], pa.x, pa.y);
                mma16816(o2, a[2], pa.z, pa.w);
                mma16816(o3, a[3], pa.z, pa.w);
                if (S_V + k + NS < NSTAGE + 3) {
                    __syncwarp();
                    if (lane == 0) mbar_arrive(done0 + (S_V + k) * 8, 1);
                }
                if (k == FFN_ST && warp < 7) {
                    strip_partial(sb, SM_STRIP, smem, warp, lane);
                    bar_arrive(BAR_FF, 256);
                }
                if (k == FFN_ST && warp == 7) {
                    bar_sync(BAR_FF, 256);
                    own = rbf(strip_sum(smem, (cta & 1) * 32 + lane));
                    st_pub1(scr->gu + (cta ^ 1) * 32 + lane, (pack_bf(0.f, strip_sum(smem, (~cta & 1) * 32 + lane)) & 0xffff0000u) | tag);
                }
                if (k == HID_ST && warp == 7) {
                    const uint2* mlp = scr->ml + (hkv * 16 + g) * 4 + (j >> 3);
                    uint2 a, b;
                    uint32_t other;
                    int it = 0;
                    do {
                        a = ld_poll2(mlp); b = ld_poll2(mlp + 32); other = ld_poll1(scr->gu + cta * 32 + lane);
                        if (++it > SPIN_LIMIT) __trap();
                    } while (warp_bad(bad2(a.x, a.y, tag) | bad2(b.x, b.y, tag) | (other ^ tag)));
                    float m[2] = {bf_hi(a.x), bf_hi(b.x)};
                    float l[2] = {__uint_as_float(a.y ^ tag), __uint_as_float(b.y ^ tag)};
#pragma unroll
                    for (int bb = 0; bb < 2; bb++) {
                        float M = m[bb];
                        M = fmaxf(M, __shfl_xor_sync(0xffffffffu, M, 4));
                        M = fmaxf(M, __shfl_xor_sync(0xffffffffu, M, 8));
                        M = fmaxf(M, __shfl_xor_sync(0xffffffffu, M, 16));
                        const float e = ex2((m[bb] - M) * SCALE_LOG2E);
                        float L = e * l[bb];
                        L += __shfl_xor_sync(0xffffffffu, L, 4);
                        L += __shfl_xor_sync(0xffffffffu, L, 8);
                        L += __shfl_xor_sync(0xffffffffu, L, 16);
                        wgt[bb] = __fdividef(e, L);
                    }
                    float ga = (cta & 1) ? bf_hi(other) : own;
                    ga *= (ga > 0.f ? 1.f : 0.f);
                    const float hv = ga * ((cta & 1) ? own : bf_hi(other));
                    const uint32_t w = pack_bf(hv, __shfl_xor_sync(0xffffffffu, hv, 2));
                    if (!(t & 2)) reinterpret_cast<uint32_t*>(smem + SM_H)[(t & 1) * 8 + (g & 3) * 2 + (g >> 2)] = w;
                    bar_arrive(BAR_H, 256);
                }
            }
            const float v0 = sel4(o0, t) + sel4(o2, t), v1 = sel4(o1, t) + sel4(o3, t);
            st_pub64(dst, tagf(v0, tag), __float_as_uint(v1));
        }
        if (warp == 7) {
            const uint4* pp = pin(scr->part + (size_t)cta * 128 + lane);
            const uint32_t obaddr = pin(sb + SM_OB + (lane >> 4) * 64 + (lane & 7) * 8 + ((lane >> 3) & 1) * 4), ll = pin(lane);
            float w[4];
#pragma unroll
            for (int i = 0; i < 4; i++) w[i] = __shfl_sync(0xffffffffu, wgt[i >> 1], ((i & 1) * 4 + (lane >> 3)) * 4);
            clk.wait_until(clk.base(sb, 2), F_E2_T);
            float f[2][4];
            poll4(f, pp, tag, w);
            const bool h16 = ll & 16, h8 = ll & 8;
            float r4[4], r2[2];
#pragma unroll
            for (int e = 0; e < 4; e++) r4[e] = (h16 ? f[1][e] : f[0][e]) + __shfl_xor_sync(0xffffffffu, h16 ? f[0][e] : f[1][e], 16);
#pragma unroll
            for (int e = 0; e < 2; e++) r2[e] = (h8 ? r4[2 + e] : r4[e]) + __shfl_xor_sync(0xffffffffu, h8 ? r4[e] : r4[2 + e], 8);
            sts32(obaddr, pack_bf(r2[0], r2[1]));
            bar_arrive(BAR_OB, 256);
        } else if (warp < 4 && (cta & 1) == 0 && cta < 2 * NRED) {
            const uint4* op = pin(scr->outp + (size_t)(cta >> 1) * (NCTA * 4) + warp * 128 + lane);
            const int oidx = (t & 1) * D_MODEL + hkv * 64 + (lane >> 3) * 16 + (j >> 1) + (t >> 1) * 8;
            const float xv = __bfloat162float(reinterpret_cast<const __nv_bfloat16*>(smem + SM_X)[oidx]);
            __nv_bfloat16* optr = pin(out + oidx);
            const uint32_t red = pin(sb + SM_S + tid * 4), ll = pin(lane);
            float r2[2], rcv[2];
            const bool h8 = ll & 8;
            clk.wait_until(clk.base(sb, 3), F_E3_T);
            poll4_sum(r2, rcv, op, tag, ll & 16);
            r2[0] += rcv[0]; r2[1] += rcv[1];
            float r = (h8 ? r2[1] : r2[0]) + __shfl_xor_sync(0xffffffffu, h8 ? r2[0] : r2[1], 8);
            r += __shfl_xor_sync(0xffffffffu, r, 4);
            if (warp != 0) {
                sts32(red, __float_as_uint(r));
                bar_arrive(BAR_FIN, 128);
            } else {
                bar_sync(BAR_FIN, 128);
                r = ((xv + r) + lds32(red + 128)) + (lds32(red + 256) + lds32(red + 384));
                asm volatile("st.global.u16 [%0], %1;" :: "l"(optr), "h"(__bfloat16_as_ushort(__float2bfloat16_rn(r))) : "memory");
            }
        }
    } else if (warp < 15) {
        const int pt = tid - 256, pw = warp - 8;
        const char* pdn = reinterpret_cast<const char*>(wd) + (size_t)cta * 14336 + (lane >> 3) * 896 + pw * 128 + (lane & 7) * 16;
        const char* pwo = reinterpret_cast<const char*>(wo) + (size_t)cta * 28672 + (lane >> 3) * 896 + pw * 128 + (lane & 7) * 16;
        if (pw < 4) {
            if (lane == 0) {
#pragma unroll
                for (int i = 0; i < 10; i++) {
                    if (pw * 10 + i != B_X) mbar_init(full0 + (pw * 10 + i) * 8, NPT);
                    mbar_init(done0 + (pw * 10 + i) * 8, 8);
                }
            }
            Prod p;
            const size_t kvoff = ((size_t)(bat * 8 + hkv) * SK + (SK - WIN)) * DH * 2 + sp * SLOT + pt * 16;
            p.sb = sb;
            p.kvdst = (sb + pt * 16) ^ (pw * 16);
            p.sdst = sb + SM_STRIP + (pt >> 2) * 64 + ((pt & 3) ^ ((pt >> 3) & 3)) * 16;
            p.k = reinterpret_cast<const char*>(kc) + kvoff;
            p.v = reinterpret_cast<const char*>(vc) + kvoff;
            p.gu = ((cta & 1) ? wu : wg) + (cta >> 1) * 32 + (pt & 3) * 8 + (size_t)(pt >> 2) * FF;
            p.ffn = cta < NFFN;
            __syncthreads();
            produce<0>(p, clk);
        } else {
            __syncthreads();
        }
        mbar_wait(full0 + B_X * 8);
        const uint32_t tag = pin((*reinterpret_cast<const uint32_t*>(smem + SM_X + 1792) + 1) & 1);
        if (pw == 4 && (cta & 3) == 0) {
#pragma unroll 1
            for (int i = 0; i < 4; i++) {
                uint32_t sum = 0;
#pragma unroll
                for (int k = 0; k < NM; k++) {
                    mbar_wait(full0 + (F_MEND - NM + 1 + k + 6 * i) * 8);
                    sum += clk.now() - t0;
                }
                if (lane < 4) st_pub2(&scr->prog[i * 128 + cta + lane], ((t0 + sum / NM) & ~1u) | tag, (t0 & ~1u) | tag);
            }
        }
        mbar_wait(done0 + (NSTAGE + 2 - NS) * 8);
        const uint32_t ta = F_LATE_T, td = F_LATE_DT;
        uint4* odst = scr->outp + ((size_t)(pt >> 2) * NCTA + cta) * 4 + t;
        const uint32_t fdst = (sb + pw * 2048 + lane * 16) ^ ((lane >> 3) * 16);
        clk.wait_base(sb, 1, ta);
        if (cta < NFFN) fetch16(fdst + slot_of(NSTAGE), pdn);
        asm volatile("cp.async.commit_group;" ::: "memory");
        clk.wait_base(sb, 1, ta + td);
        fetch16(fdst + slot_of(NSTAGE + 1), pwo);
        asm volatile("cp.async.commit_group;" ::: "memory");
        clk.wait_base(sb, 1, ta + 2 * td);
        fetch16(fdst + slot_of(NSTAGE + 2), pwo + 14336);
        asm volatile("cp.async.commit_group;" ::: "memory");
        bar_sync(BAR_H, 256);
        const uint2 h = *reinterpret_cast<const uint2*>(smem + SM_H + (g & 1) * 32 + t * 8);
        float c[4][4];
#pragma unroll
        for (int m = 0; m < 4; m++)
#pragma unroll
            for (int e = 0; e < 4; e++) c[m][e] = 0.f;
        const int r7 = ((lane & 7) >> 1) + 4 * (lane >> 4);
        const uint32_t aoff = sb + pw * 2048 + (r7 + 8 * (lane & 1)) * 128 + (((lane >> 3) & 1) ^ r7 ^ ((lane & 1) << 2)) * 16;
        const uint32_t obaddr = pin(sb + SM_OB + (g & 1) * 64 + t * 16), tt = pin(t);
        uint32_t a0[4][4], a1[4][4];
        frag16<2, slot_of(NSTAGE)>(a0, aoff);
        if (cta < NFFN) {
#pragma unroll
            for (int m = 0; m < 4; m++) mma16816(c[m], a0[m], h.x, h.y);
        }
        frag16<1, slot_of(NSTAGE + 1)>(a1, aoff);
        bar_sync(BAR_OB, 256);
        const uint4 ob = lds128(obaddr);
#pragma unroll
        for (int m = 0; m < 4; m++) mma16816(c[m], a1[m], ob.x, ob.y);
        frag16<0, slot_of(NSTAGE + 2)>(a0, aoff);
#pragma unroll
        for (int m = 0; m < 4; m++) mma16816(c[m], a0[m], ob.z, ob.w);
        st_pub2x64(odst, tagf(sel4(c[0], tt), tag), __float_as_uint(sel4(c[1], tt)), tagf(sel4(c[2], tt), tag), __float_as_uint(sel4(c[3], tt)));
    } else if (warp == 15) {
        if (lane < 4) reinterpret_cast<uint32_t*>(smem + SM_T0)[lane] = t0;
        __syncthreads();
        mbar_wait(full0 + B_X * 8);
        const uint32_t tag = (*reinterpret_cast<const uint32_t*>(smem + SM_X + 1792) + 1) & 1;
#pragma unroll 1
        for (int i = 0; i < 4; i++) {
            mbar_wait(full0 + (F_MEND + F_MGAP + 6 * i) * 8);
            uint2 v;
            int it = 0;
            do {
                v = ld_poll2(&scr->prog[i * 128 + lane * 4]);
                if (++it > SPIN_LIMIT) __trap();
            } while (warp_bad(bad2(v.x, v.y, tag)));
            const int nom = i == 0 ? F_NOM0 : i == 1 ? F_NOM1 : i == 2 ? F_NOM2 : F_NOM3;
            int base = (__reduce_add_sync(0xffffffffu, min(max((int)(v.x - t0), 0), 1 << 20)) >> 5) - nom;
            const int start = __reduce_add_sync(0xffffffffu, min(max((int)(v.y - t0), -(1 << 20)), 1 << 20)) >> 5;
            const int lag = max(lane == 0 ? base - start - SLACK : min(base - start, 2 * (base - start - DEAD)), 0);
            const int ahead = (lane == 0 ? nom : lane == 1 ? F_LATE_T : lane == 2 ? F_E2_T : F_E3_T - 150) - nom;
            const float rate = fminf(__fdividef((float)lag, (float)(nom - 500)), 0.045f);
            if (lane < 4) reinterpret_cast<volatile uint32_t*>(smem + SM_T0)[lane] = t0 + start + lag + (int)(rate * (float)ahead);
        }
    }
}

}

}

extern "C" void kernel_launch(void* const* d_in, const int* in_sizes, int n_in, void* d_out, int out_size) {
    (void)in_sizes; (void)n_in; (void)out_size;
    cudaLaunchConfig_t cfg = {};
    cfg.gridDim = dim3(NCTA); cfg.blockDim = dim3(NTHREADS); cfg.dynamicSmemBytes = SM_TOTAL; cfg.stream = cudaStreamPerThread;
    cudaLaunchAttribute at[1];
    at[0].id = cudaLaunchAttributeClusterDimension;
    at[0].val.clusterDim.x = 16; at[0].val.clusterDim.y = 1; at[0].val.clusterDim.z = 1;
    cfg.attrs = at; cfg.numAttrs = 1;

    static Scratch* scr = nullptr;
    static uint32_t scale = 64;
    static int nclusters = 0;
    if (!scr) {
        int dev = 0, khz = 0, bits = 0;
        cudaGetDevice(&dev);
        cudaDeviceGetAttribute(&khz, cudaDevAttrMemoryClockRate, dev);
        cudaDeviceGetAttribute(&bits, cudaDevAttrGlobalMemoryBusWidth, dev);
        if (khz > 0 && bits > 0) scale = (uint32_t)(64.0 * khz * bits / (2619000.0 * 5120.0) + 0.5);
        cudaFuncSetAttribute(fused_decode_kernel<false>, cudaFuncAttributeMaxDynamicSharedMemorySize, SM_TOTAL);
        cudaFuncSetAttribute(fused_decode_kernel<true>, cudaFuncAttributeMaxDynamicSharedMemorySize, SM_TOTAL);
        cudaFuncSetAttribute(flat::flat_decode_kernel<true>, cudaFuncAttributeMaxDynamicSharedMemorySize, SM_TOTAL);
        cudaFuncSetAttribute(fused_decode_kernel<false>, cudaFuncAttributeNonPortableClusterSizeAllowed, 1);
        cudaFuncSetAttribute(fused_decode_kernel<true>, cudaFuncAttributeNonPortableClusterSizeAllowed, 1);
        if (cudaOccupancyMaxActiveClusters(&nclusters, fused_decode_kernel<true>, &cfg) != cudaSuccess) nclusters = 0;
        (void)cudaGetLastError();
        cudaGetSymbolAddress(reinterpret_cast<void**>(&scr), g_scratch);
    }
    typedef const __nv_bfloat16* P;
    const P wq = (P)d_in[3], kc = (P)d_in[1], x = (P)d_in[0], vc = (P)d_in[2], wo = (P)d_in[4], wg = (P)d_in[6], wu = (P)d_in[7], wd = (P)d_in[8];
    __nv_bfloat16* out = (__nv_bfloat16*)d_out;
    if (nclusters < NCTA / 16)
        flat::flat_decode_kernel<true><<<flat::NCTA, flat::NTHREADS, SM_TOTAL, cudaStreamPerThread>>>(wq, kc, x, scr, vc, wo, wg, wu, wd, out, Clock<true>{scale});
    else if (scale == 64)
        cudaLaunchKernelEx(&cfg, fused_decode_kernel<false>, wq, kc, x, scr, vc, wo, wg, wu, wd, out, Clock<false>{scale});
    else
        cudaLaunchKernelEx(&cfg, fused_decode_kernel<true>, wq, kc, x, scr, vc, wo, wg, wu, wd, out, Clock<true>{scale});
}
```
